```python
import torch

def _softmax(x, axis=-1):
    return torch.softmax(x, dim=axis)
def _gelu(x):
    return torch.nn.functional.gelu(x, approximate="tanh")
def _silu(x):
    return torch.nn.functional.silu(x)
def _sigmoid(x):
    return torch.sigmoid(x)
def _layernorm(x, axis=-1, eps=1e-5):
    m = x.mean(dim=axis, keepdim=True)
    v = x.var(dim=axis, keepdim=True, unbiased=False)
    return (x - m) / torch.sqrt(v + eps)
def _scatter_add(tgt, idx, src, axis=0):
    return tgt.clone().index_add_(axis, idx, src)
def _segment_sum(src, seg, n):
    out = torch.zeros((n,) + src.shape[1:], dtype=src.dtype)
    return out.index_add_(0, seg, src)
def _pad(x, pw):
    flat = tuple(v for pair in reversed(pw) for v in pair)
    return torch.nn.functional.pad(x, flat)

kernel_name = 'parallel_sum__softmax_full_mha__glu_gated_glu__prompt'

def setup_inputs():

    _w = (lambda a: (lambda t: t.to(torch.bfloat16) if t.is_floating_point() else t)(torch.as_tensor(a)))
    def _A_setup():
        B, S, D = 1, 2048, 576
        return {
            "x": _w((lambda *s: torch.randn(*s, dtype=torch.bfloat16) * 0.05)(B, S, D)),
            "wqkv": _w((lambda *s: torch.randn(*s, dtype=torch.bfloat16) * 0.2)(D, 3 * D)),
            "wo": _w((lambda *s: torch.randn(*s, dtype=torch.bfloat16) * 0.1)(D, D)),
        }
    _A_in = _A_setup()

    def _B_setup():
        B, S, D, F = 1, 2048, 576, 4608
        return {
            "x": _w((lambda *s: torch.randn(*s, dtype=torch.bfloat16) * 0.05)(B, S, D)),
            "w_gate": _w((lambda *s: torch.randn(*s, dtype=torch.bfloat16) * 0.8)(D, F)),
            "w_up": _w((lambda *s: torch.randn(*s, dtype=torch.bfloat16) * 0.1)(D, F)),
            "w_down": _w((lambda *s: torch.randn(*s, dtype=torch.bfloat16) * 0.1)(F, D)),
        }
    _B_in = _B_setup()

    return {
        "A_x": _A_in["x"],
        "A_wqkv": _A_in["wqkv"],
        "A_wo": _A_in["wo"],
        "B_x": _B_in["x"],
        "B_w_gate": _B_in["w_gate"],
        "B_w_up": _B_in["w_up"],
        "B_w_down": _B_in["w_down"],
    }

def reference(A_x, A_wqkv, A_wo, B_x, B_w_gate, B_w_up, B_w_down):
    def _A_ref(x, wqkv, wo):
        B, S, D = x.shape
        H = 32; Dh = D // H
        qkv = (lambda x, *d: x.permute(*d))((x @ wqkv).reshape(B, S, 3, H, Dh), 2, 0, 3, 1, 4)
        q, k, v = qkv[0], qkv[1], qkv[2]
        scale = Dh ** -0.5
        scores = torch.einsum("bhqd,bhkd->bhqk", q, k) * scale
        p = _softmax(scores, axis=-1)
        o = torch.einsum("bhqk,bhkd->bhqd", p, v)
        return (lambda x, *d: x.permute(*d))(o, 0, 2, 1, 3).reshape(B, S, D) @ wo

    def _B_ref(x, w_gate, w_up, w_down):
        g = torch.einsum("bsd,df->bsf", x, w_gate)
        u = torch.einsum("bsd,df->bsf", x, w_up)
        h = _sigmoid(g) * u
        return torch.einsum("bsf,fd->bsd", h, w_down)

    x = A_x
    xn = _layernorm(x, axis=-1)
    return x + _A_ref(xn, A_wqkv, A_wo) + _B_ref(xn, B_w_gate, B_w_up, B_w_down)
```

```cpp
#include <cuda_runtime.h>
#include <cuda.h>
#include <cuda_bf16.h>
#include <stdint.h>

namespace {

constexpr int SEQ = 2048, DM = 576, FF = 4608;
constexpr int NCTA = 128;

constexpr uint32_t SM_XN = 0;
constexpr uint32_t SM_RING = 147456;
constexpr uint32_t SM_KV = 212992;
constexpr uint32_t QST = 27648, BST = 16384, KVST = 5120, G2ST = 57344;
constexpr uint32_t SM_BAR = 232192;
constexpr uint32_t SM_TOTAL = 232448;
enum { B_QF = 0, B_QE = 3, B_BF = 6, B_BE = 10, B_GF = 14, B_GE = 17, B_KF = 20, B_KE = 23, B_SKV = 26, B_SH = 27, B_SO = 28, B_N = 29 };

constexpr uint32_t HI_SW128 = 0x40000040u;
constexpr uint32_t LO_A = 1u << 16;
constexpr uint32_t LO_B = 512u << 16;
constexpr uint32_t HI_R = 64u, LO_R = 8u << 16;
constexpr uint32_t HI_K = 40u, LO_K = 8u << 16;
constexpr uint32_t HI_V = 8u, LO_V = 40u << 16;

constexpr float QSCALE = 0.23570226039551584f * 1.4426950408889634f;
constexpr float MOFF = 90.f;

struct __align__(64) Params {
  CUtensorMap wqkv64, wqkv8, wg, wu, h, wd[2], o, wo[2];
  const __nv_bfloat16* x;
  __nv_bfloat16* out;
};

__device__ __align__(1024) __nv_bfloat16 g_H[SEQ * FF];
__device__ __align__(1024) __nv_bfloat16 g_O[SEQ * DM];
__device__ __align__(1024) uint32_t g_KV[32 * SEQ * 20];
__device__ __align__(1024) uint32_t g_Q[NCTA * 24 * 256];
__device__ __align__(1024) float4 g_P[32 * 16 * 9 * 256];
__device__ uint32_t g_flags[8 * 32 + NCTA * 32 * 3 + 32];
#define FLAG_KV(j) (&g_flags[(j) * 32])
#define FLAG_H(c) (&g_flags[8 * 32 + (c) * 32])
#define FLAG_O(c) (&g_flags[8 * 32 + NCTA * 32 + (c) * 32])
#define FLAG_P(c) (&g_flags[8 * 32 + NCTA * 64 + (c) * 32])
#define FLAG_DONE (&g_flags[8 * 32 + NCTA * 96])
#define STAMP(i)

template<uint32_t AHI, uint32_t BHI> __device__ __forceinline__ void wg_ss_n192(float* d, uint32_t a, uint32_t b) {
  asm volatile("{\n.reg .pred p;\n.reg .b64 da, db;\nsetp.ne.b32 p, 1, 0;\nmov.b64 da, {%96, %98};\nmov.b64 db, {%97, %99};\n"
    "wgmma.mma_async.sync.aligned.m64n192k16.f32.bf16.bf16 {%0, %1, %2, %3, %4, %5, %6, %7, %8, %9, %10, %11, %12, %13, %14, %15, %16, %17, %18, %19, %20, %21, %22, %23, %24, %25, %26, %27, %28, %29, %30, %31, %32, %33, %34, %35, %36, %37, %38, %39, %40, %41, %42, %43, %44, %45, %46, %47, %48, %49, %50, %51, %52, %53, %54, %55, %56, %57, %58, %59, %60, %61, %62, %63, %64, %65, %66, %67, %68, %69, %70, %71, %72, %73, %74, %75, %76, %77, %78, %79, %80, %81, %82, %83, %84, %85, %86, %87, %88, %89, %90, %91, %92, %93, %94, %95}, da, db, p, 1, 1, 0, 1;\n}\n"
    : "+f"(d[0]), "+f"(d[1]), "+f"(d[2]), "+f"(d[3]), "+f"(d[4]), "+f"(d[5]), "+f"(d[6]), "+f"(d[7]), "+f"(d[8]), "+f"(d[9]), "+f"(d[10]), "+f"(d[11]), "+f"(d[12]), "+f"(d[13]), "+f"(d[14]), "+f"(d[15]), "+f"(d[16]), "+f"(d[17]), "+f"(d[18]), "+f"(d[19]), "+f"(d[20]), "+f"(d[21]), "+f"(d[22]), "+f"(d[23]), "+f"(d[24]), "+f"(d[25]), "+f"(d[26]), "+f"(d[27]), "+f"(d[28]), "+f"(d[29]), "+f"(d[30]), "+f"(d[31]), "+f"(d[32]), "+f"(d[33]), "+f"(d[34]), "+f"(d[35]), "+f"(d[36]), "+f"(d[37]), "+f"(d[38]), "+f"(d[39]), "+f"(d[40]), "+f"(d[41]), "+f"(d[42]), "+f"(d[43]), "+f"(d[44]), "+f"(d[45]), "+f"(d[46]), "+f"(d[47]), "+f"(d[48]), "+f"(d[49]), "+f"(d[50]), "+f"(d[51]), "+f"(d[52]), "+f"(d[53]), "+f"(d[54]), "+f"(d[55]), "+f"(d[56]), "+f"(d[57]), "+f"(d[58]), "+f"(d[59]), "+f"(d[60]), "+f"(d[61]), "+f"(d[62]), "+f"(d[63]), "+f"(d[64]), "+f"(d[65]), "+f"(d[66]), "+f"(d[67]), "+f"(d[68]), "+f"(d[69]), "+f"(d[70]), "+f"(d[71]), "+f"(d[72]), "+f"(d[73]), "+f"(d[74]), "+f"(d[75]), "+f"(d[76]), "+f"(d[77]), "+f"(d[78]), "+f"(d[79]), "+f"(d[80]), "+f"(d[81]), "+f"(d[82]), "+f"(d[83]), "+f"(d[84]), "+f"(d[85]), "+f"(d[86]), "+f"(d[87]), "+f"(d[88]), "+f"(d[89]), "+f"(d[90]), "+f"(d[91]), "+f"(d[92]), "+f"(d[93]), "+f"(d[94]), "+f"(d[95])
    : "r"(a), "r"(b), "n"(AHI), "n"(BHI));
}
template<uint32_t AHI, uint32_t BHI> __device__ __forceinline__ void wg_ss_z_n192(float* d, uint32_t a, uint32_t b) {
  asm volatile("{\n.reg .pred p;\n.reg .b64 da, db;\nsetp.ne.b32 p, 0, 0;\nmov.b64 da, {%96, %98};\nmov.b64 db, {%97, %99};\n"
    "wgmma.mma_async.sync.aligned.m64n192k16.f32.bf16.bf16 {%0, %1, %2, %3, %4, %5, %6, %7, %8, %9, %10, %11, %12, %13, %14, %15, %16, %17, %18, %19, %20, %21, %22, %23, %24, %25, %26, %27, %28, %29, %30, %31, %32, %33, %34, %35, %36, %37, %38, %39, %40, %41, %42, %43, %44, %45, %46, %47, %48, %49, %50, %51, %52, %53, %54, %55, %56, %57, %58, %59, %60, %61, %62, %63, %64, %65, %66, %67, %68, %69, %70, %71, %72, %73, %74, %75, %76, %77, %78, %79, %80, %81, %82, %83, %84, %85, %86, %87, %88, %89, %90, %91, %92, %93, %94, %95}, da, db, p, 1, 1, 0, 1;\n}\n"
    : "=f"(d[0]), "=f"(d[1]), "=f"(d[2]), "=f"(d[3]), "=f"(d[4]), "=f"(d[5]), "=f"(d[6]), "=f"(d[7]), "=f"(d[8]), "=f"(d[9]), "=f"(d[10]), "=f"(d[11]), "=f"(d[12]), "=f"(d[13]), "=f"(d[14]), "=f"(d[15]), "=f"(d[16]), "=f"(d[17]), "=f"(d[18]), "=f"(d[19]), "=f"(d[20]), "=f"(d[21]), "=f"(d[22]), "=f"(d[23]), "=f"(d[24]), "=f"(d[25]), "=f"(d[26]), "=f"(d[27]), "=f"(d[28]), "=f"(d[29]), "=f"(d[30]), "=f"(d[31]), "=f"(d[32]), "=f"(d[33]), "=f"(d[34]), "=f"(d[35]), "=f"(d[36]), "=f"(d[37]), "=f"(d[38]), "=f"(d[39]), "=f"(d[40]), "=f"(d[41]), "=f"(d[42]), "=f"(d[43]), "=f"(d[44]), "=f"(d[45]), "=f"(d[46]), "=f"(d[47]), "=f"(d[48]), "=f"(d[49]), "=f"(d[50]), "=f"(d[51]), "=f"(d[52]), "=f"(d[53]), "=f"(d[54]), "=f"(d[55]), "=f"(d[56]), "=f"(d[57]), "=f"(d[58]), "=f"(d[59]), "=f"(d[60]), "=f"(d[61]), "=f"(d[62]), "=f"(d[63]), "=f"(d[64]), "=f"(d[65]), "=f"(d[66]), "=f"(d[67]), "=f"(d[68]), "=f"(d[69]), "=f"(d[70]), "=f"(d[71]), "=f"(d[72]), "=f"(d[73]), "=f"(d[74]), "=f"(d[75]), "=f"(d[76]), "=f"(d[77]), "=f"(d[78]), "=f"(d[79]), "=f"(d[80]), "=f"(d[81]), "=f"(d[82]), "=f"(d[83]), "=f"(d[84]), "=f"(d[85]), "=f"(d[86]), "=f"(d[87]), "=f"(d[88]), "=f"(d[89]), "=f"(d[90]), "=f"(d[91]), "=f"(d[92]), "=f"(d[93]), "=f"(d[94]), "=f"(d[95])
    : "r"(a), "r"(b), "n"(AHI), "n"(BHI));
}
template<uint32_t AHI, uint32_t BHI> __device__ __forceinline__ void wg_ss_n24(float* d, uint32_t a, uint32_t b) {
  asm volatile("{\n.reg .pred p;\n.reg .b64 da, db;\nsetp.ne.b32 p, 1, 0;\nmov.b64 da, {%12, %14};\nmov.b64 db, {%13, %15};\n"
    "wgmma.mma_async.sync.aligned.m64n24k16.f32.bf16.bf16 {%0, %1, %2, %3, %4, %5, %6, %7, %8, %9, %10, %11}, da, db, p, 1, 1, 0, 1;\n}\n"
    : "+f"(d[0]), "+f"(d[1]), "+f"(d[2]), "+f"(d[3]), "+f"(d[4]), "+f"(d[5]), "+f"(d[6]), "+f"(d[7]), "+f"(d[8]), "+f"(d[9]), "+f"(d[10]), "+f"(d[11])
    : "r"(a), "r"(b), "n"(AHI), "n"(BHI));
}
template<uint32_t AHI, uint32_t BHI> __device__ __forceinline__ void wg_ss_z_n24(float* d, uint32_t a, uint32_t b) {
  asm volatile("{\n.reg .pred p;\n.reg .b64 da, db;\nsetp.ne.b32 p, 0, 0;\nmov.b64 da, {%12, %14};\nmov.b64 db, {%13, %15};\n"
    "wgmma.mma_async.sync.aligned.m64n24k16.f32.bf16.bf16 {%0, %1, %2, %3, %4, %5, %6, %7, %8, %9, %10, %11}, da, db, p, 1, 1, 0, 1;\n}\n"
    : "=f"(d[0]), "=f"(d[1]), "=f"(d[2]), "=f"(d[3]), "=f"(d[4]), "=f"(d[5]), "=f"(d[6]), "=f"(d[7]), "=f"(d[8]), "=f"(d[9]), "=f"(d[10]), "=f"(d[11])
    : "r"(a), "r"(b), "n"(AHI), "n"(BHI));
}
template<uint32_t AHI, uint32_t BHI> __device__ __forceinline__ void wg_ss_n128(float* d, uint32_t a, uint32_t b) {
  asm volatile("{\n.reg .pred p;\n.reg .b64 da, db;\nsetp.ne.b32 p, 1, 0;\nmov.b64 da, {%64, %66};\nmov.b64 db, {%65, %67};\n"
    "wgmma.mma_async.sync.aligned.m64n128k16.f32.bf16.bf16 {%0, %1, %2, %3, %4, %5, %6, %7, %8, %9, %10, %11, %12, %13, %14, %15, %16, %17, %18, %19, %20, %21, %22, %23, %24, %25, %26, %27, %28, %29, %30, %31, %32, %33, %34, %35, %36, %37, %38, %39, %40, %41, %42, %43, %44, %45, %46, %47, %48, %49, %50, %51, %52, %53, %54, %55, %56, %57, %58, %59, %60, %61, %62, %63}, da, db, p, 1, 1, 0, 1;\n}\n"
    : "+f"(d[0]), "+f"(d[1]), "+f"(d[2]), "+f"(d[3]), "+f"(d[4]), "+f"(d[5]), "+f"(d[6]), "+f"(d[7]), "+f"(d[8]), "+f"(d[9]), "+f"(d[10]), "+f"(d[11]), "+f"(d[12]), "+f"(d[13]), "+f"(d[14]), "+f"(d[15]), "+f"(d[16]), "+f"(d[17]), "+f"(d[18]), "+f"(d[19]), "+f"(d[20]), "+f"(d[21]), "+f"(d[22]), "+f"(d[23]), "+f"(d[24]), "+f"(d[25]), "+f"(d[26]), "+f"(d[27]), "+f"(d[28]), "+f"(d[29]), "+f"(d[30]), "+f"(d[31]), "+f"(d[32]), "+f"(d[33]), "+f"(d[34]), "+f"(d[35]), "+f"(d[36]), "+f"(d[37]), "+f"(d[38]), "+f"(d[39]), "+f"(d[40]), "+f"(d[41]), "+f"(d[42]), "+f"(d[43]), "+f"(d[44]), "+f"(d[45]), "+f"(d[46]), "+f"(d[47]), "+f"(d[48]), "+f"(d[49]), "+f"(d[50]), "+f"(d[51]), "+f"(d[52]), "+f"(d[53]), "+f"(d[54]), "+f"(d[55]), "+f"(d[56]), "+f"(d[57]), "+f"(d[58]), "+f"(d[59]), "+f"(d[60]), "+f"(d[61]), "+f"(d[62]), "+f"(d[63])
    : "r"(a), "r"(b), "n"(AHI), "n"(BHI));
}
template<uint32_t AHI, uint32_t BHI> __device__ __forceinline__ void wg_ss_z_n128(float* d, uint32_t a, uint32_t b) {
  asm volatile("{\n.reg .pred p;\n.reg .b64 da, db;\nsetp.ne.b32 p, 0, 0;\nmov.b64 da, {%64, %66};\nmov.b64 db, {%65, %67};\n"
    "wgmma.mma_async.sync.aligned.m64n128k16.f32.bf16.bf16 {%0, %1, %2, %3, %4, %5, %6, %7, %8, %9, %10, %11, %12, %13, %14, %15, %16, %17, %18, %19, %20, %21, %22, %23, %24, %25, %26, %27, %28, %29, %30, %31, %32, %33, %34, %35, %36, %37, %38, %39, %40, %41, %42, %43, %44, %45, %46, %47, %48, %49, %50, %51, %52, %53, %54, %55, %56, %57, %58, %59, %60, %61, %62, %63}, da, db, p, 1, 1, 0, 1;\n}\n"
    : "=f"(d[0]), "=f"(d[1]), "=f"(d[2]), "=f"(d[3]), "=f"(d[4]), "=f"(d[5]), "=f"(d[6]), "=f"(d[7]), "=f"(d[8]), "=f"(d[9]), "=f"(d[10]), "=f"(d[11]), "=f"(d[12]), "=f"(d[13]), "=f"(d[14]), "=f"(d[15]), "=f"(d[16]), "=f"(d[17]), "=f"(d[18]), "=f"(d[19]), "=f"(d[20]), "=f"(d[21]), "=f"(d[22]), "=f"(d[23]), "=f"(d[24]), "=f"(d[25]), "=f"(d[26]), "=f"(d[27]), "=f"(d[28]), "=f"(d[29]), "=f"(d[30]), "=f"(d[31]), "=f"(d[32]), "=f"(d[33]), "=f"(d[34]), "=f"(d[35]), "=f"(d[36]), "=f"(d[37]), "=f"(d[38]), "=f"(d[39]), "=f"(d[40]), "=f"(d[41]), "=f"(d[42]), "=f"(d[43]), "=f"(d[44]), "=f"(d[45]), "=f"(d[46]), "=f"(d[47]), "=f"(d[48]), "=f"(d[49]), "=f"(d[50]), "=f"(d[51]), "=f"(d[52]), "=f"(d[53]), "=f"(d[54]), "=f"(d[55]), "=f"(d[56]), "=f"(d[57]), "=f"(d[58]), "=f"(d[59]), "=f"(d[60]), "=f"(d[61]), "=f"(d[62]), "=f"(d[63])
    : "r"(a), "r"(b), "n"(AHI), "n"(BHI));
}
template<uint32_t AHI, uint32_t BHI> __device__ __forceinline__ void wg_ss_n160(float* d, uint32_t a, uint32_t b) {
  asm volatile("{\n.reg .pred p;\n.reg .b64 da, db;\nsetp.ne.b32 p, 1, 0;\nmov.b64 da, {%80, %82};\nmov.b64 db, {%81, %83};\n"
    "wgmma.mma_async.sync.aligned.m64n160k16.f32.bf16.bf16 {%0, %1, %2, %3, %4, %5, %6, %7, %8, %9, %10, %11, %12, %13, %14, %15, %16, %17, %18, %19, %20, %21, %22, %23, %24, %25, %26, %27, %28, %29, %30, %31, %32, %33, %34, %35, %36, %37, %38, %39, %40, %41, %42, %43, %44, %45, %46, %47, %48, %49, %50, %51, %52, %53, %54, %55, %56, %57, %58, %59, %60, %61, %62, %63, %64, %65, %66, %67, %68, %69, %70, %71, %72, %73, %74, %75, %76, %77, %78, %79}, da, db, p, 1, 1, 0, 1;\n}\n"
    : "+f"(d[0]), "+f"(d[1]), "+f"(d[2]), "+f"(d[3]), "+f"(d[4]), "+f"(d[5]), "+f"(d[6]), "+f"(d[7]), "+f"(d[8]), "+f"(d[9]), "+f"(d[10]), "+f"(d[11]), "+f"(d[12]), "+f"(d[13]), "+f"(d[14]), "+f"(d[15]), "+f"(d[16]), "+f"(d[17]), "+f"(d[18]), "+f"(d[19]), "+f"(d[20]), "+f"(d[21]), "+f"(d[22]), "+f"(d[23]), "+f"(d[24]), "+f"(d[25]), "+f"(d[26]), "+f"(d[27]), "+f"(d[28]), "+f"(d[29]), "+f"(d[30]), "+f"(d[31]), "+f"(d[32]), "+f"(d[33]), "+f"(d[34]), "+f"(d[35]), "+f"(d[36]), "+f"(d[37]), "+f"(d[38]), "+f"(d[39]), "+f"(d[40]), "+f"(d[41]), "+f"(d[42]), "+f"(d[43]), "+f"(d[44]), "+f"(d[45]), "+f"(d[46]), "+f"(d[47]), "+f"(d[48]), "+f"(d[49]), "+f"(d[50]), "+f"(d[51]), "+f"(d[52]), "+f"(d[53]), "+f"(d[54]), "+f"(d[55]), "+f"(d[56]), "+f"(d[57]), "+f"(d[58]), "+f"(d[59]), "+f"(d[60]), "+f"(d[61]), "+f"(d[62]), "+f"(d[63]), "+f"(d[64]), "+f"(d[65]), "+f"(d[66]), "+f"(d[67]), "+f"(d[68]), "+f"(d[69]), "+f"(d[70]), "+f"(d[71]), "+f"(d[72]), "+f"(d[73]), "+f"(d[74]), "+f"(d[75]), "+f"(d[76]), "+f"(d[77]), "+f"(d[78]), "+f"(d[79])
    : "r"(a), "r"(b), "n"(AHI), "n"(BHI));
}
template<uint32_t AHI, uint32_t BHI> __device__ __forceinline__ void wg_ss_z_n160(float* d, uint32_t a, uint32_t b) {
  asm volatile("{\n.reg .pred p;\n.reg .b64 da, db;\nsetp.ne.b32 p, 0, 0;\nmov.b64 da, {%80, %82};\nmov.b64 db, {%81, %83};\n"
    "wgmma.mma_async.sync.aligned.m64n160k16.f32.bf16.bf16 {%0, %1, %2, %3, %4, %5, %6, %7, %8, %9, %10, %11, %12, %13, %14, %15, %16, %17, %18, %19, %20, %21, %22, %23, %24, %25, %26, %27, %28, %29, %30, %31, %32, %33, %34, %35, %36, %37, %38, %39, %40, %41, %42, %43, %44, %45, %46, %47, %48, %49, %50, %51, %52, %53, %54, %55, %56, %57, %58, %59, %60, %61, %62, %63, %64, %65, %66, %67, %68, %69, %70, %71, %72, %73, %74, %75, %76, %77, %78, %79}, da, db, p, 1, 1, 0, 1;\n}\n"
    : "=f"(d[0]), "=f"(d[1]), "=f"(d[2]), "=f"(d[3]), "=f"(d[4]), "=f"(d[5]), "=f"(d[6]), "=f"(d[7]), "=f"(d[8]), "=f"(d[9]), "=f"(d[10]), "=f"(d[11]), "=f"(d[12]), "=f"(d[13]), "=f"(d[14]), "=f"(d[15]), "=f"(d[16]), "=f"(d[17]), "=f"(d[18]), "=f"(d[19]), "=f"(d[20]), "=f"(d[21]), "=f"(d[22]), "=f"(d[23]), "=f"(d[24]), "=f"(d[25]), "=f"(d[26]), "=f"(d[27]), "=f"(d[28]), "=f"(d[29]), "=f"(d[30]), "=f"(d[31]), "=f"(d[32]), "=f"(d[33]), "=f"(d[34]), "=f"(d[35]), "=f"(d[36]), "=f"(d[37]), "=f"(d[38]), "=f"(d[39]), "=f"(d[40]), "=f"(d[41]), "=f"(d[42]), "=f"(d[43]), "=f"(d[44]), "=f"(d[45]), "=f"(d[46]), "=f"(d[47]), "=f"(d[48]), "=f"(d[49]), "=f"(d[50]), "=f"(d[51]), "=f"(d[52]), "=f"(d[53]), "=f"(d[54]), "=f"(d[55]), "=f"(d[56]), "=f"(d[57]), "=f"(d[58]), "=f"(d[59]), "=f"(d[60]), "=f"(d[61]), "=f"(d[62]), "=f"(d[63]), "=f"(d[64]), "=f"(d[65]), "=f"(d[66]), "=f"(d[67]), "=f"(d[68]), "=f"(d[69]), "=f"(d[70]), "=f"(d[71]), "=f"(d[72]), "=f"(d[73]), "=f"(d[74]), "=f"(d[75]), "=f"(d[76]), "=f"(d[77]), "=f"(d[78]), "=f"(d[79])
    : "r"(a), "r"(b), "n"(AHI), "n"(BHI));
}
template<uint32_t BHI> __device__ __forceinline__ void wg_rs_n64(float* d, uint32_t a0, uint32_t a1, uint32_t a2, uint32_t a3, uint32_t b) {
  asm volatile("{\n.reg .pred p;\n.reg .b64 db;\nsetp.ne.b32 p, 1, 0;\nmov.b64 db, {%36, %37};\n"
    "wgmma.mma_async.sync.aligned.m64n64k16.f32.bf16.bf16 {%0, %1, %2, %3, %4, %5, %6, %7, %8, %9, %10, %11, %12, %13, %14, %15, %16, %17, %18, %19, %20, %21, %22, %23, %24, %25, %26, %27, %28, %29, %30, %31}, {%32, %33, %34, %35}, db, p, 1, 1, 0;\n}\n"
    : "+f"(d[0]), "+f"(d[1]), "+f"(d[2]), "+f"(d[3]), "+f"(d[4]), "+f"(d[5]), "+f"(d[6]), "+f"(d[7]), "+f"(d[8]), "+f"(d[9]), "+f"(d[10]), "+f"(d[11]), "+f"(d[12]), "+f"(d[13]), "+f"(d[14]), "+f"(d[15]), "+f"(d[16]), "+f"(d[17]), "+f"(d[18]), "+f"(d[19]), "+f"(d[20]), "+f"(d[21]), "+f"(d[22]), "+f"(d[23]), "+f"(d[24]), "+f"(d[25]), "+f"(d[26]), "+f"(d[27]), "+f"(d[28]), "+f"(d[29]), "+f"(d[30]), "+f"(d[31])
    : "r"(a0), "r"(a1), "r"(a2), "r"(a3), "r"(b), "n"(BHI));
}
template<uint32_t BHI> __device__ __forceinline__ void wg_rs_z_n64(float* d, uint32_t a0, uint32_t a1, uint32_t a2, uint32_t a3, uint32_t b) {
  asm volatile("{\n.reg .pred p;\n.reg .b64 db;\nsetp.ne.b32 p, 0, 0;\nmov.b64 db, {%36, %37};\n"
    "wgmma.mma_async.sync.aligned.m64n64k16.f32.bf16.bf16 {%0, %1, %2, %3, %4, %5, %6, %7, %8, %9, %10, %11, %12, %13, %14, %15, %16, %17, %18, %19, %20, %21, %22, %23, %24, %25, %26, %27, %28, %29, %30, %31}, {%32, %33, %34, %35}, db, p, 1, 1, 0;\n}\n"
    : "=f"(d[0]), "=f"(d[1]), "=f"(d[2]), "=f"(d[3]), "=f"(d[4]), "=f"(d[5]), "=f"(d[6]), "=f"(d[7]), "=f"(d[8]), "=f"(d[9]), "=f"(d[10]), "=f"(d[11]), "=f"(d[12]), "=f"(d[13]), "=f"(d[14]), "=f"(d[15]), "=f"(d[16]), "=f"(d[17]), "=f"(d[18]), "=f"(d[19]), "=f"(d[20]), "=f"(d[21]), "=f"(d[22]), "=f"(d[23]), "=f"(d[24]), "=f"(d[25]), "=f"(d[26]), "=f"(d[27]), "=f"(d[28]), "=f"(d[29]), "=f"(d[30]), "=f"(d[31])
    : "r"(a0), "r"(a1), "r"(a2), "r"(a3), "r"(b), "n"(BHI));
}
template<uint32_t BHI> __device__ __forceinline__ void wg_rs_n24(float* d, uint32_t a0, uint32_t a1, uint32_t a2, uint32_t a3, uint32_t b) {
  asm volatile("{\n.reg .pred p;\n.reg .b64 db;\nsetp.ne.b32 p, 1, 0;\nmov.b64 db, {%16, %17};\n"
    "wgmma.mma_async.sync.aligned.m64n24k16.f32.bf16.bf16 {%0, %1, %2, %3, %4, %5, %6, %7, %8, %9, %10, %11}, {%12, %13, %14, %15}, db, p, 1, 1, 1;\n}\n"
    : "+f"(d[0]), "+f"(d[1]), "+f"(d[2]), "+f"(d[3]), "+f"(d[4]), "+f"(d[5]), "+f"(d[6]), "+f"(d[7]), "+f"(d[8]), "+f"(d[9]), "+f"(d[10]), "+f"(d[11])
    : "r"(a0), "r"(a1), "r"(a2), "r"(a3), "r"(b), "n"(BHI));
}
template<uint32_t BHI> __device__ __forceinline__ void wg_rs_z_n24(float* d, uint32_t a0, uint32_t a1, uint32_t a2, uint32_t a3, uint32_t b) {
  asm volatile("{\n.reg .pred p;\n.reg .b64 db;\nsetp.ne.b32 p, 0, 0;\nmov.b64 db, {%16, %17};\n"
    "wgmma.mma_async.sync.aligned.m64n24k16.f32.bf16.bf16 {%0, %1, %2, %3, %4, %5, %6, %7, %8, %9, %10, %11}, {%12, %13, %14, %15}, db, p, 1, 1, 1;\n}\n"
    : "=f"(d[0]), "=f"(d[1]), "=f"(d[2]), "=f"(d[3]), "=f"(d[4]), "=f"(d[5]), "=f"(d[6]), "=f"(d[7]), "=f"(d[8]), "=f"(d[9]), "=f"(d[10]), "=f"(d[11])
    : "r"(a0), "r"(a1), "r"(a2), "r"(a3), "r"(b), "n"(BHI));
}

__device__ __forceinline__ void wg_fence() { asm volatile("wgmma.fence.sync.aligned;" ::: "memory"); }
__device__ __forceinline__ void wg_commit() { asm volatile("wgmma.commit_group.sync.aligned;" ::: "memory"); }
template <int N> __device__ __forceinline__ void wg_wait() { asm volatile("wgmma.wait_group.sync.aligned %0;" ::"n"(N) : "memory"); }
template <int R> __device__ __forceinline__ void pin(float* d) {
#pragma unroll
  for (int i = 0; i < R; i++) asm volatile("" : "+f"(d[i])::"memory");
}
template <int R> __device__ __forceinline__ void pin(uint32_t* d) {
#pragma unroll
  for (int i = 0; i < R; i++) asm volatile("" : "+r"(d[i])::"memory");
}
__device__ __forceinline__ float ex2(float x) { float y; asm("ex2.approx.ftz.f32 %0, %1;" : "=f"(y) : "f"(x)); return y; }
__device__ __forceinline__ float tanh_fast(float x) { float y; asm("tanh.approx.f32 %0, %1;" : "=f"(y) : "f"(x)); return y; }
__device__ __forceinline__ uint32_t pack(float lo, float hi) { uint32_t r; asm("cvt.rn.bf16x2.f32 %0, %1, %2;" : "=r"(r) : "f"(hi), "f"(lo)); return r; }
__device__ __forceinline__ float bf_lo(uint32_t v) { return __uint_as_float(v << 16); }
__device__ __forceinline__ float bf_hi(uint32_t v) { return __uint_as_float(v & 0xffff0000u); }
__device__ __forceinline__ float bf_round(float x) { return bf_lo(pack(x, 0.f)); }

__device__ __forceinline__ void mbar_init(uint32_t bar, uint32_t cnt) { asm volatile("mbarrier.init.shared::cta.b64 [%0], %1;" ::"r"(bar), "r"(cnt) : "memory"); }
__device__ __forceinline__ void mbar_expect(uint32_t bar, uint32_t bytes) { asm volatile("mbarrier.arrive.expect_tx.shared::cta.b64 _, [%0], %1;" ::"r"(bar), "r"(bytes) : "memory"); }
__device__ __forceinline__ void mbar_arrive(uint32_t bar) { asm volatile("mbarrier.arrive.shared::cta.b64 _, [%0];" ::"r"(bar) : "memory"); }
__device__ __forceinline__ void mbar_wait(uint32_t bar, uint32_t parity) {
  asm volatile(
      "{\n.reg .pred p;\n.reg .u32 c;\n"
      "mbarrier.try_wait.parity.shared::cta.b64 p, [%0], %1;\n"
      "@p bra.uni DONE;\n"
      "mov.u32 c, 0;\n"
      "LOOP:\n"
      "mbarrier.try_wait.parity.shared::cta.b64 p, [%0], %1;\n"
      "@p bra.uni DONE;\n"
      "add.u32 c, c, 1;\n"
      "setp.lt.u32 p, c, 0x4000000;\n"
      "@p bra.uni LOOP;\n"
      "trap;\n"
      "DONE:\n}\n" ::"r"(bar), "r"(parity) : "memory");
}
__device__ __forceinline__ void flag_wait(const uint32_t* f, uint32_t target) {
  asm volatile(
      "{\n.reg .pred p;\n.reg .u32 c, v;\n"
      "mov.u32 c, 0;\n"
      "LOOP:\n"
      "ld.acquire.gpu.global.u32 v, [%0];\n"
      "setp.ge.u32 p, v, %1;\n"
      "@p bra DONE;\n"
      "add.u32 c, c, 1;\n"
      "setp.lt.u32 p, c, 0x1000000;\n"
      "@p bra LOOP;\n"
      "trap;\n"
      "DONE:\n}\n" ::"l"(f), "r"(target) : "memory");
}
__device__ __forceinline__ void flag_add(uint32_t* f) { asm volatile("red.relaxed.gpu.global.add.u32 [%0], 1;" ::"l"(f) : "memory"); }
__device__ __forceinline__ void fence_gpu() { asm volatile("fence.acq_rel.gpu;" ::: "memory"); }
__device__ __forceinline__ void fence_async() { asm volatile("fence.proxy.async;" ::: "memory"); }
__device__ __forceinline__ void tma2d(uint32_t dst, const CUtensorMap* tm, uint32_t bar, int c0, int c1) {
  asm volatile("cp.async.bulk.tensor.2d.shared::cluster.global.mbarrier::complete_tx::bytes [%0], [%1, {%3, %4}], [%2];" ::"r"(dst), "l"(tm), "r"(bar), "r"(c0), "r"(c1) : "memory");
}
__device__ __forceinline__ void tma5d(uint32_t dst, const CUtensorMap* tm, uint32_t bar, int c0, int c4) {
  asm volatile("cp.async.bulk.tensor.5d.shared::cluster.global.mbarrier::complete_tx::bytes [%0], [%1, {%3, %5, %5, %5, %4}], [%2];" ::"r"(dst), "l"(tm), "r"(bar), "r"(c0), "r"(c4), "r"(0) : "memory");
}
__device__ __forceinline__ void pf2d(const CUtensorMap* tm, int c0, int c1) {
  asm volatile("cp.async.bulk.prefetch.tensor.2d.L2.global [%0, {%1, %2}];" ::"l"(tm), "r"(c0), "r"(c1) : "memory");
}
__device__ __forceinline__ void pf5d(const CUtensorMap* tm, int c0, int c4) {
  asm volatile("cp.async.bulk.prefetch.tensor.5d.L2.global [%0, {%1, %3, %3, %3, %2}];" ::"l"(tm), "r"(c0), "r"(c4), "r"(0) : "memory");
}
__device__ __forceinline__ void bulk_g2s(uint32_t dst, const void* src, uint32_t bytes, uint32_t bar) {
  asm volatile("cp.async.bulk.shared::cluster.global.mbarrier::complete_tx::bytes [%0], [%1], %2, [%3];" ::"r"(dst), "l"(src), "r"(bytes), "r"(bar) : "memory");
}
__device__ __forceinline__ uint4 ldg_nc(const void* p) {
  uint4 v;
  asm volatile("ld.global.nc.L1::no_allocate.v4.u32 {%0,%1,%2,%3}, [%4];" : "=r"(v.x), "=r"(v.y), "=r"(v.z), "=r"(v.w) : "l"(p));
  return v;
}

struct Att {
  float s[32];
  float o[12];
  uint32_t p[16];
  uint32_t q[8];
};

__device__ __forceinline__ void attn_slow_rows(int cta, int j, int hp, int row_base, int tid_base) {
  const int lane = threadIdx.x & 31;
  const uint32_t* kv = g_KV + (size_t)(4 * j + hp) * SEQ * 20;
#pragma unroll 1
  for (int r = 0; r < 16; r++) {
    float q[18], acc[18];
#pragma unroll
    for (int v = 0; v < 9; v++) {
      uint32_t u = g_Q[(cta * 24 + hp * 6 + 2 * (v >> 2) + (r >> 3)) * 256 + tid_base + (r & 7) * 4 + ((v + hp) & 3)];
      q[2 * v] = bf_lo(u); q[2 * v + 1] = bf_hi(u);
      acc[2 * v] = 0.f; acc[2 * v + 1] = 0.f;
    }
    float mx = -INFINITY, l = 0.f;
#pragma unroll 1
    for (int key = lane; key < SEQ; key += 32) {
      const uint32_t* kr = kv + (key >> 3) * 160 + (key & 7) * 4;
      float s = 0.f;
#pragma unroll
      for (int v = 0; v < 9; v++) {
        uint32_t u = kr[(v >> 2) * 32 + ((v + hp) & 3)];
        s = fmaf(q[2 * v], bf_lo(u), s); s = fmaf(q[2 * v + 1], bf_hi(u), s);
      }
      float mn = fmaxf(mx, s), c = exp2f(mx - mn), p = exp2f(s - mn);
      mx = mn; l = l * c + p;
#pragma unroll
      for (int v = 0; v < 9; v++) {
        uint32_t u = v < 8 ? kr[(3 + (v >> 2)) * 32 + ((v + hp) & 3)] : kr[2 * 32 + ((hp + 2) & 3)];
        acc[2 * v] = fmaf(p, bf_lo(u), acc[2 * v] * c); acc[2 * v + 1] = fmaf(p, bf_hi(u), acc[2 * v + 1] * c);
      }
    }
    float gm = mx;
#pragma unroll
    for (int d = 16; d; d >>= 1) gm = fmaxf(gm, __shfl_xor_sync(0xffffffffu, gm, d));
    float c = exp2f(mx - gm);
    l *= c;
#pragma unroll
    for (int d = 16; d; d >>= 1) l += __shfl_xor_sync(0xffffffffu, l, d);
    uint32_t* orow = reinterpret_cast<uint32_t*>(g_O + (size_t)(row_base + r) * DM + 18 * (4 * j + hp));
#pragma unroll
    for (int v = 0; v < 9; v++) {
      float a = acc[2 * v] * c, b = acc[2 * v + 1] * c;
#pragma unroll
      for (int d = 16; d; d >>= 1) { a += __shfl_xor_sync(0xffffffffu, a, d); b += __shfl_xor_sync(0xffffffffu, b, d); }
      if (lane == 0) orow[v] = pack(a / l, b / l);
    }
  }
}

__device__ __forceinline__ bool o_epilogue(float* o, int hp, int j, int row0, int lane) {
  const int t = lane & 3, src = (lane & ~3) | ((hp + 1) & 3);
  float l0 = __shfl_sync(0xffffffffu, o[0], src), l1 = __shfl_sync(0xffffffffu, o[2], src);
  float sa = 0.f;
#pragma unroll
  for (int i = 0; i < 12; i++) sa += fabsf(o[i]);
  bool ok = (l0 <= 1.329228e36f) && (l1 <= 1.329228e36f) && (l0 > 0.f) && (l1 > 0.f) && (sa <= 3.0e38f);
  float i0 = __frcp_rn(l0), i1 = __frcp_rn(l1);
  uint32_t* r0 = reinterpret_cast<uint32_t*>(g_O + (size_t)row0 * DM + 18 * (4 * j + hp));
  uint32_t* r1 = r0 + 8 * (DM / 2);
  const int v = (t - hp) & 3;
  r0[v] = pack(o[4] * i0, o[5] * i0);
  r1[v] = pack(o[6] * i1, o[7] * i1);
  r0[v + 4] = pack(o[8] * i0, o[9] * i0);
  r1[v + 4] = pack(o[10] * i1, o[11] * i1);
  if (t == ((hp + 2) & 3)) { r0[8] = pack(o[0] * i0, o[1] * i0); r1[8] = pack(o[2] * i1, o[3] * i1); }
  return __any_sync(0xffffffffu, !ok);
}

__device__ __forceinline__ void issue_att(Att& a, uint32_t kdesc, uint32_t vdesc) {
#pragma unroll
  for (int k = 0; k < 4; k++) wg_rs_n24<HI_V>(a.o, a.p[4 * k], a.p[4 * k + 1], a.p[4 * k + 2], a.p[4 * k + 3], vdesc + k * 80);
  wg_rs_z_n64<HI_K>(a.s, a.q[0], a.q[1], a.q[2], a.q[3], kdesc);
  wg_rs_n64<HI_K>(a.s, a.q[4], a.q[5], a.q[6], a.q[7], kdesc + 16);
}
__device__ __forceinline__ void softmax_tile(Att& a) {
#pragma unroll
  for (int i = 0; i < 16; i++) a.p[i] = pack(ex2(a.s[2 * i]), ex2(a.s[2 * i + 1]));
  pin<16>(a.p);
}
__device__ __forceinline__ void first_tile(Att& a, int hp, int lane) {
  float m0 = fmaxf(a.s[0], a.s[1]), m1 = fmaxf(a.s[2], a.s[3]);
#pragma unroll
  for (int i = 4; i < 32; i += 4) { m0 = fmaxf(m0, fmaxf(a.s[i], a.s[i + 1])); m1 = fmaxf(m1, fmaxf(a.s[i + 2], a.s[i + 3])); }
  m0 = fmaxf(m0, __shfl_xor_sync(0xffffffffu, m0, 1)); m1 = fmaxf(m1, __shfl_xor_sync(0xffffffffu, m1, 1));
  m0 = fmaxf(m0, __shfl_xor_sync(0xffffffffu, m0, 2)); m1 = fmaxf(m1, __shfl_xor_sync(0xffffffffu, m1, 2));
  float n0 = -(m0 + MOFF), n1 = -(m1 + MOFF);
  float h0 = bf_round(n0), h1 = bf_round(n1);
  uint32_t e0 = pack(h0, n0 - h0), e1 = pack(h1, n1 - h1);
  n0 = h0 + bf_hi(e0); n1 = h1 + bf_hi(e1);
  if ((lane & 3) == ((hp + 1) & 3)) { a.q[4] = e0; a.q[5] = e1; }
#pragma unroll
  for (int i = 0; i < 32; i += 4) { a.s[i] += n0; a.s[i + 1] += n0; a.s[i + 2] += n1; a.s[i + 3] += n1; }
#pragma unroll
  for (int i = 0; i < 12; i++) a.o[i] = 0.f;
  pin<12>(a.o); pin<8>(a.q);
}
__device__ __forceinline__ void load_q(Att& a, int cta, int hp, int tid) {
  const uint32_t* src = g_Q + (cta * 24 + hp * 6) * 256 + tid;
#pragma unroll
  for (int i = 0; i < 6; i++) a.q[i] = __ldcg(src + i * 256);
}
__device__ __forceinline__ void h_epilogue(float* acc, __nv_bfloat16* dst) {
#pragma unroll
  for (int b = 0; b < 2; b++) {
    uint32_t w0[4], w1[4];
#pragma unroll
    for (int i = 0; i < 4; i++) {
      float h[4];
#pragma unroll
      for (int e = 0; e < 4; e++) {
        float g = acc[(4 * b + i) * 4 + e], u = 0.5f * acc[32 + (4 * b + i) * 4 + e];
        h[e] = fmaf(tanh_fast(0.5f * g), u, u);
      }
      w0[i] = pack(h[0], h[1]); w1[i] = pack(h[2], h[3]);
    }
    *reinterpret_cast<uint4*>(dst + 32 * b) = make_uint4(w0[0], w0[1], w0[2], w0[3]);
    *reinterpret_cast<uint4*>(dst + 32 * b + 8 * FF) = make_uint4(w1[0], w1[1], w1[2], w1[3]);
  }
}

template <int Q> __device__ __forceinline__ void final_store(const float* acc, float* own, int m, int hh, int tid) {
  float4* pw = g_P + (size_t)((m * 2 + hh) * 16 + Q * 4) * 9 * 256 + tid;
#pragma unroll
  for (int d = 0; d < 4; d++) {
    if (d == Q) continue;
#pragma unroll
    for (int i = 0; i < 9; i++) __stcg(pw + (d * 9 + i) * 256, make_float4(acc[36 * d + 4 * i], acc[36 * d + 4 * i + 1], acc[36 * d + 4 * i + 2], acc[36 * d + 4 * i + 3]));
  }
#pragma unroll
  for (int i = 0; i < 36; i++) own[i] = acc[36 * Q + i];
}
__device__ __forceinline__ void final_reduce(float* own, const Params& prm, int cta, int m, int hh, int q, int tid, int row0, int lane) {
  const int col = 288 * hh + 72 * q + 2 * (lane & 3);
  const uint32_t* xr = reinterpret_cast<const uint32_t*>(prm.x + (size_t)row0 * DM + col);
  uint32_t xa[9], xb[9];
#pragma unroll
  for (int i = 0; i < 9; i++) { xa[i] = __ldg(xr + 4 * i); xb[i] = __ldg(xr + 4 * i + 8 * (DM / 2)); }
  asm volatile("bar.sync 3, 256;" ::: "memory");
  if (tid == 0) {
    fence_gpu();
#pragma unroll
    for (int d = 1; d < 4; d++) flag_add(FLAG_P(m * 8 + 2 * ((q + d) & 3) + hh));
    flag_wait(FLAG_P(cta), 3);
  }
  asm volatile("bar.sync 3, 256;" ::: "memory");
  const float4* pr = g_P + (size_t)((m * 2 + hh) * 16 + q) * 9 * 256 + tid;
#pragma unroll
  for (int d = 1; d < 4; d++) {
#pragma unroll
    for (int i = 0; i < 9; i++) {
      float4 v = __ldcg(pr + (((q + d) & 3) * 36 + i) * 256);
      own[4 * i] += v.x; own[4 * i + 1] += v.y; own[4 * i + 2] += v.z; own[4 * i + 3] += v.w;
    }
  }
  uint32_t* orow = reinterpret_cast<uint32_t*>(prm.out + (size_t)row0 * DM + col);
#pragma unroll
  for (int i = 0; i < 9; i++) {
    orow[4 * i] = pack(own[4 * i] + bf_lo(xa[i]), own[4 * i + 1] + bf_hi(xa[i]));
    orow[4 * i + 8 * (DM / 2)] = pack(own[4 * i + 2] + bf_lo(xb[i]), own[4 * i + 3] + bf_hi(xb[i]));
  }
}

__global__ void __launch_bounds__(384, 1) fused_kernel(const __grid_constant__ Params prm) {
  extern __shared__ __align__(1024) uint8_t smem[];
  const uint32_t sb = (uint32_t)__cvta_generic_to_shared(smem);
  const uint32_t bar = sb + SM_BAR;
  const int m = blockIdx.x & 15, j = blockIdx.x >> 4;
  const int cta = m * 8 + j;
  const int wg = __shfl_sync(0xffffffffu, (int)(threadIdx.x >> 7), 0);
  const int lane = threadIdx.x & 31;
  STAMP(0);
  if (threadIdx.x == 256) {
    if (sb & 1023) asm volatile("trap;");
#pragma unroll
    for (int i = 0; i < 3; i++) { mbar_init(bar + 8 * (B_QF + i), 1); mbar_init(bar + 8 * (B_QE + i), 8); mbar_init(bar + 8 * (B_GF + i), 1); mbar_init(bar + 8 * (B_GE + i), 8); mbar_init(bar + 8 * (B_KF + i), 1); mbar_init(bar + 8 * (B_KE + i), 8); }
#pragma unroll
    for (int i = 0; i < 4; i++) { mbar_init(bar + 8 * (B_BF + i), 1); mbar_init(bar + 8 * (B_BE + i), 8); }
    mbar_init(bar + 8 * B_SKV, 8); mbar_init(bar + 8 * B_SH, 8); mbar_init(bar + 8 * B_SO, 8);
    asm volatile("fence.mbarrier_init.release.cluster;" ::: "memory");
    fence_async();
  }
  __syncthreads();

  if (wg == 2) {
    asm volatile("setmaxnreg.dec.sync.aligned.u32 24;");
    const int pw = (threadIdx.x >> 5) & 3;
    if (lane == 0) {
      if (pw == 0) {
        for (int kb = 0; kb < 9; kb++) {
          const int s = kb % 3;
          if (kb >= 3) mbar_wait(bar + 8 * (B_QE + s), (kb / 3 - 1) & 1);
          const uint32_t fb = bar + 8 * (B_QF + s), dst = sb + SM_RING + s * QST;
          mbar_expect(fb, QST);
#pragma unroll
          for (int p = 0; p < 3; p++) {
            tma2d(dst + p * 8192, &prm.wqkv64, fb, 576 * p + 72 * j, 64 * kb);
            tma2d(dst + 24576 + p * 1024, &prm.wqkv8, fb, 576 * p + 72 * j + 64, 64 * kb);
          }
        }
        int tau = 0, kb = 0;
        for (int s = 0; s < 81; s++) {
          const int slot = s & 3;
          if (s >= 4) mbar_wait(bar + 8 * (B_BE + slot), ((s >> 2) - 1) & 1);
          else if (s != 2) mbar_wait(bar + 8 * (B_QE + (s == 3 ? 2 : s)), 0);
          const uint32_t fb = bar + 8 * (B_BF + slot), dst = sb + SM_RING + slot * BST;
          mbar_expect(fb, BST);
          tma2d(dst, &prm.wg, fb, 576 * j + 64 * tau, 64 * kb);
          tma2d(dst + 8192, &prm.wu, fb, 576 * j + 64 * tau, 64 * kb);
          if (++kb == 9) { kb = 0; tau++; }
        }
        const int hh = j & 1;
        for (int b = 0; b < 21; b++) {
          const int st = b % 3;
          if (b >= 3) mbar_wait(bar + 8 * (B_GE + st), (b / 3 - 1) & 1);
          else if (b == 1) mbar_wait(bar + 8 * (B_BE + 2), 1);
          else if (b == 2) mbar_wait(bar + 8 * (B_BE + 0), 0);
          const uint32_t fb = bar + 8 * (B_GF + st), dst = sb + st * G2ST;
          mbar_expect(fb, G2ST);
          if (b < 18) {
            const int own = (b < 8 || b == 16), tile = b < 16 ? (b & 7) : 8;
            const int jj = own ? j : (j ^ 1);
            const int kc = 576 * jj + 64 * tile;
#pragma unroll
            for (int a = 0; a < 5; a++) tma5d(dst + 16384 + a * 8192, &prm.wd[hh], fb, 64 * a, kc >> 5);
            flag_wait(FLAG_H(m * 8 + jj), tile + 1);
            fence_async();
            tma2d(dst, &prm.h, fb, kc, 128 * m);
          } else {
            const int kc = 144 * (j >> 1) + 64 * (b - 18);
#pragma unroll
            for (int a = 0; a < 5; a++) tma2d(dst + 16384 + a * 8192, &prm.wo[hh], fb, 64 * a, kc);
            if (b == 18) { flag_wait(FLAG_O(cta), 1); flag_wait(FLAG_O(cta ^ 1), 1); fence_async(); }
            tma2d(dst, &prm.o, fb, kc, 128 * m);
          }
        }
      } else if (pw == 1) {
        flag_wait(FLAG_KV(j), 16);
        fence_async();
        int slot = 0, ph = 1;
        for (int it = 0; it < 128; it++) {
          if (it >= 3) mbar_wait(bar + 8 * (B_KE + slot), ph);
          const uint32_t fb = bar + 8 * (B_KF + slot);
          mbar_expect(fb, KVST);
          bulk_g2s(sb + SM_KV + slot * KVST, g_KV + (size_t)(4 * j + (it >> 5)) * SEQ * 20 + ((it + 2 * m) & 31) * 1280, KVST, fb);
          if (++slot == 3) { slot = 0; ph ^= 1; }
        }
      } else if (pw == 2) {
        mbar_wait(bar + 8 * B_SKV, 0);
        fence_gpu(); fence_async(); flag_add(FLAG_KV(j));
        for (int t = 0; t < 9; t++) { mbar_wait(bar + 8 * B_SH, t & 1); fence_gpu(); fence_async(); flag_add(FLAG_H(cta)); }
        mbar_wait(bar + 8 * B_SO, 0);
        fence_gpu(); fence_async(); flag_add(FLAG_O(cta));
      } else {
        if (m >= 3 && m < 9) {
#pragma unroll
          for (int p = 0; p < 3; p++) { pf2d(&prm.wqkv64, 576 * p + 72 * j, 64 * m); pf2d(&prm.wqkv8, 576 * p + 72 * j + 64, 64 * m); }
        }
        mbar_wait(bar + 8 * (B_QF + 2), 0);
        for (int b = m; b < 162; b += 16) {
          const int s = b >> 1;
          pf2d((b & 1) ? &prm.wu : &prm.wg, 576 * j + 64 * (s / 9), 64 * (s % 9));
        }
        for (int b = m; b < 90; b += 16) pf5d(&prm.wd[j & 1], 64 * (b % 5), 36 * (j >> 1) + 2 * (b / 5));
        if (m < 15) pf2d(&prm.wo[j & 1], 64 * (m % 5), 144 * (j >> 1) + 64 * (m / 5));
      }
    }
  } else {
    asm volatile("setmaxnreg.inc.sync.aligned.u32 240;");
    const int tid = threadIdx.x;
    const int w = (tid >> 5) & 3, t = lane & 3;
    const int row0 = 128 * m + 64 * wg + 16 * w + (lane >> 2);
    {
      uint4 v[4][9];
      const int ch = lane & 7;
#pragma unroll
      for (int k = 0; k < 4; k++) {
        const __nv_bfloat16* src = prm.x + (size_t)(128 * m + 64 * wg + 16 * w + 4 * k + (lane >> 3)) * DM + ch * 8;
#pragma unroll
        for (int c = 0; c < 9; c++) v[k][c] = ldg_nc(src + c * 64);
      }
#pragma unroll
      for (int k = 0; k < 4; k++) {
        float s0 = 0.f, s1 = 0.f;
#pragma unroll
        for (int c = 0; c < 9; c++) {
          s0 += bf_lo(v[k][c].x) + bf_lo(v[k][c].y); s1 += bf_hi(v[k][c].x) + bf_hi(v[k][c].y);
          s0 += bf_lo(v[k][c].z) + bf_lo(v[k][c].w); s1 += bf_hi(v[k][c].z) + bf_hi(v[k][c].w);
        }
        float s = s0 + s1;
        s += __shfl_xor_sync(0xffffffffu, s, 1); s += __shfl_xor_sync(0xffffffffu, s, 2); s += __shfl_xor_sync(0xffffffffu, s, 4);
        const float mean = s * (1.f / 576.f);
        float q0 = 0.f, q1 = 0.f;
#pragma unroll
        for (int c = 0; c < 9; c++) {
          const uint32_t u[4] = {v[k][c].x, v[k][c].y, v[k][c].z, v[k][c].w};
#pragma unroll
          for (int e = 0; e < 4; e++) { float a = bf_lo(u[e]) - mean, b = bf_hi(u[e]) - mean; q0 = fmaf(a, a, q0); q1 = fmaf(b, b, q1); }
        }
        float q = q0 + q1;
        q += __shfl_xor_sync(0xffffffffu, q, 1); q += __shfl_xor_sync(0xffffffffu, q, 2); q += __shfl_xor_sync(0xffffffffu, q, 4);
        const float den = bf_round(sqrtf(bf_round(bf_round(q * (1.f / 576.f)) + 1e-5f)));
        const float inv = __frcp_rn(den);
        const uint32_t mb = pack(mean, mean);
        const int lr = 64 * wg + 16 * w + 4 * k + (lane >> 3);
        const uint32_t dst = sb + SM_XN + lr * 128 + ((ch ^ (lr & 7)) << 4);
#pragma unroll
        for (int c = 0; c < 9; c++) {
          const uint32_t u[4] = {v[k][c].x, v[k][c].y, v[k][c].z, v[k][c].w};
          uint32_t r[4];
#pragma unroll
          for (int e = 0; e < 4; e++) {
            uint32_t d;
            asm("sub.rn.bf16x2 %0, %1, %2;" : "=r"(d) : "r"(u[e]), "r"(mb));
            r[e] = pack(bf_lo(d) * inv, bf_hi(d) * inv);
          }
          asm volatile("st.shared.v4.u32 [%0], {%1,%2,%3,%4};" ::"r"(dst + c * 16384), "r"(r[0]), "r"(r[1]), "r"(r[2]), "r"(r[3]) : "memory");
        }
      }
      asm volatile("fence.proxy.async.shared::cta;" ::: "memory");
      if (wg == 0) asm volatile("bar.sync 1, 128;" ::: "memory"); else asm volatile("bar.sync 2, 128;" ::: "memory");
    }
    STAMP(1);
    const uint32_t adesc = (((sb + SM_XN + wg * 8192) & 0x3FFFF) >> 4) | LO_A;
    const uint32_t bdesc = (((sb + SM_RING) & 0x3FFFF) >> 4) | LO_B;
    const uint32_t kdesc0 = (((sb + SM_KV) & 0x3FFFF) >> 4) | LO_K;
    const uint32_t vdesc0 = (((sb + SM_KV + 256) & 0x3FFFF) >> 4) | LO_V;
    float accA[64], accB[64];
    Att a;
    uint32_t badmask = 0;
    {
      float aq[96], ar[12];
      const uint32_t rdesc = (((sb + SM_RING + 24576) & 0x3FFFF) >> 4) | LO_R;
#pragma unroll
      for (int kb = 0; kb < 9; kb++) {
        const int s = kb % 3;
        mbar_wait(bar + 8 * (B_QF + s), (kb / 3) & 1);
        wg_fence();
#pragma unroll
        for (int k = 0; k < 4; k++) {
          if (kb == 0 && k == 0) {
            wg_ss_z_n192<HI_SW128, HI_SW128>(aq, adesc, bdesc);
            wg_ss_z_n24<HI_SW128, HI_R>(ar, adesc, rdesc);
          } else {
            wg_ss_n192<HI_SW128, HI_SW128>(aq, adesc + kb * 1024 + k * 2, bdesc + s * (QST >> 4) + k * 128);
            wg_ss_n24<HI_SW128, HI_R>(ar, adesc + kb * 1024 + k * 2, rdesc + s * (QST >> 4) + k * 16);
          }
        }
        wg_commit();
        if (kb > 0) { wg_wait<1>(); if (lane == 0) mbar_arrive(bar + 8 * (B_QE + (kb - 1) % 3)); }
      }
      mbar_wait(bar + 8 * B_BF, 0);
      wg_fence();
      wg_ss_z_n128<HI_SW128, HI_SW128>(accA, adesc, bdesc);
#pragma unroll
      for (int k = 1; k < 4; k++) wg_ss_n128<HI_SW128, HI_SW128>(accA, adesc + k * 2, bdesc + k * 128);
      wg_commit();
      wg_wait<1>();
      pin<96>(aq); pin<12>(ar);
      if (lane == 0) mbar_arrive(bar + 8 * (B_QE + 2));
      STAMP(2);
      uint32_t pk[3][9][2];
#pragma unroll
      for (int p = 0; p < 3; p++)
#pragma unroll
        for (int i = 0; i < 9; i++) {
          const float* src = i < 8 ? &aq[(8 * p + i) * 4] : &ar[4 * p];
          pk[p][i][0] = pack(src[0], src[1]); pk[p][i][1] = pack(src[2], src[3]);
          if (p == 0) {
            pk[0][i][0] = pack(bf_lo(pk[0][i][0]) * QSCALE, bf_hi(pk[0][i][0]) * QSCALE);
            pk[0][i][1] = pack(bf_lo(pk[0][i][1]) * QSCALE, bf_hi(pk[0][i][1]) * QSCALE);
          }
        }
      uint32_t* kvp = g_KV + (size_t)(4 * j) * SEQ * 20 + (row0 >> 3) * 160 + lane;
      uint32_t* qp = g_Q + cta * 24 * 256 + tid;
#pragma unroll
      for (int hp = 0; hp < 4; hp++) {
        const bool up = t < hp;
#pragma unroll
        for (int rh = 0; rh < 2; rh++) {
          uint32_t* d = kvp + hp * SEQ * 20 + rh * 160;
          d[0] = up ? pk[1][2 * hp + 1][rh] : pk[1][2 * hp][rh];
          d[32] = up ? pk[1][2 * hp + 2][rh] : pk[1][2 * hp + 1][rh];
          d[96] = up ? pk[2][2 * hp + 1][rh] : pk[2][2 * hp][rh];
          d[128] = up ? pk[2][2 * hp + 2][rh] : pk[2][2 * hp + 1][rh];
          const uint32_t v9 = __shfl_sync(0xffffffffu, pk[2][2 * hp + 2][rh], (lane & ~3) | hp);
          d[64] = t == hp ? pk[1][2 * hp + 2][rh] : t == ((hp + 1) & 3) ? 0x3f803f80u : t == ((hp + 2) & 3) ? v9 : 0u;
          const uint32_t q0 = up ? pk[0][2 * hp + 1][rh] : pk[0][2 * hp][rh];
          const uint32_t q1 = up ? pk[0][2 * hp + 2][rh] : pk[0][2 * hp + 1][rh];
          const uint32_t q2 = t == hp ? pk[0][2 * hp + 2][rh] : 0u;
          qp[(hp * 6 + rh) * 256] = q0; qp[(hp * 6 + 2 + rh) * 256] = q1; qp[(hp * 6 + 4 + rh) * 256] = q2;
          if (hp == 0) { a.q[rh] = q0; a.q[2 + rh] = q1; a.q[4 + rh] = q2; }
        }
      }
      __syncwarp();
      if (lane == 0) mbar_arrive(bar + 8 * B_SKV);
      a.q[6] = 0; a.q[7] = 0;
#pragma unroll
      for (int i = 0; i < 16; i++) a.p[i] = 0;
#pragma unroll
      for (int i = 0; i < 12; i++) a.o[i] = 0.f;
      pin<8>(a.q); pin<16>(a.p); pin<12>(a.o);
    }
    STAMP(3);
    int gs = 1;
#pragma unroll 1
    for (int kb = 1; kb < 9; kb++, gs++) {
      mbar_wait(bar + 8 * (B_BF + (gs & 3)), (gs >> 2) & 1);
      wg_fence();
#pragma unroll
      for (int k = 0; k < 4; k++) wg_ss_n128<HI_SW128, HI_SW128>(accA, adesc + kb * 1024 + k * 2, bdesc + (gs & 3) * 1024 + k * 128);
      wg_commit();
      wg_wait<1>();
      if (lane == 0) mbar_arrive(bar + 8 * (B_BE + ((gs - 1) & 3)));
    }
    STAMP(4);
    int kslot = 0, kph = 0, vslot = 0;
    __nv_bfloat16* hdst = g_H + (size_t)row0 * FF + 576 * j + 8 * t;

#define EPI_STEP(ACCN, ACCO)                                                                                   \
  {                                                                                                            \
    mbar_wait(bar + 8 * (B_BF + (gs & 3)), (gs >> 2) & 1);                                                     \
    wg_fence();                                                                                                \
    wg_ss_z_n128<HI_SW128, HI_SW128>(ACCN, adesc, bdesc + (gs & 3) * 1024);                                    \
    _Pragma("unroll") for (int k = 1; k < 4; k++) wg_ss_n128<HI_SW128, HI_SW128>(ACCN, adesc + k * 2, bdesc + (gs & 3) * 1024 + k * 128); \
    wg_commit();                                                                                               \
    wg_wait<1>();                                                                                              \
    pin<64>(ACCO);                                                                                             \
    if (lane == 0) mbar_arrive(bar + 8 * (B_BE + ((gs - 1) & 3)));                                             \
    h_epilogue(ACCO, hdst);                                                                                    \
    hdst += 64;                                                                                                \
    __syncwarp();                                                                                              \
    if (lane == 0) mbar_arrive(bar + 8 * B_SH);                                                                \
    gs++;                                                                                                      \
  }
#define ATT_STEP1(ACC, KB, FIRST, HP)                                                                          \
  {                                                                                                            \
    mbar_wait(bar + 8 * (B_KF + kslot), kph);                                                                  \
    mbar_wait(bar + 8 * (B_BF + (gs & 3)), (gs >> 2) & 1);                                                     \
    wg_fence();                                                                                                \
    issue_att(a, kdesc0 + kslot * 320, vdesc0 + vslot * 320);                                                  \
    wg_commit();                                                                                               \
    _Pragma("unroll") for (int k = 0; k < 4; k++) wg_ss_n128<HI_SW128, HI_SW128>(ACC, adesc + (KB) * 1024 + k * 2, bdesc + (gs & 3) * 1024 + k * 128); \
    wg_commit();                                                                                               \
    wg_wait<1>();                                                                                              \
    pin<32>(a.s);                                                                                              \
    if (lane == 0) { mbar_arrive(bar + 8 * (B_BE + ((gs - 1) & 3))); if (!(FIRST) || (HP) > 0) mbar_arrive(bar + 8 * (B_KE + vslot)); } \
    if (FIRST) {                                                                                               \
      pin<12>(a.o);                                                                                            \
      if ((HP) > 0) badmask |= (uint32_t)o_epilogue(a.o, (HP) - 1, j, row0, lane) << ((HP) - 1);               \
      first_tile(a, HP, lane);                                                                                 \
    }                                                                                                          \
    softmax_tile(a);                                                                                           \
    vslot = kslot;                                                                                             \
    if (++kslot == 3) { kslot = 0; kph ^= 1; }                                                                 \
    gs++;                                                                                                      \
  }

#pragma unroll 1
    for (int pr = 0; pr < 4; pr++) {
      if (pr == 2) { load_q(a, cta, 1, tid); pin<8>(a.q); }
      EPI_STEP(accB, accA);
      if ((pr & 1) == 0) ATT_STEP1(accB, 1, true, pr >> 1) else ATT_STEP1(accB, 1, false, 1);
#pragma unroll 1
      for (int kb = 2; kb < 9; kb++) ATT_STEP1(accB, kb, false, 1);
      EPI_STEP(accA, accB);
#pragma unroll 1
      for (int kb = 1; kb < 9; kb++) ATT_STEP1(accA, kb, false, 1);
    }
    STAMP(5);
    load_q(a, cta, 2, tid);
    wg_wait<0>();
    pin<64>(accA);
    if (lane == 0) mbar_arrive(bar + 8 * (B_BE + 0));
    h_epilogue(accA, hdst);
    __syncwarp();
    if (lane == 0) mbar_arrive(bar + 8 * B_SH);
    pin<8>(a.q);
    STAMP(6);

    float acc2[144];
    const uint32_t a2desc = (((sb + wg * 8192) & 0x3FFFF) >> 4) | LO_A;
    const uint32_t b2desc = (((sb + 16384) & 0x3FFFF) >> 4) | LO_B;
    int st = 0, gph = 0;
#define G2_ISSUE(K)                                                                                            \
  wg_ss_n128<HI_SW128, HI_SW128>(acc2, a2desc + st * 3584 + (K) * 2, b2desc + st * 3584 + (K) * 128);          \
  wg_ss_n160<HI_SW128, HI_SW128>(acc2 + 64, a2desc + st * 3584 + (K) * 2, b2desc + st * 3584 + (K) * 128 + 1024);
#define ATT_STEP2(N, FIRST, HP)                                                                                \
  {                                                                                                            \
    const int sub = (N) & 3;                                                                                   \
    mbar_wait(bar + 8 * (B_KF + kslot), kph);                                                                  \
    if (sub == 0) mbar_wait(bar + 8 * (B_GF + st), gph);                                                       \
    wg_fence();                                                                                                \
    issue_att(a, kdesc0 + kslot * 320, vdesc0 + vslot * 320);                                                  \
    wg_commit();                                                                                               \
    if ((FIRST) && (HP) == 2) {                                                                                \
      wg_ss_z_n128<HI_SW128, HI_SW128>(acc2, a2desc, b2desc);                                                  \
      wg_ss_z_n160<HI_SW128, HI_SW128>(acc2 + 64, a2desc, b2desc + 1024);                                      \
    } else { G2_ISSUE(sub) }                                                                                   \
    wg_commit();                                                                                               \
    wg_wait<1>();                                                                                              \
    pin<32>(a.s);                                                                                              \
    if (lane == 0) { mbar_arrive(bar + 8 * (B_KE + vslot)); if (sub == 0 && !((FIRST) && (HP) == 2)) mbar_arrive(bar + 8 * (B_GE + (st == 0 ? 2 : st - 1))); } \
    if (FIRST) {                                                                                               \
      pin<12>(a.o);                                                                                            \
      badmask |= (uint32_t)o_epilogue(a.o, (HP) - 1, j, row0, lane) << ((HP) - 1);                             \
      first_tile(a, HP, lane);                                                                                 \
    } else if ((N) == 31) { load_q(a, cta, 3, tid); }                                                          \
    softmax_tile(a);                                                                                           \
    if (!(FIRST)) pin<8>(a.q);                                                                                 \
    vslot = kslot;                                                                                             \
    if (++kslot == 3) { kslot = 0; kph ^= 1; }                                                                 \
    if (sub == 3) { if (++st == 3) { st = 0; gph ^= 1; } }                                                     \
  }
    ATT_STEP2(0, true, 2);
#pragma unroll 1
    for (int n = 1; n < 32; n++) ATT_STEP2(n, false, 1);
    ATT_STEP2(32, true, 3);
#pragma unroll 1
    for (int n = 33; n < 64; n++) ATT_STEP2(n, false, 1);
    STAMP(7);
    mbar_wait(bar + 8 * (B_GF + st), gph);
    wg_fence();
#pragma unroll
    for (int k = 0; k < 4; k++) wg_rs_n24<HI_V>(a.o, a.p[4 * k], a.p[4 * k + 1], a.p[4 * k + 2], a.p[4 * k + 3], vdesc0 + vslot * 320 + k * 80);
    wg_commit();
#pragma unroll
    for (int k = 0; k < 4; k++) { G2_ISSUE(k) }
    wg_commit();
    wg_wait<1>();
    pin<12>(a.o);
    if (lane == 0) mbar_arrive(bar + 8 * (B_GE + (st == 0 ? 2 : st - 1)));
    badmask |= (uint32_t)o_epilogue(a.o, 3, j, row0, lane) << 3;
    if (badmask == 0) { __syncwarp(); if (lane == 0) mbar_arrive(bar + 8 * B_SO); }
    if (++st == 3) { st = 0; gph ^= 1; }
    mbar_wait(bar + 8 * (B_GF + st), gph);
    wg_fence();
#pragma unroll
    for (int k = 0; k < 4; k++) { G2_ISSUE(k) }
    wg_commit();
    wg_wait<0>();
    pin<144>(acc2);
    if (lane == 0) { mbar_arrive(bar + 8 * (B_GE + (st == 0 ? 2 : st - 1))); mbar_arrive(bar + 8 * (B_GE + st)); }
    if (++st == 3) { st = 0; gph ^= 1; }
    if (badmask != 0) {
#pragma unroll 1
      for (int hp = 0; hp < 4; hp++)
        if ((badmask >> hp) & 1) attn_slow_rows(cta, j, hp, 128 * m + 64 * wg + 16 * w, tid & ~31);
      __syncwarp();
      if (lane == 0) mbar_arrive(bar + 8 * B_SO);
    }
    STAMP(8);
#pragma unroll
    for (int b = 0; b < 3; b++) {
      mbar_wait(bar + 8 * (B_GF + st), gph);
      wg_fence();
#pragma unroll
      for (int k = 0; k < (b < 2 ? 4 : 1); k++) { G2_ISSUE(k) }
      wg_commit();
      if (++st == 3) { st = 0; gph ^= 1; }
    }
    wg_wait<0>();
    pin<144>(acc2);
    STAMP(9);
    {
      int tid2, bid2;
      asm volatile("mov.u32 %0, %%tid.x;" : "=r"(tid2));
      asm volatile("mov.u32 %0, %%ctaid.x;" : "=r"(bid2));
      const int m2 = bid2 & 15, j2 = bid2 >> 4;
      float own[36];
      switch (j2 >> 1) {
        case 0: final_store<0>(acc2, own, m2, j2 & 1, tid2); break;
        case 1: final_store<1>(acc2, own, m2, j2 & 1, tid2); break;
        case 2: final_store<2>(acc2, own, m2, j2 & 1, tid2); break;
        default: final_store<3>(acc2, own, m2, j2 & 1, tid2); break;
      }
      pin<36>(own);
      final_reduce(own, prm, m2 * 8 + j2, m2, j2 & 1, j2 >> 1, tid2, 128 * m2 + (tid2 >> 5) * 16 + ((tid2 & 31) >> 2), tid2 & 31);
    }
    STAMP(10);
    if (tid == 0) {
      if (atomicInc(FLAG_DONE, NCTA - 1) == NCTA - 1) {
        for (int i = 0; i < 8; i++) *FLAG_KV(i) = 0;
        for (int i = 0; i < NCTA; i++) { *FLAG_H(i) = 0; *FLAG_O(i) = 0; *FLAG_P(i) = 0; }
      }
    }
  }
}

typedef CUresult (*EncodeFn)(CUtensorMap*, CUtensorMapDataType, cuuint32_t, void*, const cuuint64_t*, const cuuint64_t*, const cuuint32_t*, const cuuint32_t*,
                             CUtensorMapInterleave, CUtensorMapSwizzle, CUtensorMapL2promotion, CUtensorMapFloatOOBfill);

void enc2d(EncodeFn enc, CUtensorMap* tm, const void* base, uint64_t w, uint64_t h, uint64_t pitch_elems, uint32_t bw, uint32_t bh, CUtensorMapSwizzle sw) {
  cuuint64_t dims[2] = {w, h}, str[1] = {pitch_elems * 2};
  cuuint32_t box[2] = {bw, bh}, es[2] = {1, 1};
  enc(tm, CU_TENSOR_MAP_DATA_TYPE_BFLOAT16, 2, const_cast<void*>(base), dims, str, box, es, CU_TENSOR_MAP_INTERLEAVE_NONE, sw,
      CU_TENSOR_MAP_L2_PROMOTION_L2_128B, CU_TENSOR_MAP_FLOAT_OOB_FILL_NONE);
}

}

extern "C" void kernel_launch(void* const* d_in, const int* in_sizes, int n_in, void* d_out, int out_size) {
  (void)in_sizes; (void)n_in; (void)out_size;
  const __nv_bfloat16* x = (const __nv_bfloat16*)d_in[0];
  const __nv_bfloat16* wqkv = (const __nv_bfloat16*)d_in[1];
  const __nv_bfloat16* wo = (const __nv_bfloat16*)d_in[2];
  const __nv_bfloat16* wg = (const __nv_bfloat16*)d_in[4];
  const __nv_bfloat16* wu = (const __nv_bfloat16*)d_in[5];
  const __nv_bfloat16* wd = (const __nv_bfloat16*)d_in[6];
  void* fn = nullptr;
  cudaDriverEntryPointQueryResult qr;
  cudaGetDriverEntryPoint("cuTensorMapEncodeTiled", &fn, cudaEnableDefault, &qr);
  EncodeFn enc = (EncodeFn)fn;
  void *hp = nullptr, *op = nullptr;
  cudaGetSymbolAddress(&hp, g_H);
  cudaGetSymbolAddress(&op, g_O);
  Params p;
  enc2d(enc, &p.wqkv64, wqkv, 3 * DM, DM, 3 * DM, 64, 64, CU_TENSOR_MAP_SWIZZLE_128B);
  enc2d(enc, &p.wqkv8, wqkv, 3 * DM, DM, 3 * DM, 8, 64, CU_TENSOR_MAP_SWIZZLE_NONE);
  enc2d(enc, &p.wg, wg, FF, DM, FF, 64, 64, CU_TENSOR_MAP_SWIZZLE_128B);
  enc2d(enc, &p.wu, wu, FF, DM, FF, 64, 64, CU_TENSOR_MAP_SWIZZLE_128B);
  enc2d(enc, &p.h, hp, FF, SEQ, FF, 64, 128, CU_TENSOR_MAP_SWIZZLE_128B);
  enc2d(enc, &p.o, op, DM, SEQ, DM, 64, 128, CU_TENSOR_MAP_SWIZZLE_128B);
  for (int hh = 0; hh < 2; hh++) {
    enc2d(enc, &p.wo[hh], wo + 288 * hh, 288, DM, DM, 64, 64, CU_TENSOR_MAP_SWIZZLE_128B);
    cuuint64_t dims[5] = {288, 2, 4, 4, FF / 32}, str[4] = {DM * 2, 8 * DM * 2, 2 * DM * 2, 32 * DM * 2};
    cuuint32_t box[5] = {64, 2, 4, 4, 2}, es[5] = {1, 1, 1, 1, 1};
    enc(&p.wd[hh], CU_TENSOR_MAP_DATA_TYPE_BFLOAT16, 5, (void*)(wd + 288 * hh), dims, str, box, es, CU_TENSOR_MAP_INTERLEAVE_NONE,
        CU_TENSOR_MAP_SWIZZLE_128B, CU_TENSOR_MAP_L2_PROMOTION_L2_128B, CU_TENSOR_MAP_FLOAT_OOB_FILL_NONE);
  }
  p.x = x;
  p.out = (__nv_bfloat16*)d_out;
  cudaFuncSetAttribute(fused_kernel, cudaFuncAttributeMaxDynamicSharedMemorySize, SM_TOTAL);
  fused_kernel<<<NCTA, 384, SM_TOTAL, cudaStreamPerThread>>>(p);
}
```

```cpp
#include <cuda_runtime.h>
#include <cuda.h>
#include <cuda_bf16.h>
#include <stdint.h>

namespace {

constexpr int SEQ = 2048, DM = 576, FF = 4608;
constexpr int NCTA = 128;

constexpr uint32_t SM_XN = 0;
constexpr uint32_t SM_RING = 147456;
constexpr uint32_t SM_KV = 212992;
constexpr uint32_t QST = 27648, BST = 16384, KVST = 6144, G2ST = 57344;
constexpr uint32_t SM_OL = 172032;
constexpr uint32_t SM_W16 = SM_OL + 16384;
constexpr uint32_t SM_BAR = 232064;
constexpr uint32_t SM_TOTAL = 232448;
enum { B_QF = 0, B_QE = 3, B_BF = 6, B_BE = 10, B_GF = 14, B_GE = 17, B_KF = 20, B_KE = 23, B_SKV = 26, B_SH = 27, B_SO1 = 28, B_SO2 = 29,
       B_OL = 30, B_X = 31, B_N = 39 };

constexpr uint32_t HI_SW128 = 0x40000040u;
constexpr uint32_t LO_A = 1u << 16;
constexpr uint32_t LO_B = 512u << 16;
constexpr uint32_t HI_R = 64u, LO_R = 8u << 16;
constexpr uint32_t HI_K = 24u, LO_K = 8u << 16;
constexpr uint32_t HI_V = 8u, LO_V = 24u << 16;
constexpr uint32_t LO_B16 = 128u << 16;

constexpr float QSCALE = 0.23570226039551584f * 1.4426950408889634f;
constexpr float MOFF = 90.f;

struct __align__(64) Params {
  CUtensorMap xm, wqkv64, wqkv8, wg, wu, h, wd[2], o, wo[2], wo16[2], kv;
  const __nv_bfloat16* x;
  __nv_bfloat16* out;
};

__device__ __align__(1024) __nv_bfloat16 g_H[SEQ * FF];
__device__ __align__(1024) __nv_bfloat16 g_O[SEQ * DM];
__device__ __align__(1024) uint32_t g_KV[32 * SEQ * 20];
__device__ __align__(1024) uint32_t g_Q[NCTA * 4 * 256 * 8];
__device__ __align__(1024) float4 g_P[32 * 16 * 9 * 256];
__device__ uint32_t g_flags[8 * 32 + NCTA * 32 * 3 + 32];
#define FLAG_KV(j) (&g_flags[(j) * 32])
#define FLAG_H(c) (&g_flags[8 * 32 + (c) * 32])
#define FLAG_O(c) (&g_flags[8 * 32 + NCTA * 32 + (c) * 32])
#define FLAG_P(c) (&g_flags[8 * 32 + NCTA * 64 + (c) * 32])
#define FLAG_DONE (&g_flags[8 * 32 + NCTA * 96])
#define FLAG_EPOCH (&g_flags[8 * 32 + NCTA * 96 + 16])
#define STAMP(i)
#define STAMPW(i)

template<uint32_t AHI, uint32_t BHI> __device__ __forceinline__ void wg_ss_n192(float* d, uint32_t a, uint32_t b) {
  asm volatile("{\n.reg .pred p;\n.reg .b64 da, db;\nsetp.ne.b32 p, 1, 0;\nmov.b64 da, {%96, %98};\nmov.b64 db, {%97, %99};\n"
    "wgmma.mma_async.sync.aligned.m64n192k16.f32.bf16.bf16 {%0, %1, %2, %3, %4, %5, %6, %7, %8, %9, %10, %11, %12, %13, %14, %15, %16, %17, %18, %19, %20, %21, %22, %23, %24, %25, %26, %27, %28, %29, %30, %31, %32, %33, %34, %35, %36, %37, %38, %39, %40, %41, %42, %43, %44, %45, %46, %47, %48, %49, %50, %51, %52, %53, %54, %55, %56, %57, %58, %59, %60, %61, %62, %63, %64, %65, %66, %67, %68, %69, %70, %71, %72, %73, %74, %75, %76, %77, %78, %79, %80, %81, %82, %83, %84, %85, %86, %87, %88, %89, %90, %91, %92, %93, %94, %95}, da, db, p, 1, 1, 0, 1;\n}\n"
    : "+f"(d[0]), "+f"(d[1]), "+f"(d[2]), "+f"(d[3]), "+f"(d[4]), "+f"(d[5]), "+f"(d[6]), "+f"(d[7]), "+f"(d[8]), "+f"(d[9]), "+f"(d[10]), "+f"(d[11]), "+f"(d[12]), "+f"(d[13]), "+f"(d[14]), "+f"(d[15]), "+f"(d[16]), "+f"(d[17]), "+f"(d[18]), "+f"(d[19]), "+f"(d[20]), "+f"(d[21]), "+f"(d[22]), "+f"(d[23]), "+f"(d[24]), "+f"(d[25]), "+f"(d[26]), "+f"(d[27]), "+f"(d[28]), "+f"(d[29]), "+f"(d[30]), "+f"(d[31]), "+f"(d[32]), "+f"(d[33]), "+f"(d[34]), "+f"(d[35]), "+f"(d[36]), "+f"(d[37]), "+f"(d[38]), "+f"(d[39]), "+f"(d[40]), "+f"(d[41]), "+f"(d[42]), "+f"(d[43]), "+f"(d[44]), "+f"(d[45]), "+f"(d[46]), "+f"(d[47]), "+f"(d[48]), "+f"(d[49]), "+f"(d[50]), "+f"(d[51]), "+f"(d[52]), "+f"(d[53]), "+f"(d[54]), "+f"(d[55]), "+f"(d[56]), "+f"(d[57]), "+f"(d[58]), "+f"(d[59]), "+f"(d[60]), "+f"(d[61]), "+f"(d[62]), "+f"(d[63]), "+f"(d[64]), "+f"(d[65]), "+f"(d[66]), "+f"(d[67]), "+f"(d[68]), "+f"(d[69]), "+f"(d[70]), "+f"(d[71]), "+f"(d[72]), "+f"(d[73]), "+f"(d[74]), "+f"(d[75]), "+f"(d[76]), "+f"(d[77]), "+f"(d[78]), "+f"(d[79]), "+f"(d[80]), "+f"(d[81]), "+f"(d[82]), "+f"(d[83]), "+f"(d[84]), "+f"(d[85]), "+f"(d[86]), "+f"(d[87]), "+f"(d[88]), "+f"(d[89]), "+f"(d[90]), "+f"(d[91]), "+f"(d[92]), "+f"(d[93]), "+f"(d[94]), "+f"(d[95])
    : "r"(a), "r"(b), "n"(AHI), "n"(BHI));
}
template<uint32_t AHI, uint32_t BHI> __device__ __forceinline__ void wg_ss_z_n192(float* d, uint32_t a, uint32_t b) {
  asm volatile("{\n.reg .pred p;\n.reg .b64 da, db;\nsetp.ne.b32 p, 0, 0;\nmov.b64 da, {%96, %98};\nmov.b64 db, {%97, %99};\n"
    "wgmma.mma_async.sync.aligned.m64n192k16.f32.bf16.bf16 {%0, %1, %2, %3, %4, %5, %6, %7, %8, %9, %10, %11, %12, %13, %14, %15, %16, %17, %18, %19, %20, %21, %22, %23, %24, %25, %26, %27, %28, %29, %30, %31, %32, %33, %34, %35, %36, %37, %38, %39, %40, %41, %42, %43, %44, %45, %46, %47, %48, %49, %50, %51, %52, %53, %54, %55, %56, %57, %58, %59, %60, %61, %62, %63, %64, %65, %66, %67, %68, %69, %70, %71, %72, %73, %74, %75, %76, %77, %78, %79, %80, %81, %82, %83, %84, %85, %86, %87, %88, %89, %90, %91, %92, %93, %94, %95}, da, db, p, 1, 1, 0, 1;\n}\n"
    : "=f"(d[0]), "=f"(d[1]), "=f"(d[2]), "=f"(d[3]), "=f"(d[4]), "=f"(d[5]), "=f"(d[6]), "=f"(d[7]), "=f"(d[8]), "=f"(d[9]), "=f"(d[10]), "=f"(d[11]), "=f"(d[12]), "=f"(d[13]), "=f"(d[14]), "=f"(d[15]), "=f"(d[16]), "=f"(d[17]), "=f"(d[18]), "=f"(d[19]), "=f"(d[20]), "=f"(d[21]), "=f"(d[22]), "=f"(d[23]), "=f"(d[24]), "=f"(d[25]), "=f"(d[26]), "=f"(d[27]), "=f"(d[28]), "=f"(d[29]), "=f"(d[30]), "=f"(d[31]), "=f"(d[32]), "=f"(d[33]), "=f"(d[34]), "=f"(d[35]), "=f"(d[36]), "=f"(d[37]), "=f"(d[38]), "=f"(d[39]), "=f"(d[40]), "=f"(d[41]), "=f"(d[42]), "=f"(d[43]), "=f"(d[44]), "=f"(d[45]), "=f"(d[46]), "=f"(d[47]), "=f"(d[48]), "=f"(d[49]), "=f"(d[50]), "=f"(d[51]), "=f"(d[52]), "=f"(d[53]), "=f"(d[54]), "=f"(d[55]), "=f"(d[56]), "=f"(d[57]), "=f"(d[58]), "=f"(d[59]), "=f"(d[60]), "=f"(d[61]), "=f"(d[62]), "=f"(d[63]), "=f"(d[64]), "=f"(d[65]), "=f"(d[66]), "=f"(d[67]), "=f"(d[68]), "=f"(d[69]), "=f"(d[70]), "=f"(d[71]), "=f"(d[72]), "=f"(d[73]), "=f"(d[74]), "=f"(d[75]), "=f"(d[76]), "=f"(d[77]), "=f"(d[78]), "=f"(d[79]), "=f"(d[80]), "=f"(d[81]), "=f"(d[82]), "=f"(d[83]), "=f"(d[84]), "=f"(d[85]), "=f"(d[86]), "=f"(d[87]), "=f"(d[88]), "=f"(d[89]), "=f"(d[90]), "=f"(d[91]), "=f"(d[92]), "=f"(d[93]), "=f"(d[94]), "=f"(d[95])
    : "r"(a), "r"(b), "n"(AHI), "n"(BHI));
}
template<uint32_t AHI, uint32_t BHI> __device__ __forceinline__ void wg_ss_n24(float* d, uint32_t a, uint32_t b) {
  asm volatile("{\n.reg .pred p;\n.reg .b64 da, db;\nsetp.ne.b32 p, 1, 0;\nmov.b64 da, {%12, %14};\nmov.b64 db, {%13, %15};\n"
    "wgmma.mma_async.sync.aligned.m64n24k16.f32.bf16.bf16 {%0, %1, %2, %3, %4, %5, %6, %7, %8, %9, %10, %11}, da, db, p, 1, 1, 0, 1;\n}\n"
    : "+f"(d[0]), "+f"(d[1]), "+f"(d[2]), "+f"(d[3]), "+f"(d[4]), "+f"(d[5]), "+f"(d[6]), "+f"(d[7]), "+f"(d[8]), "+f"(d[9]), "+f"(d[10]), "+f"(d[11])
    : "r"(a), "r"(b), "n"(AHI), "n"(BHI));
}
template<uint32_t AHI, uint32_t BHI> __device__ __forceinline__ void wg_ss_z_n24(float* d, uint32_t a, uint32_t b) {
  asm volatile("{\n.reg .pred p;\n.reg .b64 da, db;\nsetp.ne.b32 p, 0, 0;\nmov.b64 da, {%12, %14};\nmov.b64 db, {%13, %15};\n"
    "wgmma.mma_async.sync.aligned.m64n24k16.f32.bf16.bf16 {%0, %1, %2, %3, %4, %5, %6, %7, %8, %9, %10, %11}, da, db, p, 1, 1, 0, 1;\n}\n"
    : "=f"(d[0]), "=f"(d[1]), "=f"(d[2]), "=f"(d[3]), "=f"(d[4]), "=f"(d[5]), "=f"(d[6]), "=f"(d[7]), "=f"(d[8]), "=f"(d[9]), "=f"(d[10]), "=f"(d[11])
    : "r"(a), "r"(b), "n"(AHI), "n"(BHI));
}
template<uint32_t AHI, uint32_t BHI> __device__ __forceinline__ void wg_ss_n128(float* d, uint32_t a, uint32_t b) {
  asm volatile("{\n.reg .pred p;\n.reg .b64 da, db;\nsetp.ne.b32 p, 1, 0;\nmov.b64 da, {%64, %66};\nmov.b64 db, {%65, %67};\n"
    "wgmma.mma_async.sync.aligned.m64n128k16.f32.bf16.bf16 {%0, %1, %2, %3, %4, %5, %6, %7, %8, %9, %10, %11, %12, %13, %14, %15, %16, %17, %18, %19, %20, %21, %22, %23, %24, %25, %26, %27, %28, %29, %30, %31, %32, %33, %34, %35, %36, %37, %38, %39, %40, %41, %42, %43, %44, %45, %46, %47, %48, %49, %50, %51, %52, %53, %54, %55, %56, %57, %58, %59, %60, %61, %62, %63}, da, db, p, 1, 1, 0, 1;\n}\n"
    : "+f"(d[0]), "+f"(d[1]), "+f"(d[2]), "+f"(d[3]), "+f"(d[4]), "+f"(d[5]), "+f"(d[6]), "+f"(d[7]), "+f"(d[8]), "+f"(d[9]), "+f"(d[10]), "+f"(d[11]), "+f"(d[12]), "+f"(d[13]), "+f"(d[14]), "+f"(d[15]), "+f"(d[16]), "+f"(d[17]), "+f"(d[18]), "+f"(d[19]), "+f"(d[20]), "+f"(d[21]), "+f"(d[22]), "+f"(d[23]), "+f"(d[24]), "+f"(d[25]), "+f"(d[26]), "+f"(d[27]), "+f"(d[28]), "+f"(d[29]), "+f"(d[30]), "+f"(d[31]), "+f"(d[32]), "+f"(d[33]), "+f"(d[34]), "+f"(d[35]), "+f"(d[36]), "+f"(d[37]), "+f"(d[38]), "+f"(d[39]), "+f"(d[40]), "+f"(d[41]), "+f"(d[42]), "+f"(d[43]), "+f"(d[44]), "+f"(d[45]), "+f"(d[46]), "+f"(d[47]), "+f"(d[48]), "+f"(d[49]), "+f"(d[50]), "+f"(d[51]), "+f"(d[52]), "+f"(d[53]), "+f"(d[54]), "+f"(d[55]), "+f"(d[56]), "+f"(d[57]), "+f"(d[58]), "+f"(d[59]), "+f"(d[60]), "+f"(d[61]), "+f"(d[62]), "+f"(d[63])
    : "r"(a), "r"(b), "n"(AHI), "n"(BHI));
}
template<uint32_t AHI, uint32_t BHI> __device__ __forceinline__ void wg_ss_z_n128(float* d, uint32_t a, uint32_t b) {
  asm volatile("{\n.reg .pred p;\n.reg .b64 da, db;\nsetp.ne.b32 p, 0, 0;\nmov.b64 da, {%64, %66};\nmov.b64 db, {%65, %67};\n"
    "wgmma.mma_async.sync.aligned.m64n128k16.f32.bf16.bf16 {%0, %1, %2, %3, %4, %5, %6, %7, %8, %9, %10, %11, %12, %13, %14, %15, %16, %17, %18, %19, %20, %21, %22, %23, %24, %25, %26, %27, %28, %29, %30, %31, %32, %33, %34, %35, %36, %37, %38, %39, %40, %41, %42, %43, %44, %45, %46, %47, %48, %49, %50, %51, %52, %53, %54, %55, %56, %57, %58, %59, %60, %61, %62, %63}, da, db, p, 1, 1, 0, 1;\n}\n"
    : "=f"(d[0]), "=f"(d[1]), "=f"(d[2]), "=f"(d[3]), "=f"(d[4]), "=f"(d[5]), "=f"(d[6]), "=f"(d[7]), "=f"(d[8]), "=f"(d[9]), "=f"(d[10]), "=f"(d[11]), "=f"(d[12]), "=f"(d[13]), "=f"(d[14]), "=f"(d[15]), "=f"(d[16]), "=f"(d[17]), "=f"(d[18]), "=f"(d[19]), "=f"(d[20]), "=f"(d[21]), "=f"(d[22]), "=f"(d[23]), "=f"(d[24]), "=f"(d[25]), "=f"(d[26]), "=f"(d[27]), "=f"(d[28]), "=f"(d[29]), "=f"(d[30]), "=f"(d[31]), "=f"(d[32]), "=f"(d[33]), "=f"(d[34]), "=f"(d[35]), "=f"(d[36]), "=f"(d[37]), "=f"(d[38]), "=f"(d[39]), "=f"(d[40]), "=f"(d[41]), "=f"(d[42]), "=f"(d[43]), "=f"(d[44]), "=f"(d[45]), "=f"(d[46]), "=f"(d[47]), "=f"(d[48]), "=f"(d[49]), "=f"(d[50]), "=f"(d[51]), "=f"(d[52]), "=f"(d[53]), "=f"(d[54]), "=f"(d[55]), "=f"(d[56]), "=f"(d[57]), "=f"(d[58]), "=f"(d[59]), "=f"(d[60]), "=f"(d[61]), "=f"(d[62]), "=f"(d[63])
    : "r"(a), "r"(b), "n"(AHI), "n"(BHI));
}
template<uint32_t AHI, uint32_t BHI> __device__ __forceinline__ void wg_ss_n160(float* d, uint32_t a, uint32_t b) {
  asm volatile("{\n.reg .pred p;\n.reg .b64 da, db;\nsetp.ne.b32 p, 1, 0;\nmov.b64 da, {%80, %82};\nmov.b64 db, {%81, %83};\n"
    "wgmma.mma_async.sync.aligned.m64n160k16.f32.bf16.bf16 {%0, %1, %2, %3, %4, %5, %6, %7, %8, %9, %10, %11, %12, %13, %14, %15, %16, %17, %18, %19, %20, %21, %22, %23, %24, %25, %26, %27, %28, %29, %30, %31, %32, %33, %34, %35, %36, %37, %38, %39, %40, %41, %42, %43, %44, %45, %46, %47, %48, %49, %50, %51, %52, %53, %54, %55, %56, %57, %58, %59, %60, %61, %62, %63, %64, %65, %66, %67, %68, %69, %70, %71, %72, %73, %74, %75, %76, %77, %78, %79}, da, db, p, 1, 1, 0, 1;\n}\n"
    : "+f"(d[0]), "+f"(d[1]), "+f"(d[2]), "+f"(d[3]), "+f"(d[4]), "+f"(d[5]), "+f"(d[6]), "+f"(d[7]), "+f"(d[8]), "+f"(d[9]), "+f"(d[10]), "+f"(d[11]), "+f"(d[12]), "+f"(d[13]), "+f"(d[14]), "+f"(d[15]), "+f"(d[16]), "+f"(d[17]), "+f"(d[18]), "+f"(d[19]), "+f"(d[20]), "+f"(d[21]), "+f"(d[22]), "+f"(d[23]), "+f"(d[24]), "+f"(d[25]), "+f"(d[26]), "+f"(d[27]), "+f"(d[28]), "+f"(d[29]), "+f"(d[30]), "+f"(d[31]), "+f"(d[32]), "+f"(d[33]), "+f"(d[34]), "+f"(d[35]), "+f"(d[36]), "+f"(d[37]), "+f"(d[38]), "+f"(d[39]), "+f"(d[40]), "+f"(d[41]), "+f"(d[42]), "+f"(d[43]), "+f"(d[44]), "+f"(d[45]), "+f"(d[46]), "+f"(d[47]), "+f"(d[48]), "+f"(d[49]), "+f"(d[50]), "+f"(d[51]), "+f"(d[52]), "+f"(d[53]), "+f"(d[54]), "+f"(d[55]), "+f"(d[56]), "+f"(d[57]), "+f"(d[58]), "+f"(d[59]), "+f"(d[60]), "+f"(d[61]), "+f"(d[62]), "+f"(d[63]), "+f"(d[64]), "+f"(d[65]), "+f"(d[66]), "+f"(d[67]), "+f"(d[68]), "+f"(d[69]), "+f"(d[70]), "+f"(d[71]), "+f"(d[72]), "+f"(d[73]), "+f"(d[74]), "+f"(d[75]), "+f"(d[76]), "+f"(d[77]), "+f"(d[78]), "+f"(d[79])
    : "r"(a), "r"(b), "n"(AHI), "n"(BHI));
}
template<uint32_t AHI, uint32_t BHI> __device__ __forceinline__ void wg_ss_z_n160(float* d, uint32_t a, uint32_t b) {
  asm volatile("{\n.reg .pred p;\n.reg .b64 da, db;\nsetp.ne.b32 p, 0, 0;\nmov.b64 da, {%80, %82};\nmov.b64 db, {%81, %83};\n"
    "wgmma.mma_async.sync.aligned.m64n160k16.f32.bf16.bf16 {%0, %1, %2, %3, %4, %5, %6, %7, %8, %9, %10, %11, %12, %13, %14, %15, %16, %17, %18, %19, %20, %21, %22, %23, %24, %25, %26, %27, %28, %29, %30, %31, %32, %33, %34, %35, %36, %37, %38, %39, %40, %41, %42, %43, %44, %45, %46, %47, %48, %49, %50, %51, %52, %53, %54, %55, %56, %57, %58, %59, %60, %61, %62, %63, %64, %65, %66, %67, %68, %69, %70, %71, %72, %73, %74, %75, %76, %77, %78, %79}, da, db, p, 1, 1, 0, 1;\n}\n"
    : "=f"(d[0]), "=f"(d[1]), "=f"(d[2]), "=f"(d[3]), "=f"(d[4]), "=f"(d[5]), "=f"(d[6]), "=f"(d[7]), "=f"(d[8]), "=f"(d[9]), "=f"(d[10]), "=f"(d[11]), "=f"(d[12]), "=f"(d[13]), "=f"(d[14]), "=f"(d[15]), "=f"(d[16]), "=f"(d[17]), "=f"(d[18]), "=f"(d[19]), "=f"(d[20]), "=f"(d[21]), "=f"(d[22]), "=f"(d[23]), "=f"(d[24]), "=f"(d[25]), "=f"(d[26]), "=f"(d[27]), "=f"(d[28]), "=f"(d[29]), "=f"(d[30]), "=f"(d[31]), "=f"(d[32]), "=f"(d[33]), "=f"(d[34]), "=f"(d[35]), "=f"(d[36]), "=f"(d[37]), "=f"(d[38]), "=f"(d[39]), "=f"(d[40]), "=f"(d[41]), "=f"(d[42]), "=f"(d[43]), "=f"(d[44]), "=f"(d[45]), "=f"(d[46]), "=f"(d[47]), "=f"(d[48]), "=f"(d[49]), "=f"(d[50]), "=f"(d[51]), "=f"(d[52]), "=f"(d[53]), "=f"(d[54]), "=f"(d[55]), "=f"(d[56]), "=f"(d[57]), "=f"(d[58]), "=f"(d[59]), "=f"(d[60]), "=f"(d[61]), "=f"(d[62]), "=f"(d[63]), "=f"(d[64]), "=f"(d[65]), "=f"(d[66]), "=f"(d[67]), "=f"(d[68]), "=f"(d[69]), "=f"(d[70]), "=f"(d[71]), "=f"(d[72]), "=f"(d[73]), "=f"(d[74]), "=f"(d[75]), "=f"(d[76]), "=f"(d[77]), "=f"(d[78]), "=f"(d[79])
    : "r"(a), "r"(b), "n"(AHI), "n"(BHI));
}
template<uint32_t BHI> __device__ __forceinline__ void wg_rs_n64(float* d, uint32_t a0, uint32_t a1, uint32_t a2, uint32_t a3, uint32_t b) {
  asm volatile("{\n.reg .pred p;\n.reg .b64 db;\nsetp.ne.b32 p, 1, 0;\nmov.b64 db, {%36, %37};\n"
    "wgmma.mma_async.sync.aligned.m64n64k16.f32.bf16.bf16 {%0, %1, %2, %3, %4, %5, %6, %7, %8, %9, %10, %11, %12, %13, %14, %15, %16, %17, %18, %19, %20, %21, %22, %23, %24, %25, %26, %27, %28, %29, %30, %31}, {%32, %33, %34, %35}, db, p, 1, 1, 0;\n}\n"
    : "+f"(d[0]), "+f"(d[1]), "+f"(d[2]), "+f"(d[3]), "+f"(d[4]), "+f"(d[5]), "+f"(d[6]), "+f"(d[7]), "+f"(d[8]), "+f"(d[9]), "+f"(d[10]), "+f"(d[11]), "+f"(d[12]), "+f"(d[13]), "+f"(d[14]), "+f"(d[15]), "+f"(d[16]), "+f"(d[17]), "+f"(d[18]), "+f"(d[19]), "+f"(d[20]), "+f"(d[21]), "+f"(d[22]), "+f"(d[23]), "+f"(d[24]), "+f"(d[25]), "+f"(d[26]), "+f"(d[27]), "+f"(d[28]), "+f"(d[29]), "+f"(d[30]), "+f"(d[31])
    : "r"(a0), "r"(a1), "r"(a2), "r"(a3), "r"(b), "n"(BHI));
}
template<uint32_t BHI> __device__ __forceinline__ void wg_rs_z_n64(float* d, uint32_t a0, uint32_t a1, uint32_t a2, uint32_t a3, uint32_t b) {
  asm volatile("{\n.reg .pred p;\n.reg .b64 db;\nsetp.ne.b32 p, 0, 0;\nmov.b64 db, {%36, %37};\n"
    "wgmma.mma_async.sync.aligned.m64n64k16.f32.bf16.bf16 {%0, %1, %2, %3, %4, %5, %6, %7, %8, %9, %10, %11, %12, %13, %14, %15, %16, %17, %18, %19, %20, %21, %22, %23, %24, %25, %26, %27, %28, %29, %30, %31}, {%32, %33, %34, %35}, db, p, 1, 1, 0;\n}\n"
    : "=f"(d[0]), "=f"(d[1]), "=f"(d[2]), "=f"(d[3]), "=f"(d[4]), "=f"(d[5]), "=f"(d[6]), "=f"(d[7]), "=f"(d[8]), "=f"(d[9]), "=f"(d[10]), "=f"(d[11]), "=f"(d[12]), "=f"(d[13]), "=f"(d[14]), "=f"(d[15]), "=f"(d[16]), "=f"(d[17]), "=f"(d[18]), "=f"(d[19]), "=f"(d[20]), "=f"(d[21]), "=f"(d[22]), "=f"(d[23]), "=f"(d[24]), "=f"(d[25]), "=f"(d[26]), "=f"(d[27]), "=f"(d[28]), "=f"(d[29]), "=f"(d[30]), "=f"(d[31])
    : "r"(a0), "r"(a1), "r"(a2), "r"(a3), "r"(b), "n"(BHI));
}
template<uint32_t BHI> __device__ __forceinline__ void wg_rs_n24(float* d, uint32_t a0, uint32_t a1, uint32_t a2, uint32_t a3, uint32_t b) {
  asm volatile("{\n.reg .pred p;\n.reg .b64 db;\nsetp.ne.b32 p, 1, 0;\nmov.b64 db, {%16, %17};\n"
    "wgmma.mma_async.sync.aligned.m64n24k16.f32.bf16.bf16 {%0, %1, %2, %3, %4, %5, %6, %7, %8, %9, %10, %11}, {%12, %13, %14, %15}, db, p, 1, 1, 1;\n}\n"
    : "+f"(d[0]), "+f"(d[1]), "+f"(d[2]), "+f"(d[3]), "+f"(d[4]), "+f"(d[5]), "+f"(d[6]), "+f"(d[7]), "+f"(d[8]), "+f"(d[9]), "+f"(d[10]), "+f"(d[11])
    : "r"(a0), "r"(a1), "r"(a2), "r"(a3), "r"(b), "n"(BHI));
}
template<uint32_t BHI> __device__ __forceinline__ void wg_rs_z_n24(float* d, uint32_t a0, uint32_t a1, uint32_t a2, uint32_t a3, uint32_t b) {
  asm volatile("{\n.reg .pred p;\n.reg .b64 db;\nsetp.ne.b32 p, 0, 0;\nmov.b64 db, {%16, %17};\n"
    "wgmma.mma_async.sync.aligned.m64n24k16.f32.bf16.bf16 {%0, %1, %2, %3, %4, %5, %6, %7, %8, %9, %10, %11}, {%12, %13, %14, %15}, db, p, 1, 1, 1;\n}\n"
    : "=f"(d[0]), "=f"(d[1]), "=f"(d[2]), "=f"(d[3]), "=f"(d[4]), "=f"(d[5]), "=f"(d[6]), "=f"(d[7]), "=f"(d[8]), "=f"(d[9]), "=f"(d[10]), "=f"(d[11])
    : "r"(a0), "r"(a1), "r"(a2), "r"(a3), "r"(b), "n"(BHI));
}

__device__ __forceinline__ void wg_fence() { asm volatile("wgmma.fence.sync.aligned;" ::: "memory"); }
__device__ __forceinline__ void wg_commit() { asm volatile("wgmma.commit_group.sync.aligned;" ::: "memory"); }
template <int N> __device__ __forceinline__ void wg_wait() { asm volatile("wgmma.wait_group.sync.aligned %0;" ::"n"(N) : "memory"); }
template <int R> __device__ __forceinline__ void pin(float* d) {
#pragma unroll
  for (int i = 0; i < R; i++) asm volatile("" : "+f"(d[i])::"memory");
}
template <int R> __device__ __forceinline__ void pin(uint32_t* d) {
#pragma unroll
  for (int i = 0; i < R; i++) asm volatile("" : "+r"(d[i])::"memory");
}
__device__ __forceinline__ float ex2(float x) { float y; asm("ex2.approx.ftz.f32 %0, %1;" : "=f"(y) : "f"(x)); return y; }
__device__ __forceinline__ float tanh_fast(float x) { float y; asm("tanh.approx.f32 %0, %1;" : "=f"(y) : "f"(x)); return y; }
__device__ __forceinline__ uint32_t pack(float lo, float hi) { uint32_t r; asm("cvt.rn.bf16x2.f32 %0, %1, %2;" : "=r"(r) : "f"(hi), "f"(lo)); return r; }
__device__ __forceinline__ float bf_lo(uint32_t v) { return __uint_as_float(v << 16); }
__device__ __forceinline__ float bf_hi(uint32_t v) { return __uint_as_float(v & 0xffff0000u); }
__device__ __forceinline__ float bf_round(float x) { return bf_lo(pack(x, 0.f)); }

__device__ __forceinline__ void mbar_init(uint32_t bar, uint32_t cnt) { asm volatile("mbarrier.init.shared::cta.b64 [%0], %1;" ::"r"(bar), "r"(cnt) : "memory"); }
__device__ __forceinline__ void mbar_expect(uint32_t bar, uint32_t bytes) { asm volatile("mbarrier.arrive.expect_tx.shared::cta.b64 _, [%0], %1;" ::"r"(bar), "r"(bytes) : "memory"); }
__device__ __forceinline__ void mbar_arrive(uint32_t bar) { asm volatile("mbarrier.arrive.shared::cta.b64 _, [%0];" ::"r"(bar) : "memory"); }
__device__ __forceinline__ void mbar_wait(uint32_t bar, uint32_t parity) {
  asm volatile(
      "{\n.reg .pred p;\n.reg .u32 c;\n"
      "mbarrier.try_wait.parity.shared::cta.b64 p, [%0], %1;\n"
      "@p bra.uni DONE;\n"
      "mov.u32 c, 0;\n"
      "LOOP:\n"
      "mbarrier.try_wait.parity.shared::cta.b64 p, [%0], %1;\n"
      "@p bra.uni DONE;\n"
      "add.u32 c, c, 1;\n"
      "setp.lt.u32 p, c, 0x4000000;\n"
      "@p bra.uni LOOP;\n"
      "trap;\n"
      "DONE:\n}\n" ::"r"(bar), "r"(parity) : "memory");
}
__device__ __forceinline__ uint32_t mbar_test(uint32_t bar, uint32_t parity) {
  uint32_t ok;
  asm volatile("{\n.reg .pred p;\nmbarrier.test_wait.parity.shared::cta.b64 p, [%1], %2;\nselp.u32 %0, 1, 0, p;\n}\n" : "=r"(ok) : "r"(bar), "r"(parity) : "memory");
  return ok;
}
__device__ __forceinline__ void mbar_wait2_unless(uint32_t ok, uint32_t bar0, uint32_t par0, uint32_t bar1, uint32_t par1) {
  asm volatile(
      "{\n.reg .pred p, q;\n.reg .u32 c;\n"
      "setp.ne.u32 p, %0, 0;\n"
      "vote.sync.all.pred p, p, 0xffffffff;\n"
      "@p bra.uni DONE;\n"
      "mov.u32 c, 0;\n"
      "LOOP:\n"
      "mbarrier.try_wait.parity.shared::cta.b64 p, [%1], %2;\n"
      "mbarrier.try_wait.parity.shared::cta.b64 q, [%3], %4;\n"
      "and.pred p, p, q;\n"
      "vote.sync.all.pred p, p, 0xffffffff;\n"
      "@p bra.uni DONE;\n"
      "add.u32 c, c, 1;\n"
      "setp.lt.u32 p, c, 0x4000000;\n"
      "@p bra.uni LOOP;\n"
      "trap;\n"
      "DONE:\n}\n" ::"r"(ok), "r"(bar0), "r"(par0), "r"(bar1), "r"(par1) : "memory");
}
__device__ __forceinline__ void mbar_arrive_if(uint32_t bar, uint32_t cond) {
  asm volatile("{\n.reg .pred p;\nsetp.ne.u32 p, %1, 0;\n@p mbarrier.arrive.shared::cta.b64 _, [%0];\n}\n" ::"r"(bar), "r"(cond) : "memory");
}
__device__ __forceinline__ void mma16816(float* c, const uint32_t* a, uint32_t b0, uint32_t b1) {
  asm("mma.sync.aligned.m16n8k16.row.col.f32.bf16.bf16.f32 {%0,%1,%2,%3}, {%4,%5,%6,%7}, {%8,%9}, {%0,%1,%2,%3};"
      : "+f"(c[0]), "+f"(c[1]), "+f"(c[2]), "+f"(c[3]) : "r"(a[0]), "r"(a[1]), "r"(a[2]), "r"(a[3]), "r"(b0), "r"(b1));
}
__device__ __forceinline__ uint32_t bsub2(uint32_t a, uint32_t b) { uint32_t d; asm("sub.rn.bf16x2 %0, %1, %2;" : "=r"(d) : "r"(a), "r"(b)); return d; }
__device__ __forceinline__ uint32_t bscale2(uint32_t d, uint32_t hi, uint32_t lo) {
  uint32_t t, r;
  asm("mul.rn.bf16x2 %0, %1, %2;" : "=r"(t) : "r"(d), "r"(lo));
  asm("fma.rn.bf16x2 %0, %1, %2, %3;" : "=r"(r) : "r"(d), "r"(hi), "r"(t));
  return r;
}
__device__ __forceinline__ void flag_wait(const uint32_t* f, uint32_t target) {
  asm volatile(
      "{\n.reg .pred p;\n.reg .u32 c, v;\n"
      "mov.u32 c, 0;\n"
      "LOOP:\n"
      "ld.acquire.gpu.global.u32 v, [%0];\n"
      "setp.ge.u32 p, v, %1;\n"
      "@p bra DONE;\n"
      "add.u32 c, c, 1;\n"
      "setp.lt.u32 p, c, 0x1000000;\n"
      "@p bra LOOP;\n"
      "trap;\n"
      "DONE:\n}\n" ::"l"(f), "r"(target) : "memory");
}
__device__ __forceinline__ void flag_add(uint32_t* f) { asm volatile("red.relaxed.gpu.global.add.u32 [%0], 1;" ::"l"(f) : "memory"); }
__device__ __forceinline__ void fence_gpu() { asm volatile("fence.acq_rel.gpu;" ::: "memory"); }
__device__ __forceinline__ void fence_async() { asm volatile("fence.proxy.async;" ::: "memory"); }
__device__ __forceinline__ void tma2d(uint32_t dst, const CUtensorMap* tm, uint32_t bar, int c0, int c1) {
  asm volatile("cp.async.bulk.tensor.2d.shared::cluster.global.mbarrier::complete_tx::bytes [%0], [%1, {%3, %4}], [%2];" ::"r"(dst), "l"(tm), "r"(bar), "r"(c0), "r"(c1) : "memory");
}
__device__ __forceinline__ void tma5d(uint32_t dst, const CUtensorMap* tm, uint32_t bar, int c0, int c4) {
  asm volatile("cp.async.bulk.tensor.5d.shared::cluster.global.mbarrier::complete_tx::bytes [%0], [%1, {%3, %5, %5, %5, %4}], [%2];" ::"r"(dst), "l"(tm), "r"(bar), "r"(c0), "r"(c4), "r"(0) : "memory");
}
__device__ __forceinline__ void pf2d(const CUtensorMap* tm, int c0, int c1) {
  asm volatile("cp.async.bulk.prefetch.tensor.2d.L2.global [%0, {%1, %2}];" ::"l"(tm), "r"(c0), "r"(c1) : "memory");
}
__device__ __forceinline__ void pf5d(const CUtensorMap* tm, int c0, int c4) {
  asm volatile("cp.async.bulk.prefetch.tensor.5d.L2.global [%0, {%1, %3, %3, %3, %2}];" ::"l"(tm), "r"(c0), "r"(c4), "r"(0) : "memory");
}

struct Att {
  float s[32];
  float o[12];
  uint32_t p[16];
  uint32_t q[8];
};

__device__ __forceinline__ void attn_slow_rows(int cta, int j, int hp, int row_base, int tid_base) {
  const int lane = threadIdx.x & 31;
  const uint32_t* kv = g_KV + (size_t)(4 * j + hp) * SEQ * 20;
#pragma unroll 1
  for (int r = 0; r < 16; r++) {
    float q[18], acc[18];
#pragma unroll
    for (int v = 0; v < 9; v++) {
      uint32_t u = g_Q[((cta * 4 + hp) * 256 + tid_base + (r & 7) * 4 + ((v + hp) & 3)) * 8 + 2 * (v >> 2) + (r >> 3)];
      q[2 * v] = bf_lo(u); q[2 * v + 1] = bf_hi(u);
      acc[2 * v] = 0.f; acc[2 * v + 1] = 0.f;
    }
    float mx = -INFINITY, l = 0.f;
#pragma unroll 1
    for (int key = lane; key < SEQ; key += 32) {
      const uint32_t* kr = kv + (key >> 3) * 160 + (key & 7) * 4;
      float s = 0.f;
#pragma unroll
      for (int v = 0; v < 9; v++) {
        uint32_t u = kr[(v >> 2) * 32 + ((v + hp) & 3)];
        s = fmaf(q[2 * v], bf_lo(u), s); s = fmaf(q[2 * v + 1], bf_hi(u), s);
      }
      float mn = fmaxf(mx, s), c = exp2f(mx - mn), p = exp2f(s - mn);
      mx = mn; l = l * c + p;
#pragma unroll
      for (int v = 0; v < 9; v++) {
        uint32_t u = v < 8 ? kr[(3 + (v >> 2)) * 32 + ((v + hp) & 3)] : kr[2 * 32 + ((hp + 2) & 3)];
        acc[2 * v] = fmaf(p, bf_lo(u), acc[2 * v] * c); acc[2 * v + 1] = fmaf(p, bf_hi(u), acc[2 * v + 1] * c);
      }
    }
    float gm = mx;
#pragma unroll
    for (int d = 16; d; d >>= 1) gm = fmaxf(gm, __shfl_xor_sync(0xffffffffu, gm, d));
    float c = exp2f(mx - gm);
    l *= c;
#pragma unroll
    for (int d = 16; d; d >>= 1) l += __shfl_xor_sync(0xffffffffu, l, d);
    uint32_t* orow = reinterpret_cast<uint32_t*>(g_O + (size_t)(row_base + r) * DM + 18 * (4 * j + hp));
#pragma unroll
    for (int v = 0; v < 9; v++) {
      float a = acc[2 * v] * c, b = acc[2 * v + 1] * c;
#pragma unroll
      for (int d = 16; d; d >>= 1) { a += __shfl_xor_sync(0xffffffffu, a, d); b += __shfl_xor_sync(0xffffffffu, b, d); }
      if (lane == 0) orow[v] = pack(a / l, b / l);
    }
  }
}

__device__ __forceinline__ bool o_epilogue(float* o, int hp, int j, int row0, int lane) {
  const int t = lane & 3, src = (lane & ~3) | ((hp + 1) & 3);
  float l0 = __shfl_sync(0xffffffffu, o[0], src), l1 = __shfl_sync(0xffffffffu, o[2], src);
  float sa = 0.f;
#pragma unroll
  for (int i = 0; i < 12; i++) sa += fabsf(o[i]);
  bool ok = (l0 <= 1.329228e36f) && (l1 <= 1.329228e36f) && (l0 > 0.f) && (l1 > 0.f) && (sa <= 3.0e38f);
  float i0 = __frcp_rn(l0), i1 = __frcp_rn(l1);
  uint32_t* r0 = reinterpret_cast<uint32_t*>(g_O + (size_t)row0 * DM + 18 * (4 * j + hp));
  uint32_t* r1 = r0 + 8 * (DM / 2);
  const int v = (t - hp) & 3;
  r0[v] = pack(o[4] * i0, o[5] * i0);
  r1[v] = pack(o[6] * i1, o[7] * i1);
  r0[v + 4] = pack(o[8] * i0, o[9] * i0);
  r1[v + 4] = pack(o[10] * i1, o[11] * i1);
  if (t == ((hp + 2) & 3)) { r0[8] = pack(o[0] * i0, o[1] * i0); r1[8] = pack(o[2] * i1, o[3] * i1); }
  return __any_sync(0xffffffffu, !ok);
}

__device__ __forceinline__ void issue_pv(Att& a, uint32_t kdesc) {
  const uint32_t vdesc = kdesc + 192 + (LO_V - LO_K);
#pragma unroll
  for (int k = 0; k < 4; k++) wg_rs_n24<HI_V>(a.o, a.p[4 * k], a.p[4 * k + 1], a.p[4 * k + 2], a.p[4 * k + 3], vdesc + k * 48);
}
__device__ __forceinline__ void issue_att(Att& a, uint32_t kdesc) {
  issue_pv(a, kdesc);
  wg_rs_z_n64<HI_K>(a.s, a.q[0], a.q[1], a.q[2], a.q[3], kdesc);
  wg_rs_n64<HI_K>(a.s, a.q[4], a.q[5], a.q[6], a.q[7], kdesc + 16);
}
__device__ __forceinline__ void softmax_tile(Att& a) {
#pragma unroll
  for (int i = 0; i < 16; i++) a.p[i] = pack(ex2(a.s[2 * i]), ex2(a.s[2 * i + 1]));
  pin<16>(a.p);
}
__device__ __forceinline__ void first_tile(Att& a, int hp, int lane) {
  float m0 = fmaxf(a.s[0], a.s[1]), m1 = fmaxf(a.s[2], a.s[3]);
#pragma unroll
  for (int i = 4; i < 32; i += 4) { m0 = fmaxf(m0, fmaxf(a.s[i], a.s[i + 1])); m1 = fmaxf(m1, fmaxf(a.s[i + 2], a.s[i + 3])); }
  m0 = fmaxf(m0, __shfl_xor_sync(0xffffffffu, m0, 1)); m1 = fmaxf(m1, __shfl_xor_sync(0xffffffffu, m1, 1));
  m0 = fmaxf(m0, __shfl_xor_sync(0xffffffffu, m0, 2)); m1 = fmaxf(m1, __shfl_xor_sync(0xffffffffu, m1, 2));
  float n0 = -(m0 + MOFF), n1 = -(m1 + MOFF);
  float h0 = bf_round(n0), h1 = bf_round(n1);
  uint32_t e0 = pack(h0, n0 - h0), e1 = pack(h1, n1 - h1);
  n0 = h0 + bf_hi(e0); n1 = h1 + bf_hi(e1);
  if ((lane & 3) == ((hp + 1) & 3)) { a.q[4] = e0; a.q[5] = e1; }
#pragma unroll
  for (int i = 0; i < 32; i += 4) { a.s[i] += n0; a.s[i + 1] += n0; a.s[i + 2] += n1; a.s[i + 3] += n1; }
#pragma unroll
  for (int i = 0; i < 12; i++) a.o[i] = 0.f;
  pin<12>(a.o); pin<8>(a.q);
}
__device__ __forceinline__ void load_q(Att& a, int cta, int hp, int tid) {
  const uint32_t* src = g_Q + ((cta * 4 + hp) * 256 + tid) * 8;
  const uint4 u = __ldcg(reinterpret_cast<const uint4*>(src));
  const uint4 v = __ldcg(reinterpret_cast<const uint4*>(src + 4));
  a.q[0] = u.x; a.q[1] = u.y; a.q[2] = u.z; a.q[3] = u.w; a.q[4] = v.x; a.q[5] = v.y; a.q[6] = v.z; a.q[7] = v.w;
}
__device__ __forceinline__ void h_epilogue(float* acc, __nv_bfloat16* dst) {
#pragma unroll
  for (int b = 0; b < 2; b++) {
    uint32_t w0[4], w1[4];
#pragma unroll
    for (int i = 0; i < 4; i++) {
      float h[4];
#pragma unroll
      for (int e = 0; e < 4; e++) {
        float g = acc[(4 * b + i) * 4 + e], u = 0.5f * acc[32 + (4 * b + i) * 4 + e];
        h[e] = fmaf(tanh_fast(0.5f * g), u, u);
      }
      w0[i] = pack(h[0], h[1]); w1[i] = pack(h[2], h[3]);
    }
    *reinterpret_cast<uint4*>(dst + 32 * b) = make_uint4(w0[0], w0[1], w0[2], w0[3]);
    *reinterpret_cast<uint4*>(dst + 32 * b + 8 * FF) = make_uint4(w1[0], w1[1], w1[2], w1[3]);
  }
}

template <int Q> __device__ __forceinline__ void final_store(const float* acc, float* own, int m, int hh, int tid, uint32_t tag) {
  float4* pw = g_P + (size_t)((m * 2 + hh) * 16 + Q * 4) * 9 * 256 + tid;
#pragma unroll
  for (int dd = 1; dd < 4; dd++) {
    const int d = (Q + dd) & 3;
#pragma unroll
    for (int i = 0; i < 9; i++) {
      const float* v = acc + 36 * d + 4 * i;
      asm volatile("st.relaxed.gpu.global.v4.b32 [%0], {%1,%2,%3,%4};" ::"l"(pw + (d * 9 + i) * 256), "r"((__float_as_uint(v[0]) & ~1u) | tag),
                   "r"((__float_as_uint(v[1]) & ~1u) | tag), "r"((__float_as_uint(v[2]) & ~1u) | tag), "r"((__float_as_uint(v[3]) & ~1u) | tag) : "memory");
    }
  }
#pragma unroll
  for (int i = 0; i < 36; i++) own[i] = acc[36 * Q + i];
}
__device__ __forceinline__ void final_reduce(float* own, const Params& prm, int m, int hh, int q, int tid, int row0, int lane, uint32_t tag) {
  const int col = 288 * hh + 72 * q + 2 * (lane & 3);
  const uint32_t* xr = reinterpret_cast<const uint32_t*>(prm.x + (size_t)row0 * DM + col);
  uint32_t xa[9], xb[9];
#pragma unroll
  for (int i = 0; i < 9; i++) { xa[i] = __ldg(xr + 4 * i); xb[i] = __ldg(xr + 4 * i + 8 * (DM / 2)); }
  const float4* pr = g_P + (size_t)((m * 2 + hh) * 16 + q) * 9 * 256 + tid;
  uint32_t v[3][36];
  uint32_t tries = 0;
  while (true) {
    uint32_t all = 1, any = 0;
#pragma unroll
    for (int d = 0; d < 3; d++) {
#pragma unroll
      for (int i = 0; i < 9; i++)
        asm volatile("ld.relaxed.gpu.global.v4.b32 {%0,%1,%2,%3}, [%4];" : "=r"(v[d][4 * i]), "=r"(v[d][4 * i + 1]), "=r"(v[d][4 * i + 2]), "=r"(v[d][4 * i + 3])
                     : "l"(pr + (((q + 3 - d) & 3) * 36 + i) * 256) : "memory");
    }
#pragma unroll
    for (int d = 0; d < 3; d++)
#pragma unroll
      for (int i = 0; i < 36; i++) { all &= v[d][i]; any |= v[d][i]; }
    if (__all_sync(0xffffffffu, ((tag ? all : ~any) & 1) != 0)) break;
    if (++tries > 0x100000u) asm volatile("trap;");
  }
#pragma unroll
  for (int i = 0; i < 36; i++) own[i] += (__uint_as_float(v[0][i]) + __uint_as_float(v[1][i])) + __uint_as_float(v[2][i]);
  uint32_t* orow = reinterpret_cast<uint32_t*>(prm.out + (size_t)row0 * DM + col);
#pragma unroll
  for (int i = 0; i < 9; i++) {
    orow[4 * i] = pack(own[4 * i] + bf_lo(xa[i]), own[4 * i + 1] + bf_hi(xa[i]));
    orow[4 * i + 8 * (DM / 2)] = pack(own[4 * i + 2] + bf_lo(xb[i]), own[4 * i + 3] + bf_hi(xb[i]));
  }
}

__global__ void __launch_bounds__(384, 1) fused_kernel(const __grid_constant__ Params prm) {
  extern __shared__ __align__(1024) uint8_t smem[];
  const uint32_t sb = (uint32_t)__cvta_generic_to_shared(smem);
  const uint32_t bar = sb + SM_BAR;
  const int m = blockIdx.x & 15, j = blockIdx.x >> 4;
  const int cta = m * 8 + j;
  const int wr = __shfl_sync(0xffffffffu, (int)(threadIdx.x >> 5), 0);
  const int wg = wr >> 2;
  const int lane = threadIdx.x & 31;
  STAMP(0);
  if (wg < 2) {
    if (lane == 0) {
      const uint32_t xb = bar + 8 * (B_X + wr);
      mbar_init(xb, 1);
      asm volatile("fence.proxy.async.shared::cta;" ::: "memory");
      mbar_expect(xb, 9 * 2048);
#pragma unroll
      for (int c = 0; c < 9; c++) tma2d(sb + SM_XN + c * 16384 + wr * 2048, &prm.xm, xb, 64 * c, 128 * m + 16 * wr);
    }
  } else if (threadIdx.x == 256) {
    if (sb & 1023) asm volatile("trap;");
#pragma unroll
    for (int i = 0; i < 3; i++) { mbar_init(bar + 8 * (B_QF + i), 1); mbar_init(bar + 8 * (B_QE + i), 8); mbar_init(bar + 8 * (B_GF + i), 1); mbar_init(bar + 8 * (B_GE + i), 8); mbar_init(bar + 8 * (B_KF + i), 1); mbar_init(bar + 8 * (B_KE + i), 8); }
#pragma unroll
    for (int i = 0; i < 4; i++) { mbar_init(bar + 8 * (B_BF + i), 1); mbar_init(bar + 8 * (B_BE + i), 8); }
    mbar_init(bar + 8 * B_SKV, 8); mbar_init(bar + 8 * B_SH, 8); mbar_init(bar + 8 * B_SO1, 8); mbar_init(bar + 8 * B_SO2, 8); mbar_init(bar + 8 * B_OL, 1);
    asm volatile("fence.proxy.async.shared::cta;" ::: "memory");
  }
  __syncthreads();

  if (wg == 2) {
    asm volatile("setmaxnreg.dec.sync.aligned.u32 24;");
    const int pw = wr & 3;
    if (lane == 0) {
      if (pw == 0) {
#pragma unroll 1
        for (int kb = 0; kb < 9; kb++) {
          const int s = kb % 3;
          if (kb >= 3) mbar_wait(bar + 8 * (B_QE + s), (kb / 3 - 1) & 1);
          else if (kb == 1) mbar_wait(bar + 8 * (B_X + 7), 0);
          const uint32_t fb = bar + 8 * (B_QF + s), dst = sb + SM_RING + s * QST;
          mbar_expect(fb, QST);
#pragma unroll
          for (int p = 0; p < 3; p++) {
            tma2d(dst + p * 8192, &prm.wqkv64, fb, 576 * p + 72 * j, 64 * kb);
            tma2d(dst + 24576 + p * 1024, &prm.wqkv8, fb, 576 * p + 72 * j + 64, 64 * kb);
          }
        }
        int tau = 0, kb = 0;
#pragma unroll 1
        for (int s = 0; s < 81; s++) {
          const int slot = s & 3;
          if (s >= 4) mbar_wait(bar + 8 * (B_BE + slot), ((s >> 2) - 1) & 1);
          else if (s != 2) mbar_wait(bar + 8 * (B_QE + (s == 3 ? 2 : s)), 0);
          const uint32_t fb = bar + 8 * (B_BF + slot), dst = sb + SM_RING + slot * BST;
          mbar_expect(fb, BST);
          tma2d(dst, &prm.wg, fb, 576 * j + 64 * tau, 64 * kb);
          tma2d(dst + 8192, &prm.wu, fb, 576 * j + 64 * tau, 64 * kb);
          if (++kb == 9) { kb = 0; tau++; }
        }
        mbar_arrive(bar + 8 * (B_BF + 1));
        const int hh = j & 1;
#pragma unroll 1
        for (int b = 0; b < 20; b++) {
          const int st = b % 3;
          if (b >= 3) mbar_wait(bar + 8 * (B_GE + st), (b / 3 - 1) & 1);
          else if (b == 1) mbar_wait(bar + 8 * (B_BE + 2), 1);
          else if (b == 2) mbar_wait(bar + 8 * (B_BE + 0), 0);
          const uint32_t fb = bar + 8 * (B_GF + st), dst = sb + st * G2ST;
          if (b == 0) STAMPW(16);
          if (b < 18) {
            mbar_expect(fb, G2ST);
            const int own = (b < 8 || b == 16), tile = b < 16 ? (b & 7) : 8;
            const int jj = own ? j : (j ^ 1);
            const int kc = 576 * jj + 64 * tile;
#pragma unroll
            for (int a = 0; a < 5; a++) tma5d(dst + 16384 + a * 8192, &prm.wd[hh], fb, 64 * a, kc >> 5);
            flag_wait(FLAG_H(m * 8 + jj), tile + 1);
            fence_async();
            tma2d(dst, &prm.h, fb, kc, 128 * m);
          } else {
            const int kc = 144 * (j >> 1);
            mbar_expect(fb, b == 18 ? G2ST : G2ST + 10240);
#pragma unroll
            for (int a = 0; a < 5; a++) tma2d(dst + 16384 + a * 8192, &prm.wo[hh], fb, 64 * a, kc + 64 * (b - 18));
            if (b == 18) { flag_wait(FLAG_O(cta), 1); flag_wait(FLAG_O(cta ^ 1), 1); fence_async(); }
            else {
#pragma unroll
              for (int a = 0; a < 5; a++) tma2d(sb + SM_W16 + a * 2048, &prm.wo16[hh], fb, 64 * a, kc + 128);
            }
            tma2d(dst, &prm.o, fb, kc + 80 * (b - 18), 128 * m);
          }
          if (b == 0) STAMPW(17);
        }
      } else if (pw == 1) {
        flag_wait(FLAG_KV(j), 16);
        fence_async();
        STAMPW(18);
        int slot = 0, ph = 1, vrow = 0;
        const int hx = (j & 1) * 3;
#pragma unroll 1
        for (int u = 0; u <= 128; u++) {
          if (u >= 3) mbar_wait(bar + 8 * (B_KE + slot), ph);
          const uint32_t fb = bar + 8 * (B_KF + slot), dst = sb + SM_KV + slot * KVST;
          const int krow = (4 * j + ((u >> 5) ^ hx)) * 256 + ((u + 2 * m) & 31) * 8;
          if (u == 0) vrow = krow;
          mbar_expect(fb, u < 128 ? KVST : KVST / 2);
          if (u < 128) tma2d(dst, &prm.kv, fb, 0, krow);
          tma2d(dst + 3072, &prm.kv, fb, 128, vrow);
          vrow = krow;
          if (++slot == 3) { slot = 0; ph ^= 1; }
        }
        mbar_expect(bar + 8 * B_OL, 16384);
        flag_wait(FLAG_O(cta), 2); flag_wait(FLAG_O(cta ^ 1), 2);
        fence_async();
        STAMPW(19);
        tma2d(sb + SM_OL, &prm.o, bar + 8 * B_OL, 144 * (j >> 1) + 48, 128 * m);
      } else if (pw == 2) {
        mbar_wait(bar + 8 * B_SKV, 0);
        fence_gpu(); fence_async(); flag_add(FLAG_KV(j));
        STAMPW(20);
#pragma unroll 1
        for (int t = 0; t < 9; t++) { mbar_wait(bar + 8 * B_SH, t & 1); fence_gpu(); fence_async(); flag_add(FLAG_H(cta)); }
        mbar_wait(bar + 8 * B_SO1, 0);
        fence_gpu(); fence_async(); flag_add(FLAG_O(cta));
        mbar_wait(bar + 8 * B_SO2, 0);
        fence_gpu(); fence_async(); flag_add(FLAG_O(cta));
        STAMPW(21);
      } else {
        if (m >= 1 && m < 9) {
#pragma unroll
          for (int p = 0; p < 3; p++) { pf2d(&prm.wqkv64, 576 * p + 72 * j, 64 * m); pf2d(&prm.wqkv8, 576 * p + 72 * j + 64, 64 * m); }
        }
        mbar_wait(bar + 8 * (B_X + 7), 0);
#pragma unroll 1
        for (int b = m; b < 162; b += 16) {
          const int s = b >> 1;
          pf2d((b & 1) ? &prm.wu : &prm.wg, 576 * j + 64 * (s / 9), 64 * (s % 9));
        }
        mbar_wait(bar + 8 * B_SH, 0);
#pragma unroll 1
        for (int b = m; b < 90; b += 16) pf5d(&prm.wd[j & 1], 64 * (b % 5), 36 * (j >> 1) + 2 * (b / 5));
        if (m < 15) pf2d(&prm.wo[j & 1], 64 * (m % 5), 144 * (j >> 1) + 64 * (m / 5));
      }
    }
  } else {
    asm volatile("setmaxnreg.inc.sync.aligned.u32 240;");
    const int tid = threadIdx.x;
    const int w = wr & 3, t = lane & 3;
    const int row0 = 128 * m + 64 * wg + 16 * w + (lane >> 2);
    const uint32_t l0 = lane == 0;
    {
      uint32_t v[36][4];
      const int lr = wr * 16 + (lane & 15);
      const uint32_t rb = sb + SM_XN + lr * 128;
      mbar_wait(bar + 8 * (B_X + wr), 0);
      STAMP(11);
#pragma unroll
      for (int i = 0; i < 36; i++)
        asm volatile("ldmatrix.sync.aligned.m8n8.x4.shared.b16 {%0,%1,%2,%3}, [%4];" : "=r"(v[i][0]), "=r"(v[i][1]), "=r"(v[i][2]), "=r"(v[i][3])
                     : "r"(rb + (i >> 2) * 16384 + (((2 * (i & 3) + (lane >> 4)) ^ (lr & 7)) << 4)) : "memory");
      float cs[2][4] = {}, c0[2][4] = {}, c1[2][4] = {};
#pragma unroll
      for (int i = 0; i < 36; i++) {
        mma16816(cs[i & 1], v[i], 0x3f803f80u, 0x3f803f80u);
        mma16816(c0[i & 1], v[i], v[i][0], v[i][2]);
        mma16816(c1[i & 1], v[i], v[i][1], v[i][3]);
      }
      const int g = lane >> 2, src = (lane & ~3) | (g >> 1);
      const float mean0 = (cs[0][0] + cs[1][0]) * (1.f / 576.f), mean1 = (cs[0][2] + cs[1][2]) * (1.f / 576.f);
      float var0 = __shfl_sync(0xffffffffu, (g & 1) ? c0[0][1] + c0[1][1] : c0[0][0] + c0[1][0], src) * (1.f / 576.f) - mean0 * mean0;
      float var1 = __shfl_sync(0xffffffffu, (g & 1) ? c1[0][3] + c1[1][3] : c1[0][2] + c1[1][2], src) * (1.f / 576.f) - mean1 * mean1;
      if (__any_sync(0xffffffffu, !(mean0 * mean0 <= 8.f * var0) || !(mean1 * mean1 <= 8.f * var1))) {
        float q0 = 0.f, q1 = 0.f;
#pragma unroll
        for (int i = 0; i < 36; i++)
#pragma unroll
          for (int e = 0; e < 4; e += 2) {
            float a = bf_lo(v[i][e]) - mean0, b = bf_hi(v[i][e]) - mean0, c = bf_lo(v[i][e + 1]) - mean1, d = bf_hi(v[i][e + 1]) - mean1;
            q0 = fmaf(a, a, fmaf(b, b, q0)); q1 = fmaf(c, c, fmaf(d, d, q1));
          }
        q0 += __shfl_xor_sync(0xffffffffu, q0, 1); q0 += __shfl_xor_sync(0xffffffffu, q0, 2);
        q1 += __shfl_xor_sync(0xffffffffu, q1, 1); q1 += __shfl_xor_sync(0xffffffffu, q1, 2);
        var0 = q0 * (1.f / 576.f); var1 = q1 * (1.f / 576.f);
      }
      const float inv0 = __frcp_rn(bf_round(sqrtf(bf_round(bf_round(var0) + 1e-5f)))), inv1 = __frcp_rn(bf_round(sqrtf(bf_round(bf_round(var1) + 1e-5f))));
      const uint32_t mb0 = pack(mean0, mean0), mb1 = pack(mean1, mean1);
      const uint32_t h0 = pack(inv0, inv0), h1 = pack(inv1, inv1);
      const uint32_t e0 = pack(inv0 - bf_lo(h0), inv0 - bf_lo(h0)), e1 = pack(inv1 - bf_lo(h1), inv1 - bf_lo(h1));
#pragma unroll
      for (int i = 0; i < 36; i++)
        asm volatile("stmatrix.sync.aligned.m8n8.x4.shared.b16 [%0], {%1,%2,%3,%4};" ::"r"(rb + (i >> 2) * 16384 + (((2 * (i & 3) + (lane >> 4)) ^ (lr & 7)) << 4)),
                     "r"(bscale2(bsub2(v[i][0], mb0), h0, e0)), "r"(bscale2(bsub2(v[i][1], mb1), h1, e1)),
                     "r"(bscale2(bsub2(v[i][2], mb0), h0, e0)), "r"(bscale2(bsub2(v[i][3], mb1), h1, e1)) : "memory");
      asm volatile("fence.proxy.async.shared::cta;" ::: "memory");
      if (wg == 0) asm volatile("bar.sync 1, 128;" ::: "memory"); else asm volatile("bar.sync 2, 128;" ::: "memory");
    }
    STAMP(1);
    const uint32_t adesc = (((sb + SM_XN + wg * 8192) & 0x3FFFF) >> 4) | LO_A;
    const uint32_t bdesc = (((sb + SM_RING) & 0x3FFFF) >> 4) | LO_B;
    const uint32_t kdesc0 = (((sb + SM_KV) & 0x3FFFF) >> 4) | LO_K;
    const int hx = (j & 1) * 3;
    float accA[64], accB[64];
    Att a;
    uint32_t badmask = 0;
#define G1_ISSUE(ACC, KB, SLOT) _Pragma("unroll") for (int k = 0; k < 4; k++) wg_ss_n128<HI_SW128, HI_SW128>(ACC, adesc + (KB) * 1024 + k * 2, bdesc + (SLOT) * 1024 + k * 128);
#define G1_ISSUE_Z(ACC, SLOT)                                                                                  \
  wg_ss_z_n128<HI_SW128, HI_SW128>(ACC, adesc, bdesc + (SLOT) * 1024);                                         \
  _Pragma("unroll") for (int k = 1; k < 4; k++) wg_ss_n128<HI_SW128, HI_SW128>(ACC, adesc + k * 2, bdesc + (SLOT) * 1024 + k * 128);
    {
      float aq[96], ar[12];
      const uint32_t rdesc = (((sb + SM_RING + 24576) & 0x3FFFF) >> 4) | LO_R;
      mbar_wait(bar + 8 * B_QF, 0);
      wg_fence();
      wg_ss_z_n192<HI_SW128, HI_SW128>(aq, adesc, bdesc);
      wg_ss_z_n24<HI_SW128, HI_R>(ar, adesc, rdesc);
#pragma unroll
      for (int k = 1; k < 4; k++) {
        wg_ss_n192<HI_SW128, HI_SW128>(aq, adesc + k * 2, bdesc + k * 128);
        wg_ss_n24<HI_SW128, HI_R>(ar, adesc + k * 2, rdesc + k * 16);
      }
      wg_commit();
      int s = 1, ph = 0;
#pragma unroll 1
      for (int kb = 1; kb < 9; kb++) {
        mbar_wait(bar + 8 * (B_QF + s), ph);
        wg_fence();
#pragma unroll
        for (int k = 0; k < 4; k++) {
          wg_ss_n192<HI_SW128, HI_SW128>(aq, adesc + kb * 1024 + k * 2, bdesc + s * (QST >> 4) + k * 128);
          wg_ss_n24<HI_SW128, HI_R>(ar, adesc + kb * 1024 + k * 2, rdesc + s * (QST >> 4) + k * 16);
        }
        wg_commit();
        wg_wait<1>();
        mbar_arrive_if(bar + 8 * (B_QE + (s == 0 ? 2 : s - 1)), l0);
        if (++s == 3) { s = 0; ph ^= 1; }
      }
      mbar_wait(bar + 8 * B_BF, 0);
      wg_fence();
      G1_ISSUE_Z(accA, 0)
      wg_commit();
      wg_wait<1>();
      pin<96>(aq); pin<12>(ar);
      mbar_arrive_if(bar + 8 * (B_QE + 2), l0);
      STAMP(2);
      uint32_t pk[3][9][2];
#pragma unroll
      for (int p = 0; p < 3; p++)
#pragma unroll
        for (int i = 0; i < 9; i++) {
          const float* src = i < 8 ? &aq[(8 * p + i) * 4] : &ar[4 * p];
          pk[p][i][0] = pack(src[0], src[1]); pk[p][i][1] = pack(src[2], src[3]);
        }
      uint32_t* kvp = g_KV + (size_t)(4 * j) * SEQ * 20 + (row0 >> 3) * 160 + lane;
#pragma unroll
      for (int hp = 0; hp < 4; hp++) {
        const bool up = t < hp;
#pragma unroll
        for (int rh = 0; rh < 2; rh++) {
          uint32_t* d = kvp + hp * SEQ * 20 + rh * 160;
          d[0] = up ? pk[1][2 * hp + 1][rh] : pk[1][2 * hp][rh];
          d[32] = up ? pk[1][2 * hp + 2][rh] : pk[1][2 * hp + 1][rh];
          d[96] = up ? pk[2][2 * hp + 1][rh] : pk[2][2 * hp][rh];
          d[128] = up ? pk[2][2 * hp + 2][rh] : pk[2][2 * hp + 1][rh];
          const uint32_t v9 = __shfl_sync(0xffffffffu, pk[2][2 * hp + 2][rh], (lane & ~3) | hp);
          d[64] = t == hp ? pk[1][2 * hp + 2][rh] : t == ((hp + 1) & 3) ? 0x3f803f80u : t == ((hp + 2) & 3) ? v9 : 0u;
        }
        if (hp & 1) {
          const int kb = 1 + (hp >> 1);
          mbar_wait(bar + 8 * (B_BF + kb), 0);
          wg_fence();
          G1_ISSUE(accA, kb, kb)
          wg_commit();
          wg_wait<1>();
          mbar_arrive_if(bar + 8 * (B_BE + kb - 1), l0);
        }
      }
      __syncwarp();
      mbar_arrive_if(bar + 8 * B_SKV, l0);
#pragma unroll
      for (int i = 0; i < 9; i++)
#pragma unroll
        for (int rh = 0; rh < 2; rh++) pk[0][i][rh] = pack(bf_lo(pk[0][i][rh]) * QSCALE, bf_hi(pk[0][i][rh]) * QSCALE);
      uint32_t* qp = g_Q + (cta * 4 * 256 + tid) * 8;
#pragma unroll
      for (int hp = 0; hp < 4; hp++) {
        const bool up = t < hp;
        *reinterpret_cast<uint4*>(qp + hp * 2048) = make_uint4(up ? pk[0][2 * hp + 1][0] : pk[0][2 * hp][0], up ? pk[0][2 * hp + 1][1] : pk[0][2 * hp][1],
                                                               up ? pk[0][2 * hp + 2][0] : pk[0][2 * hp + 1][0], up ? pk[0][2 * hp + 2][1] : pk[0][2 * hp + 1][1]);
        *reinterpret_cast<uint4*>(qp + hp * 2048 + 4) = make_uint4(t == hp ? pk[0][2 * hp + 2][0] : 0u, t == hp ? pk[0][2 * hp + 2][1] : 0u, 0u, 0u);
      }
      load_q(a, cta, hx, tid);
#pragma unroll
      for (int i = 0; i < 16; i++) a.p[i] = 0;
#pragma unroll
      for (int i = 0; i < 12; i++) a.o[i] = 0.f;
      pin<16>(a.p); pin<12>(a.o);
    }
    STAMP(3);
    int gs = 3;
#pragma unroll 1
    for (int kb = 3; kb < 9; kb++, gs++) {
      mbar_wait(bar + 8 * (B_BF + (gs & 3)), (gs >> 2) & 1);
      wg_fence();
      G1_ISSUE(accA, kb, gs & 3)
      wg_commit();
      wg_wait<1>();
      mbar_arrive_if(bar + 8 * (B_BE + ((gs - 1) & 3)), l0);
    }
    pin<8>(a.q);
    mbar_wait(bar + 8 * (B_BF + (gs & 3)), (gs >> 2) & 1);
    STAMP(4);
    uint32_t kslot = 0, kph = 0;
    __nv_bfloat16* hdst = g_H + (size_t)row0 * FF + 576 * j + 8 * t;

#define EPI_STEP(ACCN, ACCO)                                                                                   \
  {                                                                                                            \
    wg_fence();                                                                                                \
    G1_ISSUE_Z(ACCN, gs & 3)                                                                                   \
    wg_commit();                                                                                               \
    wg_wait<1>();                                                                                              \
    pin<64>(ACCO);                                                                                             \
    mbar_arrive_if(bar + 8 * (B_BE + ((gs - 1) & 3)), l0);                                                     \
    h_epilogue(ACCO, hdst);                                                                                    \
    hdst += 64;                                                                                                \
    __syncwarp();                                                                                              \
    mbar_arrive_if(bar + 8 * B_SH, l0);                                                                        \
    gs++;                                                                                                      \
    mbar_wait(bar + 8 * (B_BF + (gs & 3)), (gs >> 2) & 1);                                                     \
    mbar_wait(bar + 8 * B_KF + kslot * 8, kph);                                                                \
  }
#define ATT_STEP1(ACC, KB, FIRST, IT)                                                                          \
  {                                                                                                            \
    wg_fence();                                                                                                \
    issue_att(a, kdesc0 + kslot * 384);                                                                        \
    wg_commit();                                                                                               \
    G1_ISSUE(ACC, KB, gs & 3)                                                                                  \
    wg_commit();                                                                                               \
    wg_wait<1>();                                                                                              \
    pin<32>(a.s);                                                                                              \
    mbar_arrive_if(bar + 8 * (B_BE + ((gs - 1) & 3)), l0);                                                     \
    mbar_arrive_if(bar + 8 * B_KE + kslot * 8, l0);                                                            \
    gs++;                                                                                                      \
    if (++kslot == 3) { kslot = 0; kph ^= 1; }                                                                 \
    const uint32_t ok = mbar_test(bar + 8 * (B_BF + (gs & 3)), (gs >> 2) & 1) & mbar_test(bar + 8 * B_KF + kslot * 8, kph); \
    if (FIRST) {                                                                                               \
      pin<12>(a.o);                                                                                            \
      if ((IT) > 0) badmask |= (uint32_t)o_epilogue(a.o, ((IT) - 1) ^ hx, j, row0, lane) << (((IT) - 1) ^ hx); \
      first_tile(a, (IT) ^ hx, lane);                                                                          \
    }                                                                                                          \
    softmax_tile(a);                                                                                           \
    mbar_wait2_unless(ok, bar + 8 * (B_BF + (gs & 3)), (gs >> 2) & 1, bar + 8 * B_KF + kslot * 8, kph); \
  }

#pragma unroll 1
    for (int pr = 0; pr < 4; pr++) {
      if (pr == 2) load_q(a, cta, 1 ^ hx, tid);
      EPI_STEP(accB, accA);
      pin<8>(a.q);
      if ((pr & 1) == 0) ATT_STEP1(accB, 1, true, pr >> 1) else ATT_STEP1(accB, 1, false, 1);
#pragma unroll 1
      for (int kb = 2; kb < 9; kb++) ATT_STEP1(accB, kb, false, 1);
      EPI_STEP(accA, accB);
#pragma unroll 1
      for (int kb = 1; kb < 9; kb++) ATT_STEP1(accA, kb, false, 1);
    }
    STAMP(5);
    load_q(a, cta, 2 ^ hx, tid);
    wg_wait<0>();
    pin<64>(accA);
    mbar_arrive_if(bar + 8 * (B_BE + 0), l0);
    h_epilogue(accA, hdst);
    __syncwarp();
    mbar_arrive_if(bar + 8 * B_SH, l0);
    pin<8>(a.q);
    STAMP(6);
    mbar_wait(bar + 8 * B_GF, 0);
    STAMP(12);

    float acc2[144];
    const uint32_t a2desc = (((sb + wg * 8192) & 0x3FFFF) >> 4) | LO_A;
    const uint32_t b2desc = (((sb + 16384) & 0x3FFFF) >> 4) | LO_B;
    uint32_t st = 0, gph = 0;
#define G2_MMA(AD, BD, NOFF)                                                                                   \
  wg_ss_n128<HI_SW128, HI_SW128>(acc2, AD, BD);                                                                \
  wg_ss_n160<HI_SW128, HI_SW128>(acc2 + 64, AD, (BD) + (NOFF));
#define G2_ISSUE(K) G2_MMA(a2desc + st * 3584 + (K) * 2, b2desc + st * 3584 + (K) * 128, 1024)
#define ATT_STEP2(N, FIRST, IT)                                                                                \
  {                                                                                                            \
    const uint32_t sub = (N) & 3;                                                                              \
    wg_fence();                                                                                                \
    issue_att(a, kdesc0 + kslot * 384);                                                                        \
    wg_commit();                                                                                               \
    if ((FIRST) && (IT) == 2) {                                                                                \
      wg_ss_z_n128<HI_SW128, HI_SW128>(acc2, a2desc, b2desc);                                                  \
      wg_ss_z_n160<HI_SW128, HI_SW128>(acc2 + 64, a2desc, b2desc + 1024);                                      \
    } else { G2_ISSUE(sub) }                                                                                   \
    wg_commit();                                                                                               \
    wg_wait<1>();                                                                                              \
    pin<32>(a.s);                                                                                              \
    mbar_arrive_if(bar + 8 * B_KE + kslot * 8, l0);                                                            \
    if (!((FIRST) && (IT) == 2)) mbar_arrive_if(bar + 8 * B_GE + (st == 0 ? 16 : st * 8 - 8), l0 & (sub == 0)); \
    if (++kslot == 3) { kslot = 0; kph ^= 1; }                                                                 \
    if (sub == 3) { if (++st == 3) { st = 0; gph ^= 1; } }                                                     \
    const uint32_t ok = mbar_test(bar + 8 * B_GF + st * 8, gph) & mbar_test(bar + 8 * B_KF + kslot * 8, kph);  \
    if (FIRST) {                                                                                               \
      pin<12>(a.o);                                                                                            \
      badmask |= (uint32_t)o_epilogue(a.o, ((IT) - 1) ^ hx, j, row0, lane) << (((IT) - 1) ^ hx);               \
      if ((IT) == 3) { __syncwarp(); mbar_arrive_if(bar + 8 * B_SO1, l0 & (badmask == 0)); early_o = badmask == 0; } \
      first_tile(a, (IT) ^ hx, lane);                                                                          \
    }                                                                                                          \
    if ((IT) == -1) load_q(a, cta, 3 ^ hx, tid);                                                               \
    softmax_tile(a);                                                                                           \
    if ((IT) == -1) pin<8>(a.q);                                                                               \
    mbar_wait2_unless(ok, bar + 8 * B_GF + st * 8, gph, bar + 8 * B_KF + kslot * 8, kph);          \
  }
    bool early_o = false;
    ATT_STEP2(0, true, 2);
#pragma unroll 1
    for (int n = 1; n < 31; n++) ATT_STEP2(n, false, 1);
    ATT_STEP2(31, false, -1);
    ATT_STEP2(32, true, 3);
#pragma unroll 1
    for (int n = 33; n < 64; n++) ATT_STEP2(n, false, 1);
    STAMP(7);
    wg_fence();
    issue_pv(a, kdesc0 + kslot * 384);
    wg_commit();
#pragma unroll
    for (int k = 0; k < 4; k++) { G2_MMA(a2desc + 3584 + k * 2, b2desc + 3584 + k * 128, 1024) }
    wg_commit();
    wg_wait<1>();
    pin<12>(a.o);
    mbar_arrive_if(bar + 8 * (B_GE + 0), l0);
    badmask |= (uint32_t)o_epilogue(a.o, 3 ^ hx, j, row0, lane) << (3 ^ hx);
    __syncwarp();
    mbar_arrive_if(bar + 8 * B_SO2, l0 & (badmask == 0));
    mbar_wait(bar + 8 * (B_GF + 2), 1);
    wg_fence();
#pragma unroll
    for (int k = 0; k < 4; k++) { G2_MMA(a2desc + 7168 + k * 2, b2desc + 7168 + k * 128, 1024) }
    wg_commit();
    wg_wait<1>();
    mbar_arrive_if(bar + 8 * (B_GE + 1), l0);
    if (badmask != 0) {
      wg_wait<0>();
#pragma unroll 1
      for (int hp = 0; hp < 4; hp++)
        if ((badmask >> hp) & 1) attn_slow_rows(cta, j, hp, 128 * m + 64 * wg + 16 * w, tid & ~31);
      __syncwarp();
      mbar_arrive_if(bar + 8 * B_SO1, l0 & !early_o);
      mbar_arrive_if(bar + 8 * B_SO2, l0);
    }
    STAMP(8);
    mbar_wait(bar + 8 * (B_GF + 0), 0);
    wg_fence();
#pragma unroll
    for (int k = 0; k < 3; k++) { G2_MMA(a2desc + k * 2, b2desc + k * 128, 1024) }
    wg_commit();
    mbar_wait(bar + 8 * (B_GF + 1), 0);
    wg_fence();
    G2_MMA(a2desc + 3584 + 2, b2desc + 3584 + 256, 1024)
    G2_MMA(a2desc + 3584 + 4, b2desc + 3584 + 384, 1024)
    G2_MMA(a2desc + 3584 + 6, (((sb + SM_W16) & 0x3FFFF) >> 4) | LO_B16, 256)
    wg_commit();
    STAMP(13);
    mbar_wait(bar + 8 * B_OL, 0);
    STAMP(14);
    wg_fence();
    G2_MMA(a2desc + (SM_OL >> 4), b2desc + 384, 1024)
    G2_MMA(a2desc + (SM_OL >> 4) + 2, b2desc + 3584, 1024)
    G2_MMA(a2desc + (SM_OL >> 4) + 4, b2desc + 3584 + 128, 1024)
    wg_commit();
    const uint32_t tag = (*(volatile uint32_t*)FLAG_EPOCH + 1) & 1;
    wg_wait<0>();
    pin<144>(acc2);
    STAMP(9);
    {
      int tid2, bid2;
      asm volatile("mov.u32 %0, %%tid.x;" : "=r"(tid2));
      asm volatile("mov.u32 %0, %%ctaid.x;" : "=r"(bid2));
      const int m2 = bid2 & 15, j2 = bid2 >> 4;
      float own[36];
      switch (j2 >> 1) {
        case 0: final_store<0>(acc2, own, m2, j2 & 1, tid2, tag); break;
        case 1: final_store<1>(acc2, own, m2, j2 & 1, tid2, tag); break;
        case 2: final_store<2>(acc2, own, m2, j2 & 1, tid2, tag); break;
        default: final_store<3>(acc2, own, m2, j2 & 1, tid2, tag); break;
      }
      pin<36>(own);
      STAMP(15);
      final_reduce(own, prm, m2, j2 & 1, j2 >> 1, tid2, 128 * m2 + (tid2 >> 5) * 16 + ((tid2 & 31) >> 2), tid2 & 31, tag);
    }
    STAMP(10);
    __syncwarp();
    if (lane == 0) {
      if (atomicInc(FLAG_DONE, NCTA * 8 - 1) == NCTA * 8 - 1) {
        for (int i = 0; i < 8; i++) *FLAG_KV(i) = 0;
        for (int i = 0; i < NCTA; i++) { *FLAG_H(i) = 0; *FLAG_O(i) = 0; }
        *FLAG_EPOCH = tag;
      }
    }
  }
}

typedef CUresult (*EncodeFn)(CUtensorMap*, CUtensorMapDataType, cuuint32_t, void*, const cuuint64_t*, const cuuint64_t*, const cuuint32_t*, const cuuint32_t*,
                             CUtensorMapInterleave, CUtensorMapSwizzle, CUtensorMapL2promotion, CUtensorMapFloatOOBfill);

void enc2d(EncodeFn enc, CUtensorMap* tm, const void* base, uint64_t w, uint64_t h, uint64_t pitch_elems, uint32_t bw, uint32_t bh, CUtensorMapSwizzle sw) {
  cuuint64_t dims[2] = {w, h}, str[1] = {pitch_elems * 2};
  cuuint32_t box[2] = {bw, bh}, es[2] = {1, 1};
  enc(tm, CU_TENSOR_MAP_DATA_TYPE_BFLOAT16, 2, const_cast<void*>(base), dims, str, box, es, CU_TENSOR_MAP_INTERLEAVE_NONE, sw,
      CU_TENSOR_MAP_L2_PROMOTION_L2_128B, CU_TENSOR_MAP_FLOAT_OOB_FILL_NONE);
}

}

extern "C" void kernel_launch(void* const* d_in, const int* in_sizes, int n_in, void* d_out, int out_size) {
  (void)in_sizes; (void)n_in; (void)out_size;
  const __nv_bfloat16* x = (const __nv_bfloat16*)d_in[0];
  const __nv_bfloat16* wqkv = (const __nv_bfloat16*)d_in[1];
  const __nv_bfloat16* wo = (const __nv_bfloat16*)d_in[2];
  const __nv_bfloat16* wg = (const __nv_bfloat16*)d_in[4];
  const __nv_bfloat16* wu = (const __nv_bfloat16*)d_in[5];
  const __nv_bfloat16* wd = (const __nv_bfloat16*)d_in[6];
  void* fn = nullptr;
  cudaDriverEntryPointQueryResult qr;
  cudaGetDriverEntryPoint("cuTensorMapEncodeTiled", &fn, cudaEnableDefault, &qr);
  EncodeFn enc = (EncodeFn)fn;
  void *hp = nullptr, *op = nullptr, *kvp = nullptr;
  cudaGetSymbolAddress(&kvp, g_KV);
  cudaGetSymbolAddress(&hp, g_H);
  cudaGetSymbolAddress(&op, g_O);
  Params p;
  enc2d(enc, &p.xm, x, DM, SEQ, DM, 64, 16, CU_TENSOR_MAP_SWIZZLE_128B);
  enc2d(enc, &p.kv, kvp, 320, 32 * 256, 320, 192, 8, CU_TENSOR_MAP_SWIZZLE_NONE);
  enc2d(enc, &p.wqkv64, wqkv, 3 * DM, DM, 3 * DM, 64, 64, CU_TENSOR_MAP_SWIZZLE_128B);
  enc2d(enc, &p.wqkv8, wqkv, 3 * DM, DM, 3 * DM, 8, 64, CU_TENSOR_MAP_SWIZZLE_NONE);
  enc2d(enc, &p.wg, wg, FF, DM, FF, 64, 64, CU_TENSOR_MAP_SWIZZLE_128B);
  enc2d(enc, &p.wu, wu, FF, DM, FF, 64, 64, CU_TENSOR_MAP_SWIZZLE_128B);
  enc2d(enc, &p.h, hp, FF, SEQ, FF, 64, 128, CU_TENSOR_MAP_SWIZZLE_128B);
  enc2d(enc, &p.o, op, DM, SEQ, DM, 64, 128, CU_TENSOR_MAP_SWIZZLE_128B);
  for (int hh = 0; hh < 2; hh++) {
    enc2d(enc, &p.wo[hh], wo + 288 * hh, 288, DM, DM, 64, 64, CU_TENSOR_MAP_SWIZZLE_128B);
    enc2d(enc, &p.wo16[hh], wo + 288 * hh, 288, DM, DM, 64, 16, CU_TENSOR_MAP_SWIZZLE_128B);
    cuuint64_t dims[5] = {288, 2, 4, 4, FF / 32}, str[4] = {DM * 2, 8 * DM * 2, 2 * DM * 2, 32 * DM * 2};
    cuuint32_t box[5] = {64, 2, 4, 4, 2}, es[5] = {1, 1, 1, 1, 1};
    enc(&p.wd[hh], CU_TENSOR_MAP_DATA_TYPE_BFLOAT16, 5, (void*)(wd + 288 * hh), dims, str, box, es, CU_TENSOR_MAP_INTERLEAVE_NONE,
        CU_TENSOR_MAP_SWIZZLE_128B, CU_TENSOR_MAP_L2_PROMOTION_L2_128B, CU_TENSOR_MAP_FLOAT_OOB_FILL_NONE);
  }
  p.x = x;
  p.out = (__nv_bfloat16*)d_out;
  cudaFuncSetAttribute(fused_kernel, cudaFuncAttributeMaxDynamicSharedMemorySize, SM_TOTAL);
  fused_kernel<<<NCTA, 384, SM_TOTAL, cudaStreamPerThread>>>(p);
}
```

```cpp
#include <cuda_runtime.h>
#include <cuda.h>
#include <cuda_bf16.h>
#include <stdint.h>

namespace {

constexpr int SEQ = 2048, DM = 576, FF = 4608;
constexpr int NCTA = 128;

constexpr uint32_t SM_XN = 0;
constexpr uint32_t SM_RING = 147456;
constexpr uint32_t SM_KV = 208896;
constexpr uint32_t QST = 27648, BST = 12288, KVST = 6144, G2ST = 57344;
constexpr uint32_t SM_OL = 172032;
constexpr uint32_t SM_W16 = SM_OL + 16384;
constexpr uint32_t SM_BAR = 232064;
constexpr uint32_t SM_TOTAL = 232448;
enum { B_QF = 0, B_QE = 3, B_BF = 6, B_BE = 11, B_GF = 16, B_GE = 19, B_KF = 22, B_KE = 25, B_SKV = 28, B_SH = 29, B_SO1 = 30, B_SO2 = 31,
       B_OL = 32, B_X = 33, B_N = 42 };
constexpr int NG0 = 7;

constexpr uint32_t HI_SW128 = 0x40000040u;
constexpr uint32_t LO_A = 1u << 16;
constexpr uint32_t LO_B = 512u << 16;
constexpr uint32_t HI_R = 64u, LO_R = 8u << 16;
constexpr uint32_t HI_K = 24u, LO_K = 8u << 16;
constexpr uint32_t HI_V = 8u, LO_V = 24u << 16;
constexpr uint32_t LO_B48 = 384u << 16;
constexpr uint32_t LO_B16 = 128u << 16;

constexpr float QSCALE = 0.23570226039551584f * 1.4426950408889634f;
constexpr float MOFF = 90.f;

struct __align__(64) Params {
  CUtensorMap xm, wqkv64, wqkv8, wg, wu, h, wd[2], o, wo[2], wo16[2], kv;
  const __nv_bfloat16* x;
  __nv_bfloat16* out;
};

__device__ __align__(1024) __nv_bfloat16 g_H[SEQ * FF];
__device__ __align__(1024) __nv_bfloat16 g_O[SEQ * DM];
__device__ __align__(1024) uint32_t g_KV[32 * SEQ * 20];
__device__ __align__(1024) uint32_t g_Q[NCTA * 4 * 256 * 8];
__device__ __align__(1024) uint4 g_P[32 * 16 * 5 * 256];
__device__ uint32_t g_flags[8 * 32 + NCTA * 32 * 3 + 32];
#define FLAG_KV(j) (&g_flags[(j) * 32])
#define FLAG_H(c) (&g_flags[8 * 32 + (c) * 32])
#define FLAG_O(c) (&g_flags[8 * 32 + NCTA * 32 + (c) * 32])
#define FLAG_P(c) (&g_flags[8 * 32 + NCTA * 64 + (c) * 32])
#define FLAG_DONE (&g_flags[8 * 32 + NCTA * 96])
#define FLAG_EPOCH (&g_flags[8 * 32 + NCTA * 96 + 16])
#define STAMP(i)
#define STAMPW(i)

template<uint32_t AHI, uint32_t BHI> __device__ __forceinline__ void wg_ss_p_n192(float* d, uint32_t a, uint32_t b, uint32_t acc) {
  asm volatile("{\n.reg .pred p;\n.reg .b64 da, db;\nsetp.ne.b32 p, %100, 0;\nmov.b64 da, {%96, %98};\nmov.b64 db, {%97, %99};\n"
    "wgmma.mma_async.sync.aligned.m64n192k16.f32.bf16.bf16 {%0, %1, %2, %3, %4, %5, %6, %7, %8, %9, %10, %11, %12, %13, %14, %15, %16, %17, %18, %19, %20, %21, %22, %23, %24, %25, %26, %27, %28, %29, %30, %31, %32, %33, %34, %35, %36, %37, %38, %39, %40, %41, %42, %43, %44, %45, %46, %47, %48, %49, %50, %51, %52, %53, %54, %55, %56, %57, %58, %59, %60, %61, %62, %63, %64, %65, %66, %67, %68, %69, %70, %71, %72, %73, %74, %75, %76, %77, %78, %79, %80, %81, %82, %83, %84, %85, %86, %87, %88, %89, %90, %91, %92, %93, %94, %95}, da, db, p, 1, 1, 0, 1;\n}\n"
    : "+f"(d[0]), "+f"(d[1]), "+f"(d[2]), "+f"(d[3]), "+f"(d[4]), "+f"(d[5]), "+f"(d[6]), "+f"(d[7]), "+f"(d[8]), "+f"(d[9]), "+f"(d[10]), "+f"(d[11]), "+f"(d[12]), "+f"(d[13]), "+f"(d[14]), "+f"(d[15]), "+f"(d[16]), "+f"(d[17]), "+f"(d[18]), "+f"(d[19]), "+f"(d[20]), "+f"(d[21]), "+f"(d[22]), "+f"(d[23]), "+f"(d[24]), "+f"(d[25]), "+f"(d[26]), "+f"(d[27]), "+f"(d[28]), "+f"(d[29]), "+f"(d[30]), "+f"(d[31]), "+f"(d[32]), "+f"(d[33]), "+f"(d[34]), "+f"(d[35]), "+f"(d[36]), "+f"(d[37]), "+f"(d[38]), "+f"(d[39]), "+f"(d[40]), "+f"(d[41]), "+f"(d[42]), "+f"(d[43]), "+f"(d[44]), "+f"(d[45]), "+f"(d[46]), "+f"(d[47]), "+f"(d[48]), "+f"(d[49]), "+f"(d[50]), "+f"(d[51]), "+f"(d[52]), "+f"(d[53]), "+f"(d[54]), "+f"(d[55]), "+f"(d[56]), "+f"(d[57]), "+f"(d[58]), "+f"(d[59]), "+f"(d[60]), "+f"(d[61]), "+f"(d[62]), "+f"(d[63]), "+f"(d[64]), "+f"(d[65]), "+f"(d[66]), "+f"(d[67]), "+f"(d[68]), "+f"(d[69]), "+f"(d[70]), "+f"(d[71]), "+f"(d[72]), "+f"(d[73]), "+f"(d[74]), "+f"(d[75]), "+f"(d[76]), "+f"(d[77]), "+f"(d[78]), "+f"(d[79]), "+f"(d[80]), "+f"(d[81]), "+f"(d[82]), "+f"(d[83]), "+f"(d[84]), "+f"(d[85]), "+f"(d[86]), "+f"(d[87]), "+f"(d[88]), "+f"(d[89]), "+f"(d[90]), "+f"(d[91]), "+f"(d[92]), "+f"(d[93]), "+f"(d[94]), "+f"(d[95])
    : "r"(a), "r"(b), "n"(AHI), "n"(BHI), "r"(acc));
}
template<uint32_t AHI, uint32_t BHI> __device__ __forceinline__ void wg_ss_p_n24(float* d, uint32_t a, uint32_t b, uint32_t acc) {
  asm volatile("{\n.reg .pred p;\n.reg .b64 da, db;\nsetp.ne.b32 p, %16, 0;\nmov.b64 da, {%12, %14};\nmov.b64 db, {%13, %15};\n"
    "wgmma.mma_async.sync.aligned.m64n24k16.f32.bf16.bf16 {%0, %1, %2, %3, %4, %5, %6, %7, %8, %9, %10, %11}, da, db, p, 1, 1, 0, 1;\n}\n"
    : "+f"(d[0]), "+f"(d[1]), "+f"(d[2]), "+f"(d[3]), "+f"(d[4]), "+f"(d[5]), "+f"(d[6]), "+f"(d[7]), "+f"(d[8]), "+f"(d[9]), "+f"(d[10]), "+f"(d[11])
    : "r"(a), "r"(b), "n"(AHI), "n"(BHI), "r"(acc));
}
template<uint32_t AHI, uint32_t BHI> __device__ __forceinline__ void wg_ss_n128(float* d, uint32_t a, uint32_t b) {
  asm volatile("{\n.reg .pred p;\n.reg .b64 da, db;\nsetp.ne.b32 p, 1, 0;\nmov.b64 da, {%64, %66};\nmov.b64 db, {%65, %67};\n"
    "wgmma.mma_async.sync.aligned.m64n128k16.f32.bf16.bf16 {%0, %1, %2, %3, %4, %5, %6, %7, %8, %9, %10, %11, %12, %13, %14, %15, %16, %17, %18, %19, %20, %21, %22, %23, %24, %25, %26, %27, %28, %29, %30, %31, %32, %33, %34, %35, %36, %37, %38, %39, %40, %41, %42, %43, %44, %45, %46, %47, %48, %49, %50, %51, %52, %53, %54, %55, %56, %57, %58, %59, %60, %61, %62, %63}, da, db, p, 1, 1, 0, 1;\n}\n"
    : "+f"(d[0]), "+f"(d[1]), "+f"(d[2]), "+f"(d[3]), "+f"(d[4]), "+f"(d[5]), "+f"(d[6]), "+f"(d[7]), "+f"(d[8]), "+f"(d[9]), "+f"(d[10]), "+f"(d[11]), "+f"(d[12]), "+f"(d[13]), "+f"(d[14]), "+f"(d[15]), "+f"(d[16]), "+f"(d[17]), "+f"(d[18]), "+f"(d[19]), "+f"(d[20]), "+f"(d[21]), "+f"(d[22]), "+f"(d[23]), "+f"(d[24]), "+f"(d[25]), "+f"(d[26]), "+f"(d[27]), "+f"(d[28]), "+f"(d[29]), "+f"(d[30]), "+f"(d[31]), "+f"(d[32]), "+f"(d[33]), "+f"(d[34]), "+f"(d[35]), "+f"(d[36]), "+f"(d[37]), "+f"(d[38]), "+f"(d[39]), "+f"(d[40]), "+f"(d[41]), "+f"(d[42]), "+f"(d[43]), "+f"(d[44]), "+f"(d[45]), "+f"(d[46]), "+f"(d[47]), "+f"(d[48]), "+f"(d[49]), "+f"(d[50]), "+f"(d[51]), "+f"(d[52]), "+f"(d[53]), "+f"(d[54]), "+f"(d[55]), "+f"(d[56]), "+f"(d[57]), "+f"(d[58]), "+f"(d[59]), "+f"(d[60]), "+f"(d[61]), "+f"(d[62]), "+f"(d[63])
    : "r"(a), "r"(b), "n"(AHI), "n"(BHI));
}
template<uint32_t AHI, uint32_t BHI> __device__ __forceinline__ void wg_ss_z_n128(float* d, uint32_t a, uint32_t b) {
  asm volatile("{\n.reg .pred p;\n.reg .b64 da, db;\nsetp.ne.b32 p, 0, 0;\nmov.b64 da, {%64, %66};\nmov.b64 db, {%65, %67};\n"
    "wgmma.mma_async.sync.aligned.m64n128k16.f32.bf16.bf16 {%0, %1, %2, %3, %4, %5, %6, %7, %8, %9, %10, %11, %12, %13, %14, %15, %16, %17, %18, %19, %20, %21, %22, %23, %24, %25, %26, %27, %28, %29, %30, %31, %32, %33, %34, %35, %36, %37, %38, %39, %40, %41, %42, %43, %44, %45, %46, %47, %48, %49, %50, %51, %52, %53, %54, %55, %56, %57, %58, %59, %60, %61, %62, %63}, da, db, p, 1, 1, 0, 1;\n}\n"
    : "=f"(d[0]), "=f"(d[1]), "=f"(d[2]), "=f"(d[3]), "=f"(d[4]), "=f"(d[5]), "=f"(d[6]), "=f"(d[7]), "=f"(d[8]), "=f"(d[9]), "=f"(d[10]), "=f"(d[11]), "=f"(d[12]), "=f"(d[13]), "=f"(d[14]), "=f"(d[15]), "=f"(d[16]), "=f"(d[17]), "=f"(d[18]), "=f"(d[19]), "=f"(d[20]), "=f"(d[21]), "=f"(d[22]), "=f"(d[23]), "=f"(d[24]), "=f"(d[25]), "=f"(d[26]), "=f"(d[27]), "=f"(d[28]), "=f"(d[29]), "=f"(d[30]), "=f"(d[31]), "=f"(d[32]), "=f"(d[33]), "=f"(d[34]), "=f"(d[35]), "=f"(d[36]), "=f"(d[37]), "=f"(d[38]), "=f"(d[39]), "=f"(d[40]), "=f"(d[41]), "=f"(d[42]), "=f"(d[43]), "=f"(d[44]), "=f"(d[45]), "=f"(d[46]), "=f"(d[47]), "=f"(d[48]), "=f"(d[49]), "=f"(d[50]), "=f"(d[51]), "=f"(d[52]), "=f"(d[53]), "=f"(d[54]), "=f"(d[55]), "=f"(d[56]), "=f"(d[57]), "=f"(d[58]), "=f"(d[59]), "=f"(d[60]), "=f"(d[61]), "=f"(d[62]), "=f"(d[63])
    : "r"(a), "r"(b), "n"(AHI), "n"(BHI));
}
template<uint32_t AHI, uint32_t BHI> __device__ __forceinline__ void wg_ss_n160(float* d, uint32_t a, uint32_t b) {
  asm volatile("{\n.reg .pred p;\n.reg .b64 da, db;\nsetp.ne.b32 p, 1, 0;\nmov.b64 da, {%80, %82};\nmov.b64 db, {%81, %83};\n"
    "wgmma.mma_async.sync.aligned.m64n160k16.f32.bf16.bf16 {%0, %1, %2, %3, %4, %5, %6, %7, %8, %9, %10, %11, %12, %13, %14, %15, %16, %17, %18, %19, %20, %21, %22, %23, %24, %25, %26, %27, %28, %29, %30, %31, %32, %33, %34, %35, %36, %37, %38, %39, %40, %41, %42, %43, %44, %45, %46, %47, %48, %49, %50, %51, %52, %53, %54, %55, %56, %57, %58, %59, %60, %61, %62, %63, %64, %65, %66, %67, %68, %69, %70, %71, %72, %73, %74, %75, %76, %77, %78, %79}, da, db, p, 1, 1, 0, 1;\n}\n"
    : "+f"(d[0]), "+f"(d[1]), "+f"(d[2]), "+f"(d[3]), "+f"(d[4]), "+f"(d[5]), "+f"(d[6]), "+f"(d[7]), "+f"(d[8]), "+f"(d[9]), "+f"(d[10]), "+f"(d[11]), "+f"(d[12]), "+f"(d[13]), "+f"(d[14]), "+f"(d[15]), "+f"(d[16]), "+f"(d[17]), "+f"(d[18]), "+f"(d[19]), "+f"(d[20]), "+f"(d[21]), "+f"(d[22]), "+f"(d[23]), "+f"(d[24]), "+f"(d[25]), "+f"(d[26]), "+f"(d[27]), "+f"(d[28]), "+f"(d[29]), "+f"(d[30]), "+f"(d[31]), "+f"(d[32]), "+f"(d[33]), "+f"(d[34]), "+f"(d[35]), "+f"(d[36]), "+f"(d[37]), "+f"(d[38]), "+f"(d[39]), "+f"(d[40]), "+f"(d[41]), "+f"(d[42]), "+f"(d[43]), "+f"(d[44]), "+f"(d[45]), "+f"(d[46]), "+f"(d[47]), "+f"(d[48]), "+f"(d[49]), "+f"(d[50]), "+f"(d[51]), "+f"(d[52]), "+f"(d[53]), "+f"(d[54]), "+f"(d[55]), "+f"(d[56]), "+f"(d[57]), "+f"(d[58]), "+f"(d[59]), "+f"(d[60]), "+f"(d[61]), "+f"(d[62]), "+f"(d[63]), "+f"(d[64]), "+f"(d[65]), "+f"(d[66]), "+f"(d[67]), "+f"(d[68]), "+f"(d[69]), "+f"(d[70]), "+f"(d[71]), "+f"(d[72]), "+f"(d[73]), "+f"(d[74]), "+f"(d[75]), "+f"(d[76]), "+f"(d[77]), "+f"(d[78]), "+f"(d[79])
    : "r"(a), "r"(b), "n"(AHI), "n"(BHI));
}
template<uint32_t AHI, uint32_t BHI> __device__ __forceinline__ void wg_ss_z_n160(float* d, uint32_t a, uint32_t b) {
  asm volatile("{\n.reg .pred p;\n.reg .b64 da, db;\nsetp.ne.b32 p, 0, 0;\nmov.b64 da, {%80, %82};\nmov.b64 db, {%81, %83};\n"
    "wgmma.mma_async.sync.aligned.m64n160k16.f32.bf16.bf16 {%0, %1, %2, %3, %4, %5, %6, %7, %8, %9, %10, %11, %12, %13, %14, %15, %16, %17, %18, %19, %20, %21, %22, %23, %24, %25, %26, %27, %28, %29, %30, %31, %32, %33, %34, %35, %36, %37, %38, %39, %40, %41, %42, %43, %44, %45, %46, %47, %48, %49, %50, %51, %52, %53, %54, %55, %56, %57, %58, %59, %60, %61, %62, %63, %64, %65, %66, %67, %68, %69, %70, %71, %72, %73, %74, %75, %76, %77, %78, %79}, da, db, p, 1, 1, 0, 1;\n}\n"
    : "=f"(d[0]), "=f"(d[1]), "=f"(d[2]), "=f"(d[3]), "=f"(d[4]), "=f"(d[5]), "=f"(d[6]), "=f"(d[7]), "=f"(d[8]), "=f"(d[9]), "=f"(d[10]), "=f"(d[11]), "=f"(d[12]), "=f"(d[13]), "=f"(d[14]), "=f"(d[15]), "=f"(d[16]), "=f"(d[17]), "=f"(d[18]), "=f"(d[19]), "=f"(d[20]), "=f"(d[21]), "=f"(d[22]), "=f"(d[23]), "=f"(d[24]), "=f"(d[25]), "=f"(d[26]), "=f"(d[27]), "=f"(d[28]), "=f"(d[29]), "=f"(d[30]), "=f"(d[31]), "=f"(d[32]), "=f"(d[33]), "=f"(d[34]), "=f"(d[35]), "=f"(d[36]), "=f"(d[37]), "=f"(d[38]), "=f"(d[39]), "=f"(d[40]), "=f"(d[41]), "=f"(d[42]), "=f"(d[43]), "=f"(d[44]), "=f"(d[45]), "=f"(d[46]), "=f"(d[47]), "=f"(d[48]), "=f"(d[49]), "=f"(d[50]), "=f"(d[51]), "=f"(d[52]), "=f"(d[53]), "=f"(d[54]), "=f"(d[55]), "=f"(d[56]), "=f"(d[57]), "=f"(d[58]), "=f"(d[59]), "=f"(d[60]), "=f"(d[61]), "=f"(d[62]), "=f"(d[63]), "=f"(d[64]), "=f"(d[65]), "=f"(d[66]), "=f"(d[67]), "=f"(d[68]), "=f"(d[69]), "=f"(d[70]), "=f"(d[71]), "=f"(d[72]), "=f"(d[73]), "=f"(d[74]), "=f"(d[75]), "=f"(d[76]), "=f"(d[77]), "=f"(d[78]), "=f"(d[79])
    : "r"(a), "r"(b), "n"(AHI), "n"(BHI));
}
template<uint32_t BHI> __device__ __forceinline__ void wg_rs_n64(float* d, uint32_t a0, uint32_t a1, uint32_t a2, uint32_t a3, uint32_t b) {
  asm volatile("{\n.reg .pred p;\n.reg .b64 db;\nsetp.ne.b32 p, 1, 0;\nmov.b64 db, {%36, %37};\n"
    "wgmma.mma_async.sync.aligned.m64n64k16.f32.bf16.bf16 {%0, %1, %2, %3, %4, %5, %6, %7, %8, %9, %10, %11, %12, %13, %14, %15, %16, %17, %18, %19, %20, %21, %22, %23, %24, %25, %26, %27, %28, %29, %30, %31}, {%32, %33, %34, %35}, db, p, 1, 1, 0;\n}\n"
    : "+f"(d[0]), "+f"(d[1]), "+f"(d[2]), "+f"(d[3]), "+f"(d[4]), "+f"(d[5]), "+f"(d[6]), "+f"(d[7]), "+f"(d[8]), "+f"(d[9]), "+f"(d[10]), "+f"(d[11]), "+f"(d[12]), "+f"(d[13]), "+f"(d[14]), "+f"(d[15]), "+f"(d[16]), "+f"(d[17]), "+f"(d[18]), "+f"(d[19]), "+f"(d[20]), "+f"(d[21]), "+f"(d[22]), "+f"(d[23]), "+f"(d[24]), "+f"(d[25]), "+f"(d[26]), "+f"(d[27]), "+f"(d[28]), "+f"(d[29]), "+f"(d[30]), "+f"(d[31])
    : "r"(a0), "r"(a1), "r"(a2), "r"(a3), "r"(b), "n"(BHI));
}
template<uint32_t BHI> __device__ __forceinline__ void wg_rs_z_n64(float* d, uint32_t a0, uint32_t a1, uint32_t a2, uint32_t a3, uint32_t b) {
  asm volatile("{\n.reg .pred p;\n.reg .b64 db;\nsetp.ne.b32 p, 0, 0;\nmov.b64 db, {%36, %37};\n"
    "wgmma.mma_async.sync.aligned.m64n64k16.f32.bf16.bf16 {%0, %1, %2, %3, %4, %5, %6, %7, %8, %9, %10, %11, %12, %13, %14, %15, %16, %17, %18, %19, %20, %21, %22, %23, %24, %25, %26, %27, %28, %29, %30, %31}, {%32, %33, %34, %35}, db, p, 1, 1, 0;\n}\n"
    : "=f"(d[0]), "=f"(d[1]), "=f"(d[2]), "=f"(d[3]), "=f"(d[4]), "=f"(d[5]), "=f"(d[6]), "=f"(d[7]), "=f"(d[8]), "=f"(d[9]), "=f"(d[10]), "=f"(d[11]), "=f"(d[12]), "=f"(d[13]), "=f"(d[14]), "=f"(d[15]), "=f"(d[16]), "=f"(d[17]), "=f"(d[18]), "=f"(d[19]), "=f"(d[20]), "=f"(d[21]), "=f"(d[22]), "=f"(d[23]), "=f"(d[24]), "=f"(d[25]), "=f"(d[26]), "=f"(d[27]), "=f"(d[28]), "=f"(d[29]), "=f"(d[30]), "=f"(d[31])
    : "r"(a0), "r"(a1), "r"(a2), "r"(a3), "r"(b), "n"(BHI));
}
template<uint32_t BHI> __device__ __forceinline__ void wg_rs_n24(float* d, uint32_t a0, uint32_t a1, uint32_t a2, uint32_t a3, uint32_t b) {
  asm volatile("{\n.reg .pred p;\n.reg .b64 db;\nsetp.ne.b32 p, 1, 0;\nmov.b64 db, {%16, %17};\n"
    "wgmma.mma_async.sync.aligned.m64n24k16.f32.bf16.bf16 {%0, %1, %2, %3, %4, %5, %6, %7, %8, %9, %10, %11}, {%12, %13, %14, %15}, db, p, 1, 1, 1;\n}\n"
    : "+f"(d[0]), "+f"(d[1]), "+f"(d[2]), "+f"(d[3]), "+f"(d[4]), "+f"(d[5]), "+f"(d[6]), "+f"(d[7]), "+f"(d[8]), "+f"(d[9]), "+f"(d[10]), "+f"(d[11])
    : "r"(a0), "r"(a1), "r"(a2), "r"(a3), "r"(b), "n"(BHI));
}
template<uint32_t BHI> __device__ __forceinline__ void wg_rs_z_n24(float* d, uint32_t a0, uint32_t a1, uint32_t a2, uint32_t a3, uint32_t b) {
  asm volatile("{\n.reg .pred p;\n.reg .b64 db;\nsetp.ne.b32 p, 0, 0;\nmov.b64 db, {%16, %17};\n"
    "wgmma.mma_async.sync.aligned.m64n24k16.f32.bf16.bf16 {%0, %1, %2, %3, %4, %5, %6, %7, %8, %9, %10, %11}, {%12, %13, %14, %15}, db, p, 1, 1, 1;\n}\n"
    : "=f"(d[0]), "=f"(d[1]), "=f"(d[2]), "=f"(d[3]), "=f"(d[4]), "=f"(d[5]), "=f"(d[6]), "=f"(d[7]), "=f"(d[8]), "=f"(d[9]), "=f"(d[10]), "=f"(d[11])
    : "r"(a0), "r"(a1), "r"(a2), "r"(a3), "r"(b), "n"(BHI));
}

__device__ __forceinline__ void wg_fence() { asm volatile("wgmma.fence.sync.aligned;" ::: "memory"); }
__device__ __forceinline__ void wg_commit() { asm volatile("wgmma.commit_group.sync.aligned;" ::: "memory"); }
template <int N> __device__ __forceinline__ void wg_wait() { asm volatile("wgmma.wait_group.sync.aligned %0;" ::"n"(N) : "memory"); }
template <int R> __device__ __forceinline__ void pin(float* d) {
#pragma unroll
  for (int i = 0; i < R; i++) asm volatile("" : "+f"(d[i])::"memory");
}
template <int R> __device__ __forceinline__ void pin(uint32_t* d) {
#pragma unroll
  for (int i = 0; i < R; i++) asm volatile("" : "+r"(d[i])::"memory");
}
__device__ __forceinline__ float ex2(float x) { float y; asm("ex2.approx.ftz.f32 %0, %1;" : "=f"(y) : "f"(x)); return y; }
__device__ __forceinline__ float tanh_fast(float x) { float y; asm("tanh.approx.f32 %0, %1;" : "=f"(y) : "f"(x)); return y; }
__device__ __forceinline__ uint32_t pack(float lo, float hi) { uint32_t r; asm("cvt.rn.bf16x2.f32 %0, %1, %2;" : "=r"(r) : "f"(hi), "f"(lo)); return r; }
__device__ __forceinline__ float bf_lo(uint32_t v) { return __uint_as_float(v << 16); }
__device__ __forceinline__ float bf_hi(uint32_t v) { return __uint_as_float(v & 0xffff0000u); }
__device__ __forceinline__ float bf_round(float x) { return bf_lo(pack(x, 0.f)); }

__device__ __forceinline__ void mbar_init(uint32_t bar, uint32_t cnt) { asm volatile("mbarrier.init.shared::cta.b64 [%0], %1;" ::"r"(bar), "r"(cnt) : "memory"); }
__device__ __forceinline__ void mbar_expect(uint32_t bar, uint32_t bytes) { asm volatile("mbarrier.arrive.expect_tx.shared::cta.b64 _, [%0], %1;" ::"r"(bar), "r"(bytes) : "memory"); }
__device__ __forceinline__ void mbar_arrive(uint32_t bar) { asm volatile("mbarrier.arrive.shared::cta.b64 _, [%0];" ::"r"(bar) : "memory"); }
__device__ __forceinline__ void mbar_wait(uint32_t bar, uint32_t parity) {
  asm volatile(
      "{\n.reg .pred p;\n.reg .u32 c;\n"
      "mbarrier.try_wait.parity.shared::cta.b64 p, [%0], %1;\n"
      "@p bra.uni DONE;\n"
      "mov.u32 c, 0;\n"
      "LOOP:\n"
      "mbarrier.try_wait.parity.shared::cta.b64 p, [%0], %1;\n"
      "@p bra.uni DONE;\n"
      "add.u32 c, c, 1;\n"
      "setp.lt.u32 p, c, 0x4000000;\n"
      "@p bra.uni LOOP;\n"
      "trap;\n"
      "DONE:\n}\n" ::"r"(bar), "r"(parity) : "memory");
}
__device__ __forceinline__ uint32_t mbar_test(uint32_t bar, uint32_t parity) {
  uint32_t ok;
  asm volatile("{\n.reg .pred p;\nmbarrier.test_wait.parity.shared::cta.b64 p, [%1], %2;\nselp.u32 %0, 1, 0, p;\n}\n" : "=r"(ok) : "r"(bar), "r"(parity) : "memory");
  return ok;
}
__device__ __forceinline__ void mbar_wait2_unless(uint32_t ok, uint32_t bar0, uint32_t par0, uint32_t bar1, uint32_t par1) {
  asm volatile(
      "{\n.reg .pred p, q;\n.reg .u32 c;\n"
      "setp.ne.u32 p, %0, 0;\n"
      "vote.sync.all.pred p, p, 0xffffffff;\n"
      "@p bra.uni DONE;\n"
      "mov.u32 c, 0;\n"
      "LOOP:\n"
      "mbarrier.try_wait.parity.shared::cta.b64 p, [%1], %2;\n"
      "mbarrier.try_wait.parity.shared::cta.b64 q, [%3], %4;\n"
      "and.pred p, p, q;\n"
      "vote.sync.all.pred p, p, 0xffffffff;\n"
      "@p bra.uni DONE;\n"
      "add.u32 c, c, 1;\n"
      "setp.lt.u32 p, c, 0x4000000;\n"
      "@p bra.uni LOOP;\n"
      "trap;\n"
      "DONE:\n}\n" ::"r"(ok), "r"(bar0), "r"(par0), "r"(bar1), "r"(par1) : "memory");
}
__device__ __forceinline__ void mbar_arrive_if(uint32_t bar, uint32_t cond) {
  asm volatile("{\n.reg .pred p;\nsetp.ne.u32 p, %1, 0;\n@p mbarrier.arrive.shared::cta.b64 _, [%0];\n}\n" ::"r"(bar), "r"(cond) : "memory");
}
__device__ __forceinline__ uint32_t bsub2(uint32_t a, uint32_t b) { uint32_t d; asm("sub.rn.bf16x2 %0, %1, %2;" : "=r"(d) : "r"(a), "r"(b)); return d; }
__device__ __forceinline__ uint32_t bscale2(uint32_t d, uint32_t hi, uint32_t lo) {
  uint32_t t, r;
  asm("mul.rn.bf16x2 %0, %1, %2;" : "=r"(t) : "r"(d), "r"(lo));
  asm("fma.rn.bf16x2 %0, %1, %2, %3;" : "=r"(r) : "r"(d), "r"(hi), "r"(t));
  return r;
}
__device__ __forceinline__ void flag_wait(const uint32_t* f, uint32_t target) {
  asm volatile(
      "{\n.reg .pred p;\n.reg .u32 c, v;\n"
      "mov.u32 c, 0;\n"
      "LOOP:\n"
      "ld.acquire.gpu.global.u32 v, [%0];\n"
      "setp.ge.u32 p, v, %1;\n"
      "@p bra DONE;\n"
      "add.u32 c, c, 1;\n"
      "setp.lt.u32 p, c, 0x1000000;\n"
      "@p bra LOOP;\n"
      "trap;\n"
      "DONE:\n}\n" ::"l"(f), "r"(target) : "memory");
}
__device__ __forceinline__ uint32_t flag_wait_v(const uint32_t* f, uint32_t target) {
  uint32_t v;
  asm volatile(
      "{\n.reg .pred p;\n.reg .u32 c;\n"
      "mov.u32 c, 0;\n"
      "LOOP:\n"
      "ld.acquire.gpu.global.u32 %0, [%1];\n"
      "setp.ge.u32 p, %0, %2;\n"
      "@p bra DONE;\n"
      "add.u32 c, c, 1;\n"
      "setp.lt.u32 p, c, 0x1000000;\n"
      "@p bra LOOP;\n"
      "trap;\n"
      "DONE:\n}\n" : "=&r"(v) : "l"(f), "r"(target) : "memory");
  return v;
}
__device__ __forceinline__ float rcp_fast(float x) { float y; asm("rcp.approx.ftz.f32 %0, %1;" : "=f"(y) : "f"(x)); return y; }
__device__ __forceinline__ void ldsm4(uint32_t* v, uint32_t addr) {
  asm volatile("ldmatrix.sync.aligned.m8n8.x4.shared.b16 {%0,%1,%2,%3}, [%4];" : "=r"(v[0]), "=r"(v[1]), "=r"(v[2]), "=r"(v[3]) : "r"(addr) : "memory");
}
__device__ __forceinline__ void stsm4(uint32_t addr, uint32_t a, uint32_t b, uint32_t c, uint32_t d) {
  asm volatile("stmatrix.sync.aligned.m8n8.x4.shared.b16 [%0], {%1,%2,%3,%4};" ::"r"(addr), "r"(a), "r"(b), "r"(c), "r"(d) : "memory");
}
__device__ __forceinline__ void flag_add(uint32_t* f) { asm volatile("red.relaxed.gpu.global.add.u32 [%0], 1;" ::"l"(f) : "memory"); }
__device__ __forceinline__ void fence_gpu() { asm volatile("fence.acq_rel.gpu;" ::: "memory"); }
__device__ __forceinline__ void fence_async() { asm volatile("fence.proxy.async;" ::: "memory"); }
__device__ __forceinline__ void tma2d(uint32_t dst, const CUtensorMap* tm, uint32_t bar, int c0, int c1) {
  asm volatile("cp.async.bulk.tensor.2d.shared::cluster.global.mbarrier::complete_tx::bytes [%0], [%1, {%3, %4}], [%2];" ::"r"(dst), "l"(tm), "r"(bar), "r"(c0), "r"(c1) : "memory");
}
__device__ __forceinline__ void tma5d(uint32_t dst, const CUtensorMap* tm, uint32_t bar, int c0, int c4) {
  asm volatile("cp.async.bulk.tensor.5d.shared::cluster.global.mbarrier::complete_tx::bytes [%0], [%1, {%3, %5, %5, %5, %4}], [%2];" ::"r"(dst), "l"(tm), "r"(bar), "r"(c0), "r"(c4), "r"(0) : "memory");
}
__device__ __forceinline__ void pf2d(const CUtensorMap* tm, int c0, int c1) {
  asm volatile("cp.async.bulk.prefetch.tensor.2d.L2.global [%0, {%1, %2}];" ::"l"(tm), "r"(c0), "r"(c1) : "memory");
}
__device__ __forceinline__ void pf5d(const CUtensorMap* tm, int c0, int c4) {
  asm volatile("cp.async.bulk.prefetch.tensor.5d.L2.global [%0, {%1, %3, %3, %3, %2}];" ::"l"(tm), "r"(c0), "r"(c4), "r"(0) : "memory");
}

struct Att {
  float s[32];
  float o[12];
  uint32_t p[16];
  uint32_t q[8];
};

__device__ __forceinline__ void attn_slow_rows(int cta, int j, int hp, int row_base, int tid_base) {
  const int lane = threadIdx.x & 31;
  const uint32_t* kv = g_KV + (size_t)(4 * j + hp) * SEQ * 20;
#pragma unroll 1
  for (int r = 0; r < 16; r++) {
    float q[18], acc[18];
#pragma unroll
    for (int v = 0; v < 9; v++) {
      uint32_t u = g_Q[((cta * 4 + hp) * 256 + tid_base + (r & 7) * 4 + ((v + hp) & 3)) * 8 + 2 * (v >> 2) + (r >> 3)];
      q[2 * v] = bf_lo(u); q[2 * v + 1] = bf_hi(u);
      acc[2 * v] = 0.f; acc[2 * v + 1] = 0.f;
    }
    float mx = -INFINITY, l = 0.f;
#pragma unroll 1
    for (int key = lane; key < SEQ; key += 32) {
      const uint32_t* kr = kv + (key >> 3) * 160 + (key & 7) * 4;
      float s = 0.f;
#pragma unroll
      for (int v = 0; v < 9; v++) {
        uint32_t u = kr[(v >> 2) * 32 + ((v + hp) & 3)];
        s = fmaf(q[2 * v], bf_lo(u), s); s = fmaf(q[2 * v + 1], bf_hi(u), s);
      }
      float mn = fmaxf(mx, s), c = exp2f(mx - mn), p = exp2f(s - mn);
      mx = mn; l = l * c + p;
#pragma unroll
      for (int v = 0; v < 9; v++) {
        uint32_t u = v < 8 ? kr[(3 + (v >> 2)) * 32 + ((v + hp) & 3)] : kr[2 * 32 + ((hp + 2) & 3)];
        acc[2 * v] = fmaf(p, bf_lo(u), acc[2 * v] * c); acc[2 * v + 1] = fmaf(p, bf_hi(u), acc[2 * v + 1] * c);
      }
    }
    float gm = mx;
#pragma unroll
    for (int d = 16; d; d >>= 1) gm = fmaxf(gm, __shfl_xor_sync(0xffffffffu, gm, d));
    float c = exp2f(mx - gm);
    l *= c;
#pragma unroll
    for (int d = 16; d; d >>= 1) l += __shfl_xor_sync(0xffffffffu, l, d);
    uint32_t* orow = reinterpret_cast<uint32_t*>(g_O + (size_t)(row_base + r) * DM + 18 * (4 * j + hp));
#pragma unroll
    for (int v = 0; v < 9; v++) {
      float a = acc[2 * v] * c, b = acc[2 * v + 1] * c;
#pragma unroll
      for (int d = 16; d; d >>= 1) { a += __shfl_xor_sync(0xffffffffu, a, d); b += __shfl_xor_sync(0xffffffffu, b, d); }
      if (lane == 0) orow[v] = pack(2.f * (a / l), 2.f * (b / l));
    }
  }
}

__device__ __forceinline__ bool o_epilogue(float* o, int hp, int j, int row0, int lane) {
  const int t = lane & 3, src = (lane & ~3) | ((hp + 1) & 3);
  float l0 = __shfl_sync(0xffffffffu, o[0], src), l1 = __shfl_sync(0xffffffffu, o[2], src);
  float sa = 0.f;
#pragma unroll
  for (int i = 0; i < 12; i++) sa += fabsf(o[i]);
  bool ok = (l0 <= 1.329228e36f) && (l1 <= 1.329228e36f) && (l0 > 0.f) && (l1 > 0.f) && (sa <= 3.0e38f);
  float i0 = 2.f * rcp_fast(l0), i1 = 2.f * rcp_fast(l1);
  uint32_t* r0 = reinterpret_cast<uint32_t*>(g_O + (size_t)row0 * DM + 18 * (4 * j + hp));
  uint32_t* r1 = r0 + 8 * (DM / 2);
  const int v = (t - hp) & 3;
  r0[v] = pack(o[4] * i0, o[5] * i0);
  r1[v] = pack(o[6] * i1, o[7] * i1);
  r0[v + 4] = pack(o[8] * i0, o[9] * i0);
  r1[v + 4] = pack(o[10] * i1, o[11] * i1);
  if (t == ((hp + 2) & 3)) { r0[8] = pack(o[0] * i0, o[1] * i0); r1[8] = pack(o[2] * i1, o[3] * i1); }
  return __any_sync(0xffffffffu, !ok);
}

__device__ __forceinline__ void issue_pv(Att& a, uint32_t kdesc) {
  const uint32_t vdesc = kdesc + 192 + (LO_V - LO_K);
#pragma unroll
  for (int k = 0; k < 4; k++) wg_rs_n24<HI_V>(a.o, a.p[4 * k], a.p[4 * k + 1], a.p[4 * k + 2], a.p[4 * k + 3], vdesc + k * 48);
}
__device__ __forceinline__ void issue_att(Att& a, uint32_t kdesc) {
  issue_pv(a, kdesc);
  wg_rs_z_n64<HI_K>(a.s, a.q[0], a.q[1], a.q[2], a.q[3], kdesc);
  wg_rs_n64<HI_K>(a.s, a.q[4], a.q[5], a.q[6], a.q[7], kdesc + 16);
}
__device__ __forceinline__ void softmax_tile(Att& a) {
#pragma unroll
  for (int i = 0; i < 16; i++) a.p[i] = pack(ex2(a.s[2 * i]), ex2(a.s[2 * i + 1]));
  pin<16>(a.p);
}
__device__ __forceinline__ void first_tile(Att& a, int hp, int lane) {
  float m0 = fmaxf(a.s[0], a.s[1]), m1 = fmaxf(a.s[2], a.s[3]);
#pragma unroll
  for (int i = 4; i < 32; i += 4) { m0 = fmaxf(m0, fmaxf(a.s[i], a.s[i + 1])); m1 = fmaxf(m1, fmaxf(a.s[i + 2], a.s[i + 3])); }
  m0 = fmaxf(m0, __shfl_xor_sync(0xffffffffu, m0, 1)); m1 = fmaxf(m1, __shfl_xor_sync(0xffffffffu, m1, 1));
  m0 = fmaxf(m0, __shfl_xor_sync(0xffffffffu, m0, 2)); m1 = fmaxf(m1, __shfl_xor_sync(0xffffffffu, m1, 2));
  float n0 = -(m0 + MOFF), n1 = -(m1 + MOFF);
  float h0 = bf_round(n0), h1 = bf_round(n1);
  uint32_t e0 = pack(h0, n0 - h0), e1 = pack(h1, n1 - h1);
  n0 = h0 + bf_hi(e0); n1 = h1 + bf_hi(e1);
  if ((lane & 3) == ((hp + 1) & 3)) { a.q[4] = e0; a.q[5] = e1; }
#pragma unroll
  for (int i = 0; i < 32; i += 4) { a.s[i] += n0; a.s[i + 1] += n0; a.s[i + 2] += n1; a.s[i + 3] += n1; }
#pragma unroll
  for (int i = 0; i < 12; i++) a.o[i] = 0.f;
  pin<12>(a.o); pin<8>(a.q);
}
__device__ __forceinline__ void load_q(Att& a, int cta, int hp, int tid) {
  const uint32_t* src = g_Q + ((cta * 4 + hp) * 256 + tid) * 8;
  const uint4 u = __ldcg(reinterpret_cast<const uint4*>(src));
  const uint4 v = __ldcg(reinterpret_cast<const uint4*>(src + 4));
  a.q[0] = u.x; a.q[1] = u.y; a.q[2] = u.z; a.q[3] = u.w; a.q[4] = v.x; a.q[5] = v.y; a.q[6] = v.z; a.q[7] = v.w;
}
__device__ __forceinline__ void h_epilogue(float* acc, __nv_bfloat16* dst) {
#pragma unroll
  for (int b = 0; b < 2; b++) {
    uint32_t w0[4], w1[4];
#pragma unroll
    for (int i = 0; i < 4; i++) {
      float h[4];
#pragma unroll
      for (int e = 0; e < 4; e++) {
        float g = acc[(4 * b + i) * 4 + e], u = acc[32 + (4 * b + i) * 4 + e];
        h[e] = fmaf(tanh_fast(0.5f * g), u, u);
      }
      w0[i] = pack(h[0], h[1]); w1[i] = pack(h[2], h[3]);
    }
    *reinterpret_cast<uint4*>(dst + 32 * b) = make_uint4(w0[0], w0[1], w0[2], w0[3]);
    *reinterpret_cast<uint4*>(dst + 32 * b + 8 * FF) = make_uint4(w1[0], w1[1], w1[2], w1[3]);
  }
}

template <int Q> __device__ __forceinline__ void final_store(const float* acc, float* own, int m, int hh, int tid, uint32_t tag) {
  uint4* pw = g_P + (size_t)((m * 2 + hh) * 16 + Q * 4) * 5 * 256 + tid;
#pragma unroll
  for (int dd = 1; dd < 4; dd++) {
    const int d = (Q + dd) & 3;
    uint32_t u[20];
#pragma unroll
    for (int i = 0; i < 18; i++) u[i] = (pack(acc[36 * d + 2 * i], acc[36 * d + 2 * i + 1]) & ~1u) | tag;
    u[18] = u[19] = tag;
#pragma unroll
    for (int i = 0; i < 5; i++)
      asm volatile("st.relaxed.gpu.global.v4.b32 [%0], {%1,%2,%3,%4};" ::"l"(pw + (d * 5 + i) * 256), "r"(u[4 * i]), "r"(u[4 * i + 1]), "r"(u[4 * i + 2]), "r"(u[4 * i + 3]) : "memory");
  }
#pragma unroll
  for (int i = 0; i < 36; i++) own[i] = acc[36 * Q + i];
}
__device__ __forceinline__ void final_reduce(float* own, const uint32_t* xa, const uint32_t* xb, uint32_t* orow, int m, int hh, int q, int tid, uint32_t tag) {
  const uint4* pr = g_P + (size_t)((m * 2 + hh) * 16 + q) * 5 * 256 + tid;
  uint32_t v[3][20];
  uint32_t tries = 0;
  while (true) {
    uint32_t all = 1, any = 0;
#pragma unroll
    for (int d = 0; d < 3; d++) {
#pragma unroll
      for (int i = 0; i < 5; i++)
        asm volatile("ld.relaxed.gpu.global.v4.b32 {%0,%1,%2,%3}, [%4];" : "=r"(v[d][4 * i]), "=r"(v[d][4 * i + 1]), "=r"(v[d][4 * i + 2]), "=r"(v[d][4 * i + 3])
                     : "l"(pr + (((q + 3 - d) & 3) * 20 + i) * 256) : "memory");
    }
#pragma unroll
    for (int d = 0; d < 3; d++)
#pragma unroll
      for (int i = 0; i < 20; i++) { all &= v[d][i]; any |= v[d][i]; }
    if (__all_sync(0xffffffffu, ((tag ? all : ~any) & 1) != 0)) break;
    if (++tries > 0x100000u) asm volatile("trap;");
  }
#pragma unroll
  for (int i = 0; i < 18; i++) {
    own[2 * i] += (bf_lo(v[0][i]) + bf_lo(v[1][i])) + bf_lo(v[2][i]);
    own[2 * i + 1] += (bf_hi(v[0][i]) + bf_hi(v[1][i])) + bf_hi(v[2][i]);
  }
#pragma unroll
  for (int i = 0; i < 9; i++) {
    orow[4 * i] = pack(fmaf(own[4 * i], 0.5f, bf_lo(xa[i])), fmaf(own[4 * i + 1], 0.5f, bf_hi(xa[i])));
    orow[4 * i + 8 * (DM / 2)] = pack(fmaf(own[4 * i + 2], 0.5f, bf_lo(xb[i])), fmaf(own[4 * i + 3], 0.5f, bf_hi(xb[i])));
  }
}

__global__ void __launch_bounds__(384, 1) fused_kernel(const __grid_constant__ Params prm) {
  extern __shared__ __align__(1024) uint8_t smem[];
  const uint32_t sb = (uint32_t)__cvta_generic_to_shared(smem);
  const uint32_t bar = sb + SM_BAR;
  const int m = blockIdx.x & 15, j = blockIdx.x >> 4;
  const int cta = m * 8 + j;
  const int wr = __shfl_sync(0xffffffffu, (int)(threadIdx.x >> 5), 0);
  const int wg = wr >> 2;
  const int lane = threadIdx.x & 31;
  STAMP(0);
  if (threadIdx.x == 256) {
#pragma unroll
    for (int c = 0; c < 9; c++) mbar_init(bar + 8 * (B_X + c), 1);
    asm volatile("fence.proxy.async.shared::cta;" ::: "memory");
#pragma unroll 1
    for (int c = 0; c < 9; c++) {
      mbar_expect(bar + 8 * (B_X + c), 16384);
      tma2d(sb + SM_XN + c * 16384, &prm.xm, bar + 8 * (B_X + c), 64 * c, 128 * m);
    }
  } else if (threadIdx.x == 288) {
    if (sb & 1023) asm volatile("trap;");
#pragma unroll
    for (int i = 0; i < 3; i++) { mbar_init(bar + 8 * (B_QF + i), 1); mbar_init(bar + 8 * (B_QE + i), 8); mbar_init(bar + 8 * (B_GF + i), 1); mbar_init(bar + 8 * (B_GE + i), 8); mbar_init(bar + 8 * (B_KF + i), 1); mbar_init(bar + 8 * (B_KE + i), 8); }
#pragma unroll
    for (int i = 0; i < 5; i++) { mbar_init(bar + 8 * (B_BF + i), 1); mbar_init(bar + 8 * (B_BE + i), 8); }
    mbar_init(bar + 8 * B_SKV, 8); mbar_init(bar + 8 * B_SH, 8); mbar_init(bar + 8 * B_SO1, 8); mbar_init(bar + 8 * B_SO2, 8); mbar_init(bar + 8 * B_OL, 1);
    asm volatile("fence.proxy.async.shared::cta;" ::: "memory");
  } else if (threadIdx.x == 352 && m < 9) {
#pragma unroll
    for (int p = 0; p < 3; p++) { pf2d(&prm.wqkv64, 576 * p + 72 * j, 64 * m); pf2d(&prm.wqkv8, 576 * p + 72 * j + 64, 64 * m); }
  }
  __syncthreads();

  if (wg == 2) {
    asm volatile("setmaxnreg.dec.sync.aligned.u32 24;");
    const int pw = wr & 3;
    if (lane == 0) {
      if (pw == 0) {
#pragma unroll 1
        for (int kb = 0; kb < 9; kb++) {
          const int s = kb % 3;
          if (kb >= 3) mbar_wait(bar + 8 * (B_QE + s), (kb / 3 - 1) & 1);
          const uint32_t fb = bar + 8 * (B_QF + s), dst = sb + SM_RING + s * QST;
          mbar_expect(fb, QST);
#pragma unroll
          for (int p = 0; p < 3; p++) {
            tma2d(dst + p * 8192, &prm.wqkv64, fb, 576 * p + 72 * j, 64 * kb);
            tma2d(dst + 24576 + p * 1024, &prm.wqkv8, fb, 576 * p + 72 * j + 64, 64 * kb);
          }
        }
        int col = 576 * j, kr = 0, slot = 0, ph = 1;
#pragma unroll 1
        for (int s = 0; s < 108; s++) {
          if (s >= 5) mbar_wait(bar + 8 * (B_BE + slot), ph);
          else if (!(s & 1)) mbar_wait(bar + 8 * (B_QE + (s >> 1)), 0);
          const uint32_t fb = bar + 8 * (B_BF + slot), dst = sb + SM_RING + slot * BST;
          mbar_expect(fb, BST);
          tma2d(dst, &prm.wg, fb, col, kr);
          tma2d(dst + 6144, &prm.wu, fb, col, kr);
          if ((kr += 48) == 576) { kr = 0; col += 64; }
          if (++slot == 5) { slot = 0; ph ^= 1; }
        }
        mbar_arrive(bar + 8 * (B_BF + 3));
        const int hh = j & 1;
        uint32_t seen = 0;
#pragma unroll 1
        for (int b = 0; b < 20; b++) {
          const int st = b % 3;
          if (b >= 3) mbar_wait(bar + 8 * (B_GE + st), (b / 3 - 1) & 1);
          else if (b == 1) mbar_wait(bar + 8 * (B_BE + 0), 1);
          else if (b == 2) mbar_wait(bar + 8 * (B_BE + 2), 1);
          const uint32_t fb = bar + 8 * (B_GF + st), dst = sb + st * G2ST;
          if (b == 0) STAMPW(16);
          if (b < 18) {
            mbar_expect(fb, G2ST);
            const int own = (b < 8 || b == 16), tile = b < 16 ? (b & 7) : 8;
            const int jj = own ? j : (j ^ 1);
            const int kc = 576 * jj + 64 * tile;
            if (b == 8 || b >= 16) seen = 0;
            if (seen <= tile) { seen = flag_wait_v(FLAG_H(m * 8 + jj), tile + 1); fence_async(); }
            tma2d(dst, &prm.h, fb, kc, 128 * m);
#pragma unroll
            for (int a = 0; a < 5; a++) tma5d(dst + 16384 + a * 8192, &prm.wd[hh], fb, 64 * a, kc >> 5);
          } else {
            const int kc = 144 * (j >> 1);
            mbar_expect(fb, b == 18 ? G2ST : G2ST + 10240);
            if (b == 18) { flag_wait(FLAG_O(cta), 1); flag_wait(FLAG_O(cta ^ 1), 1); fence_async(); }
            tma2d(dst, &prm.o, fb, kc + 80 * (b - 18), 128 * m);
#pragma unroll
            for (int a = 0; a < 5; a++) tma2d(dst + 16384 + a * 8192, &prm.wo[hh], fb, 64 * a, kc + 64 * (b - 18));
            if (b == 19) {
#pragma unroll
              for (int a = 0; a < 5; a++) tma2d(sb + SM_W16 + a * 2048, &prm.wo16[hh], fb, 64 * a, kc + 128);
            }
          }
          if (b == 0) STAMPW(17);
        }
      } else if (pw == 1) {
        flag_wait(FLAG_KV(j), 16);
        fence_async();
        STAMPW(18);
        int slot = 0, ph = 1, vrow = 0;
        const int hx = (j & 1) * 3;
#pragma unroll 1
        for (int u = 0; u <= 128; u++) {
          if (u >= 3) mbar_wait(bar + 8 * (B_KE + slot), ph);
          const uint32_t fb = bar + 8 * (B_KF + slot), dst = sb + SM_KV + slot * KVST;
          const int krow = (4 * j + ((u >> 5) ^ hx)) * 256 + ((u + 2 * m) & 31) * 8;
          if (u == 0) vrow = krow;
          mbar_expect(fb, u < 128 ? KVST : KVST / 2);
          if (u < 128) tma2d(dst, &prm.kv, fb, 0, krow);
          tma2d(dst + 3072, &prm.kv, fb, 128, vrow);
          vrow = krow;
          if (++slot == 3) { slot = 0; ph ^= 1; }
        }
        mbar_expect(bar + 8 * B_OL, 16384);
        flag_wait(FLAG_O(cta), 2); flag_wait(FLAG_O(cta ^ 1), 2);
        fence_async();
        STAMPW(19);
        tma2d(sb + SM_OL, &prm.o, bar + 8 * B_OL, 144 * (j >> 1) + 48, 128 * m);
      } else if (pw == 2) {
        mbar_wait(bar + 8 * B_SKV, 0);
        STAMPW(22);
        fence_gpu(); flag_add(FLAG_KV(j));
        STAMPW(20);
#pragma unroll 1
        for (int t = 0; t < 9; t++) { mbar_wait(bar + 8 * B_SH, t & 1); fence_gpu(); flag_add(FLAG_H(cta)); }
        mbar_wait(bar + 8 * B_SO1, 0);
        fence_gpu(); flag_add(FLAG_O(cta));
        mbar_wait(bar + 8 * B_SO2, 0);
        fence_gpu(); flag_add(FLAG_O(cta));
        STAMPW(21);
      } else {
        mbar_wait(bar + 8 * (B_X + 8), 0);
#pragma unroll 1
        for (int b = m; b < 216; b += 16) {
          const int s = b >> 1;
          pf2d((b & 1) ? &prm.wu : &prm.wg, 576 * j + 64 * (s / 12), 48 * (s % 12));
        }
        mbar_wait(bar + 8 * B_SH, 0);
#pragma unroll 1
        for (int b = m; b < 90; b += 16) pf5d(&prm.wd[j & 1], 64 * (b % 5), 36 * (j >> 1) + 2 * (b / 5));
        if (m < 15) pf2d(&prm.wo[j & 1], 64 * (m % 5), 144 * (j >> 1) + 64 * (m / 5));
      }
    }
  } else {
    asm volatile("setmaxnreg.inc.sync.aligned.u32 240;");
    const int tid = threadIdx.x;
    const int t = lane & 3;
    const int row0 = 128 * m + 16 * wr + (lane >> 2);
    const uint32_t l0 = lane == 0;
    const uint32_t adesc = (((sb + SM_XN + wg * 8192) & 0x3FFFF) >> 4) | LO_A;
    const uint32_t bdesc = (((sb + SM_RING) & 0x3FFFF) >> 4) | LO_B48;
    const uint32_t kdesc0 = (((sb + SM_KV) & 0x3FFFF) >> 4) | LO_K;
    const int hx = (j & 1) * 3;
    float accA[64], accB[64];
    Att a;
    uint32_t badmask = 0;
#define AOFF(K) ((K) * 2 + ((K) >> 2) * 1016)
#define G1_ISSUE(ACC, I) _Pragma("unroll") for (int k = 0; k < 3; k++) wg_ss_n128<HI_SW128, HI_SW128>(ACC, adesc + AOFF(3 * (I) + k), bdesc + bslot * 768 + k * 128);
#define G1_ISSUE_Z(ACC)                                                                                        \
  wg_ss_z_n128<HI_SW128, HI_SW128>(ACC, adesc, bdesc + bslot * 768);                                           \
  _Pragma("unroll") for (int k = 1; k < 3; k++) wg_ss_n128<HI_SW128, HI_SW128>(ACC, adesc + k * 2, bdesc + bslot * 768 + k * 128);
    uint32_t bslot = 0, bph = 0, bprev = 0;
#define B_ADVANCE() { bprev = bslot; if (++bslot == 5) { bslot = 0; bph ^= 1; } }
    {
      const int lr = wr * 16 + (lane & 15);
      uint32_t ra[4];
#pragma unroll
      for (int k = 0; k < 4; k++) ra[k] = sb + SM_XN + lr * 128 + (((2 * k + (lane >> 4)) ^ (lr & 7)) << 4);
      float pv0 = 0.f, pv1 = 0.f, s0 = 0.f, s1 = 0.f, s2 = 0.f, s3 = 0.f, q0 = 0.f, q1 = 0.f, q2 = 0.f, q3 = 0.f;
#pragma unroll 1
      for (int c = 0; c < 9; c++) {
        mbar_wait(bar + 8 * (B_X + c), 0);
        uint32_t v[4][4];
#pragma unroll
        for (int k = 0; k < 4; k++) ldsm4(v[k], ra[k] + c * 16384);
        if (c == 0) { pv0 = __shfl_sync(0xffffffffu, bf_lo(v[0][0]), lane & ~3); pv1 = __shfl_sync(0xffffffffu, bf_lo(v[0][1]), lane & ~3); }
#pragma unroll
        for (int k = 0; k < 4; k++)
#pragma unroll
          for (int e = 0; e < 4; e += 2) {
            const float x0 = bf_lo(v[k][e]) - pv0, x1 = bf_hi(v[k][e]) - pv0, y0 = bf_lo(v[k][e + 1]) - pv1, y1 = bf_hi(v[k][e + 1]) - pv1;
            s0 += x0; s1 += x1; s2 += y0; s3 += y1;
            q0 = fmaf(x0, x0, q0); q1 = fmaf(x1, x1, q1); q2 = fmaf(y0, y0, q2); q3 = fmaf(y1, y1, q3);
          }
      }
      STAMP(11);
      s0 += s1; s2 += s3; q0 += q1; q2 += q3;
#pragma unroll
      for (int d = 1; d < 4; d <<= 1) {
        s0 += __shfl_xor_sync(0xffffffffu, s0, d); s2 += __shfl_xor_sync(0xffffffffu, s2, d);
        q0 += __shfl_xor_sync(0xffffffffu, q0, d); q2 += __shfl_xor_sync(0xffffffffu, q2, d);
      }
      s0 *= (1.f / 576.f); s2 *= (1.f / 576.f);
      const float var0 = fmaxf(fmaf(q0, 1.f / 576.f, -s0 * s0), 0.f), var1 = fmaxf(fmaf(q2, 1.f / 576.f, -s2 * s2), 0.f);
      const float inv0 = 1.f / bf_round(sqrtf(bf_round(bf_round(var0) + 1e-5f))), inv1 = 1.f / bf_round(sqrtf(bf_round(bf_round(var1) + 1e-5f)));
      const uint32_t mb0 = pack(pv0 + s0, pv0 + s0), mb1 = pack(pv1 + s2, pv1 + s2);
      const uint32_t h0 = pack(inv0, inv0), h1 = pack(inv1, inv1);
      const uint32_t e0 = pack(inv0 - bf_lo(h0), inv0 - bf_lo(h0)), e1 = pack(inv1 - bf_lo(h1), inv1 - bf_lo(h1));
#define NORM_SLAB(C)                                                                                           \
  {                                                                                                            \
    uint32_t v[4][4];                                                                                          \
    _Pragma("unroll") for (int k = 0; k < 4; k++) ldsm4(v[k], ra[k] + (C) * 16384);                            \
    _Pragma("unroll") for (int k = 0; k < 4; k++)                                                              \
      stsm4(ra[k] + (C) * 16384, bscale2(bsub2(v[k][0], mb0), h0, e0), bscale2(bsub2(v[k][1], mb1), h1, e1),   \
            bscale2(bsub2(v[k][2], mb0), h0, e0), bscale2(bsub2(v[k][3], mb1), h1, e1));                       \
    asm volatile("fence.proxy.async.shared::cta;" ::: "memory");                                               \
    if (wg == 0) asm volatile("bar.sync 1, 128;" ::: "memory"); else asm volatile("bar.sync 2, 128;" ::: "memory"); \
  }
      NORM_SLAB(0)
      STAMP(1);
      float aq[96], ar[12];
      const uint32_t qdesc = (((sb + SM_RING) & 0x3FFFF) >> 4) | LO_B;
      const uint32_t rdesc = (((sb + SM_RING + 24576) & 0x3FFFF) >> 4) | LO_R;
      uint32_t s = 0, ph = 0;
#pragma unroll 1
      for (int kb = 0; kb < 9; kb++) {
        mbar_wait(bar + 8 * B_QF + 8 * s, ph);
        wg_fence();
#pragma unroll
        for (int k = 0; k < 4; k++) {
          wg_ss_p_n192<HI_SW128, HI_SW128>(aq, adesc + kb * 1024 + k * 2, qdesc + s * (QST >> 4) + k * 128, kb + k);
          wg_ss_p_n24<HI_SW128, HI_R>(ar, adesc + kb * 1024 + k * 2, rdesc + s * (QST >> 4) + k * 16, kb + k);
        }
        wg_commit();
        if (kb < 8) NORM_SLAB(kb + 1)
        wg_wait<1>();
        mbar_arrive_if(bar + 8 * B_QE + (s == 0 ? 16 : 8 * s - 8), l0 & (kb > 0));
        if (++s == 3) { s = 0; ph ^= 1; }
      }
      wg_wait<0>();
      pin<96>(aq); pin<12>(ar);
      mbar_arrive_if(bar + 8 * (B_QE + 2), l0);
      STAMP(2);
      uint32_t* kvp = g_KV + (size_t)(4 * j) * SEQ * 20 + (row0 >> 3) * 160 + lane;
      {
        uint32_t pk[2][9][2];
#pragma unroll
        for (int p = 0; p < 2; p++)
#pragma unroll
          for (int i = 0; i < 9; i++) {
            const float* src = i < 8 ? &aq[(8 * (p + 1) + i) * 4] : &ar[4 * (p + 1)];
            pk[p][i][0] = pack(src[0], src[1]); pk[p][i][1] = pack(src[2], src[3]);
          }
#pragma unroll
        for (int hp = 0; hp < 4; hp++) {
          const bool up = t < hp;
#pragma unroll
          for (int rh = 0; rh < 2; rh++) {
            uint32_t* d = kvp + hp * SEQ * 20 + rh * 160;
            d[0] = up ? pk[0][2 * hp + 1][rh] : pk[0][2 * hp][rh];
            d[32] = up ? pk[0][2 * hp + 2][rh] : pk[0][2 * hp + 1][rh];
            d[96] = up ? pk[1][2 * hp + 1][rh] : pk[1][2 * hp][rh];
            d[128] = up ? pk[1][2 * hp + 2][rh] : pk[1][2 * hp + 1][rh];
            const uint32_t v9 = __shfl_sync(0xffffffffu, pk[1][2 * hp + 2][rh], (lane & ~3) | hp);
            d[64] = t == hp ? pk[0][2 * hp + 2][rh] : t == ((hp + 1) & 3) ? 0x3f803f80u : t == ((hp + 2) & 3) ? v9 : 0u;
          }
        }
      }
      __syncwarp();
      mbar_arrive_if(bar + 8 * B_SKV, l0);
      STAMP(3);
      mbar_wait(bar + 8 * B_BF, 0);
      wg_fence();
      G1_ISSUE_Z(accA)
      wg_commit();
      B_ADVANCE()
      uint32_t pq[9][2];
#pragma unroll
      for (int i = 0; i < 9; i++) {
        const float* src = i < 8 ? &aq[i * 4] : &ar[0];
        pq[i][0] = pack(bf_round(src[0]) * QSCALE, bf_round(src[1]) * QSCALE); pq[i][1] = pack(bf_round(src[2]) * QSCALE, bf_round(src[3]) * QSCALE);
      }
      uint32_t* qp = g_Q + (cta * 4 * 256 + tid) * 8;
#pragma unroll
      for (int hp = 0; hp < 4; hp++) {
        const bool up = t < hp;
        *reinterpret_cast<uint4*>(qp + hp * 2048) = make_uint4(up ? pq[2 * hp + 1][0] : pq[2 * hp][0], up ? pq[2 * hp + 1][1] : pq[2 * hp][1],
                                                               up ? pq[2 * hp + 2][0] : pq[2 * hp + 1][0], up ? pq[2 * hp + 2][1] : pq[2 * hp + 1][1]);
        *reinterpret_cast<uint4*>(qp + hp * 2048 + 4) = make_uint4(t == hp ? pq[2 * hp + 2][0] : 0u, t == hp ? pq[2 * hp + 2][1] : 0u, 0u, 0u);
      }
      load_q(a, cta, hx, tid);
#pragma unroll
      for (int i = 0; i < 16; i++) a.p[i] = 0;
#pragma unroll
      for (int i = 0; i < 12; i++) a.o[i] = 0.f;
      pin<16>(a.p); pin<12>(a.o);
    }
#pragma unroll 1
    for (int i = 1; i < NG0; i++) {
      mbar_wait(bar + 8 * B_BF + 8 * bslot, bph);
      wg_fence();
      G1_ISSUE(accA, i)
      wg_commit();
      wg_wait<1>();
      mbar_arrive_if(bar + 8 * B_BE + 8 * bprev, l0);
      B_ADVANCE()
    }
    pin<8>(a.q);
    STAMP(4);
    mbar_wait(bar + 8 * B_BF + 8 * bslot, bph);
    mbar_wait(bar + 8 * B_KF, 0);
    STAMP(23);
    uint32_t kslot = 0, kph = 0;
    uint32_t it = 0;
    bool early_o = false;
    __nv_bfloat16* hdst = g_H + (size_t)row0 * FF + 576 * j + 8 * t;

#define ITEM_SWITCH()                                                                                          \
  if ((it & 31) == 0) {                                                                                        \
    pin<12>(a.o);                                                                                              \
    if (it != 0) badmask |= (uint32_t)o_epilogue(a.o, ((it >> 5) - 1) ^ hx, j, row0, lane) << (((it >> 5) - 1) ^ hx); \
    first_tile(a, (it >> 5) ^ hx, lane);                                                                       \
  } else if ((it & 31) == 31) {                                                                                \
    load_q(a, cta, (((it >> 5) + 1) & 3) ^ hx, tid);                                                           \
  }
#define EPI_STEP(ACCN, ACCO)                                                                                   \
  {                                                                                                            \
    wg_fence();                                                                                                \
    G1_ISSUE_Z(ACCN)                                                                                           \
    wg_commit();                                                                                               \
    wg_wait<1>();                                                                                              \
    pin<64>(ACCO);                                                                                             \
    mbar_arrive_if(bar + 8 * B_BE + 8 * bprev, l0);                                                            \
    B_ADVANCE()                                                                                                \
    const uint32_t ok = mbar_test(bar + 8 * B_BF + 8 * bslot, bph);                                            \
    h_epilogue(ACCO, hdst);                                                                                    \
    hdst += 64;                                                                                                \
    __syncwarp();                                                                                              \
    mbar_arrive_if(bar + 8 * B_SH, l0);                                                                        \
    mbar_wait2_unless(ok, bar + 8 * B_BF + 8 * bslot, bph, bar + 8 * B_BF + 8 * bslot, bph);                   \
  }
#define ATT_STEP1(ACC, I)                                                                                      \
  {                                                                                                            \
    wg_fence();                                                                                                \
    issue_att(a, kdesc0 + kslot * 384);                                                                        \
    wg_commit();                                                                                               \
    G1_ISSUE(ACC, I)                                                                                           \
    wg_commit();                                                                                               \
    wg_wait<1>();                                                                                              \
    pin<32>(a.s);                                                                                              \
    mbar_arrive_if(bar + 8 * B_BE + 8 * bprev, l0);                                                            \
    mbar_arrive_if(bar + 8 * B_KE + kslot * 8, l0);                                                            \
    B_ADVANCE()                                                                                                \
    if (++kslot == 3) { kslot = 0; kph ^= 1; }                                                                 \
    const uint32_t ok = mbar_test(bar + 8 * B_BF + 8 * bslot, bph) & mbar_test(bar + 8 * B_KF + kslot * 8, kph); \
    ITEM_SWITCH()                                                                                              \
    softmax_tile(a);                                                                                           \
    pin<8>(a.q);                                                                                               \
    it++;                                                                                                      \
    mbar_wait2_unless(ok, bar + 8 * B_BF + 8 * bslot, bph, bar + 8 * B_KF + kslot * 8, kph);                   \
  }
    {
      int i = NG0;
#pragma unroll 1
      for (int pr = 0;; pr++) {
#pragma unroll 1
        for (; i < 12; i++) ATT_STEP1(accA, i)
        if (pr == 4) break;
        EPI_STEP(accB, accA)
#pragma unroll 1
        for (i = 1; i < 12; i++) ATT_STEP1(accB, i)
        EPI_STEP(accA, accB)
        i = 1;
      }
    }
    STAMP(5);
    wg_wait<0>();
    pin<64>(accA);
    mbar_arrive_if(bar + 8 * B_BE + 8 * bprev, l0);
    h_epilogue(accA, hdst);
    __syncwarp();
    mbar_arrive_if(bar + 8 * B_SH, l0);
    STAMP(6);
    mbar_wait(bar + 8 * B_GF, 0);
    STAMP(12);

    float acc2[144];
    const uint32_t a2desc = (((sb + wg * 8192) & 0x3FFFF) >> 4) | LO_A;
    const uint32_t b2desc = (((sb + 16384) & 0x3FFFF) >> 4) | LO_B;
    uint32_t st = 0, gph = 0;
#define G2_MMA(AD, BD, NOFF)                                                                                   \
  wg_ss_n128<HI_SW128, HI_SW128>(acc2, AD, BD);                                                                \
  wg_ss_n160<HI_SW128, HI_SW128>(acc2 + 64, AD, (BD) + (NOFF));
#define ATT_STEP2(N, ZERO)                                                                                     \
  {                                                                                                            \
    const uint32_t h2 = (N) & 1;                                                                               \
    wg_fence();                                                                                                \
    issue_att(a, kdesc0 + kslot * 384);                                                                        \
    wg_commit();                                                                                               \
    if (ZERO) {                                                                                                \
      wg_ss_z_n128<HI_SW128, HI_SW128>(acc2, a2desc, b2desc);                                                  \
      wg_ss_z_n160<HI_SW128, HI_SW128>(acc2 + 64, a2desc, b2desc + 1024);                                      \
    } else { G2_MMA(a2desc + st * 3584 + h2 * 4, b2desc + st * 3584 + h2 * 256, 1024) }                        \
    G2_MMA(a2desc + st * 3584 + h2 * 4 + 2, b2desc + st * 3584 + h2 * 256 + 128, 1024)                         \
    wg_commit();                                                                                               \
    wg_wait<1>();                                                                                              \
    pin<32>(a.s);                                                                                              \
    mbar_arrive_if(bar + 8 * B_KE + kslot * 8, l0);                                                            \
    if (!(ZERO)) mbar_arrive_if(bar + 8 * B_GE + (st == 0 ? 16 : st * 8 - 8), l0 & (h2 ^ 1));                  \
    if (++kslot == 3) { kslot = 0; kph ^= 1; }                                                                 \
    if (h2) { if (++st == 3) { st = 0; gph ^= 1; } }                                                           \
    const uint32_t ok = mbar_test(bar + 8 * B_GF + st * 8, gph) & mbar_test(bar + 8 * B_KF + kslot * 8, kph);  \
    if (!(ZERO)) {                                                                                             \
      ITEM_SWITCH()                                                                                            \
      if (it == 96) { __syncwarp(); mbar_arrive_if(bar + 8 * B_SO1, l0 & (badmask == 0)); early_o = badmask == 0; } \
    }                                                                                                          \
    softmax_tile(a);                                                                                           \
    pin<8>(a.q);                                                                                               \
    it++;                                                                                                      \
    mbar_wait2_unless(ok, bar + 8 * B_GF + st * 8, gph, bar + 8 * B_KF + kslot * 8, kph);                      \
  }
    static_assert(NG0 == 7, "tail code below assumes 35 GEMM2 slots");
    ATT_STEP2(0, true);
#pragma unroll 1
    for (int n = 1; n < 35; n++) ATT_STEP2(n, false);
    STAMP(7);
    wg_fence();
    issue_pv(a, kdesc0 + kslot * 384);
    wg_commit();
    G2_MMA(a2desc + 7168 + 4, b2desc + 7168 + 256, 1024)
    G2_MMA(a2desc + 7168 + 6, b2desc + 7168 + 384, 1024)
    wg_commit();
    wg_wait<1>();
    pin<12>(a.o);
    badmask |= (uint32_t)o_epilogue(a.o, 3 ^ hx, j, row0, lane) << (3 ^ hx);
    __syncwarp();
    mbar_arrive_if(bar + 8 * B_SO2, l0 & (badmask == 0));
    if (badmask != 0) {
      wg_wait<0>();
#pragma unroll 1
      for (int hp = 0; hp < 4; hp++)
        if ((badmask >> hp) & 1) attn_slow_rows(cta, j, hp, 128 * m + 16 * wr, tid & ~31);
      __syncwarp();
      mbar_arrive_if(bar + 8 * B_SO1, l0 & !early_o);
      mbar_arrive_if(bar + 8 * B_SO2, l0);
    }
    STAMP(8);
    mbar_wait(bar + 8 * (B_GF + 0), 0);
    wg_fence();
#pragma unroll
    for (int k = 0; k < 3; k++) { G2_MMA(a2desc + k * 2, b2desc + k * 128, 1024) }
    wg_commit();
    mbar_wait(bar + 8 * (B_GF + 1), 0);
    wg_fence();
    G2_MMA(a2desc + 3584 + 2, b2desc + 3584 + 256, 1024)
    G2_MMA(a2desc + 3584 + 4, b2desc + 3584 + 384, 1024)
    G2_MMA(a2desc + 3584 + 6, (((sb + SM_W16) & 0x3FFFF) >> 4) | LO_B16, 256)
    wg_commit();
    STAMP(13);
    int tid2, bid2;
    asm volatile("mov.u32 %0, %%tid.x;" : "=r"(tid2));
    asm volatile("mov.u32 %0, %%ctaid.x;" : "=r"(bid2));
    const int m2 = bid2 & 15, j2 = bid2 >> 4;
    const size_t xoff = (size_t)(128 * m2 + (tid2 >> 5) * 16 + ((tid2 & 31) >> 2)) * DM + 288 * (j2 & 1) + 72 * (j2 >> 1) + 2 * (tid2 & 3);
    uint32_t xa[9], xb[9];
    {
      const uint32_t* xr = reinterpret_cast<const uint32_t*>(prm.x + xoff);
#pragma unroll
      for (int i = 0; i < 9; i++) { xa[i] = __ldg(xr + 4 * i); xb[i] = __ldg(xr + 4 * i + 8 * (DM / 2)); }
    }
    const uint32_t tag = (*(volatile uint32_t*)FLAG_EPOCH + 1) & 1;
    mbar_wait(bar + 8 * B_OL, 0);
    STAMP(14);
    wg_fence();
    G2_MMA(a2desc + (SM_OL >> 4), b2desc + 384, 1024)
    G2_MMA(a2desc + (SM_OL >> 4) + 2, b2desc + 3584, 1024)
    G2_MMA(a2desc + (SM_OL >> 4) + 4, b2desc + 3584 + 128, 1024)
    wg_commit();
    wg_wait<0>();
    pin<144>(acc2);
    STAMP(9);
    {
      float own[36];
      switch (j2 >> 1) {
        case 0: final_store<0>(acc2, own, m2, j2 & 1, tid2, tag); break;
        case 1: final_store<1>(acc2, own, m2, j2 & 1, tid2, tag); break;
        case 2: final_store<2>(acc2, own, m2, j2 & 1, tid2, tag); break;
        default: final_store<3>(acc2, own, m2, j2 & 1, tid2, tag); break;
      }
      pin<36>(own);
      STAMP(15);
      final_reduce(own, xa, xb, reinterpret_cast<uint32_t*>(prm.out + xoff), m2, j2 & 1, j2 >> 1, tid2, tag);
    }
    STAMP(10);
    __syncwarp();
    if (lane == 0) {
      if (atomicInc(FLAG_DONE, NCTA * 8 - 1) == NCTA * 8 - 1) {
        for (int i = 0; i < 8; i++) *FLAG_KV(i) = 0;
        for (int i = 0; i < NCTA; i++) { *FLAG_H(i) = 0; *FLAG_O(i) = 0; }
        *FLAG_EPOCH = tag;
      }
    }
  }
}

typedef CUresult (*EncodeFn)(CUtensorMap*, CUtensorMapDataType, cuuint32_t, void*, const cuuint64_t*, const cuuint64_t*, const cuuint32_t*, const cuuint32_t*,
                             CUtensorMapInterleave, CUtensorMapSwizzle, CUtensorMapL2promotion, CUtensorMapFloatOOBfill);

void enc2d(EncodeFn enc, CUtensorMap* tm, const void* base, uint64_t w, uint64_t h, uint64_t pitch_elems, uint32_t bw, uint32_t bh, CUtensorMapSwizzle sw) {
  cuuint64_t dims[2] = {w, h}, str[1] = {pitch_elems * 2};
  cuuint32_t box[2] = {bw, bh}, es[2] = {1, 1};
  enc(tm, CU_TENSOR_MAP_DATA_TYPE_BFLOAT16, 2, const_cast<void*>(base), dims, str, box, es, CU_TENSOR_MAP_INTERLEAVE_NONE, sw,
      CU_TENSOR_MAP_L2_PROMOTION_L2_128B, CU_TENSOR_MAP_FLOAT_OOB_FILL_NONE);
}

}

extern "C" void kernel_launch(void* const* d_in, const int* in_sizes, int n_in, void* d_out, int out_size) {
  (void)in_sizes; (void)n_in; (void)out_size;
  const __nv_bfloat16* x = (const __nv_bfloat16*)d_in[0];
  const __nv_bfloat16* wqkv = (const __nv_bfloat16*)d_in[1];
  const __nv_bfloat16* wo = (const __nv_bfloat16*)d_in[2];
  const __nv_bfloat16* wg = (const __nv_bfloat16*)d_in[4];
  const __nv_bfloat16* wu = (const __nv_bfloat16*)d_in[5];
  const __nv_bfloat16* wd = (const __nv_bfloat16*)d_in[6];
  void* fn = nullptr;
  cudaDriverEntryPointQueryResult qr;
  cudaGetDriverEntryPoint("cuTensorMapEncodeTiled", &fn, cudaEnableDefault, &qr);
  EncodeFn enc = (EncodeFn)fn;
  void *hp = nullptr, *op = nullptr, *kvp = nullptr;
  cudaGetSymbolAddress(&kvp, g_KV);
  cudaGetSymbolAddress(&hp, g_H);
  cudaGetSymbolAddress(&op, g_O);
  Params p;
  enc2d(enc, &p.xm, x, DM, SEQ, DM, 64, 128, CU_TENSOR_MAP_SWIZZLE_128B);
  enc2d(enc, &p.kv, kvp, 320, 32 * 256, 320, 192, 8, CU_TENSOR_MAP_SWIZZLE_NONE);
  enc2d(enc, &p.wqkv64, wqkv, 3 * DM, DM, 3 * DM, 64, 64, CU_TENSOR_MAP_SWIZZLE_128B);
  enc2d(enc, &p.wqkv8, wqkv, 3 * DM, DM, 3 * DM, 8, 64, CU_TENSOR_MAP_SWIZZLE_NONE);
  enc2d(enc, &p.wg, wg, FF, DM, FF, 64, 48, CU_TENSOR_MAP_SWIZZLE_128B);
  enc2d(enc, &p.wu, wu, FF, DM, FF, 64, 48, CU_TENSOR_MAP_SWIZZLE_128B);
  enc2d(enc, &p.h, hp, FF, SEQ, FF, 64, 128, CU_TENSOR_MAP_SWIZZLE_128B);
  enc2d(enc, &p.o, op, DM, SEQ, DM, 64, 128, CU_TENSOR_MAP_SWIZZLE_128B);
  for (int hh = 0; hh < 2; hh++) {
    enc2d(enc, &p.wo[hh], wo + 288 * hh, 288, DM, DM, 64, 64, CU_TENSOR_MAP_SWIZZLE_128B);
    enc2d(enc, &p.wo16[hh], wo + 288 * hh, 288, DM, DM, 64, 16, CU_TENSOR_MAP_SWIZZLE_128B);
    cuuint64_t dims[5] = {288, 2, 4, 4, FF / 32}, str[4] = {DM * 2, 8 * DM * 2, 2 * DM * 2, 32 * DM * 2};
    cuuint32_t box[5] = {64, 2, 4, 4, 2}, es[5] = {1, 1, 1, 1, 1};
    enc(&p.wd[hh], CU_TENSOR_MAP_DATA_TYPE_BFLOAT16, 5, (void*)(wd + 288 * hh), dims, str, box, es, CU_TENSOR_MAP_INTERLEAVE_NONE,
        CU_TENSOR_MAP_SWIZZLE_128B, CU_TENSOR_MAP_L2_PROMOTION_L2_128B, CU_TENSOR_MAP_FLOAT_OOB_FILL_NONE);
  }
  p.x = x;
  p.out = (__nv_bfloat16*)d_out;
  cudaFuncSetAttribute(fused_kernel, cudaFuncAttributeMaxDynamicSharedMemorySize, SM_TOTAL);
  fused_kernel<<<NCTA, 384, SM_TOTAL, cudaStreamPerThread>>>(p);
}
```

```cpp
#include <cuda_runtime.h>
#include <cuda.h>
#include <cuda_bf16.h>
#include <stdint.h>

namespace {

constexpr int SEQ = 2048, DM = 576, FF = 4608;
constexpr int NCTA = 128;

constexpr uint32_t SM_XN = 0;
constexpr uint32_t SM_RING = 147456;
constexpr uint32_t SM_KV = 208896;
constexpr uint32_t QST = 27648, BST = 12288, KVST = 6144, G2ST = 57344;
constexpr uint32_t SM_OL = 172032;
constexpr uint32_t SM_W16 = SM_OL + 4096;
constexpr uint32_t SM_BAR = 232064;
constexpr uint32_t SM_TOTAL = 232448;
enum { B_QF = 0, B_QE = 3, B_BF = 6, B_BE = 11, B_GF = 16, B_GE = 19, B_KF = 22, B_KE = 25, B_SKV = 28, B_SH = 29, B_SO1 = 30, B_SO2 = 31,
       B_OL = 32, B_X = 33, B_NR = 42, B_N = 44 };
constexpr int NG0 = 7;

constexpr uint32_t HI_SW128 = 0x40000040u;
constexpr uint32_t LO_A = 1u << 16;
constexpr uint32_t LO_B = 512u << 16;
constexpr uint32_t HI_R = 64u, LO_R = 8u << 16;
constexpr uint32_t HI_K = 24u, LO_K = 8u << 16;
constexpr uint32_t HI_V = 8u, LO_V = 24u << 16;
constexpr uint32_t LO_B48 = 384u << 16;
constexpr uint32_t HI_O = 8u, LO_O = 128u << 16;
constexpr uint32_t LO_B16 = 128u << 16;

constexpr float QSCALE = 0.23570226039551584f * 1.4426950408889634f;
constexpr float MOFF = 90.f;

struct __align__(64) Params {
  CUtensorMap xm, wqkv64, wqkv8, wg, wu, h, wd[2], wo[2], wo16[2], kv;
  const __nv_bfloat16* x;
  __nv_bfloat16* out;
};

__device__ __align__(1024) __nv_bfloat16 g_H[SEQ * FF];
__device__ __align__(1024) uint32_t g_O[NCTA * 9 * 512];
__device__ __align__(1024) uint32_t g_KV[32 * SEQ * 20];
__device__ __align__(1024) uint32_t g_Q[NCTA * 4 * 256 * 8];
__device__ __align__(1024) uint4 g_P[32 * 16 * 5 * 256];
__device__ uint32_t g_flags[8 * 32 + NCTA * 32 * 3 + 32];
#define FLAG_KV(j) (&g_flags[(j) * 32])
#define FLAG_H(c) (&g_flags[8 * 32 + (c) * 32])
#define FLAG_O(c) (&g_flags[8 * 32 + NCTA * 32 + (c) * 32])
#define FLAG_P(c) (&g_flags[8 * 32 + NCTA * 64 + (c) * 32])
#define FLAG_DONE (&g_flags[8 * 32 + NCTA * 96])
#define FLAG_EPOCH (&g_flags[8 * 32 + NCTA * 96 + 16])
#define STAMP(i)
#define STAMPW(i)

template<uint32_t AHI, uint32_t BHI> __device__ __forceinline__ void wg_ss_n192(float* d, uint32_t a, uint32_t b) {
  asm volatile("{\n.reg .pred p;\n.reg .b64 da, db;\nsetp.ne.b32 p, 1, 0;\nmov.b64 da, {%96, %98};\nmov.b64 db, {%97, %99};\n"
    "wgmma.mma_async.sync.aligned.m64n192k16.f32.bf16.bf16 {%0, %1, %2, %3, %4, %5, %6, %7, %8, %9, %10, %11, %12, %13, %14, %15, %16, %17, %18, %19, %20, %21, %22, %23, %24, %25, %26, %27, %28, %29, %30, %31, %32, %33, %34, %35, %36, %37, %38, %39, %40, %41, %42, %43, %44, %45, %46, %47, %48, %49, %50, %51, %52, %53, %54, %55, %56, %57, %58, %59, %60, %61, %62, %63, %64, %65, %66, %67, %68, %69, %70, %71, %72, %73, %74, %75, %76, %77, %78, %79, %80, %81, %82, %83, %84, %85, %86, %87, %88, %89, %90, %91, %92, %93, %94, %95}, da, db, p, 1, 1, 0, 1;\n}\n"
    : "+f"(d[0]), "+f"(d[1]), "+f"(d[2]), "+f"(d[3]), "+f"(d[4]), "+f"(d[5]), "+f"(d[6]), "+f"(d[7]), "+f"(d[8]), "+f"(d[9]), "+f"(d[10]), "+f"(d[11]), "+f"(d[12]), "+f"(d[13]), "+f"(d[14]), "+f"(d[15]), "+f"(d[16]), "+f"(d[17]), "+f"(d[18]), "+f"(d[19]), "+f"(d[20]), "+f"(d[21]), "+f"(d[22]), "+f"(d[23]), "+f"(d[24]), "+f"(d[25]), "+f"(d[26]), "+f"(d[27]), "+f"(d[28]), "+f"(d[29]), "+f"(d[30]), "+f"(d[31]), "+f"(d[32]), "+f"(d[33]), "+f"(d[34]), "+f"(d[35]), "+f"(d[36]), "+f"(d[37]), "+f"(d[38]), "+f"(d[39]), "+f"(d[40]), "+f"(d[41]), "+f"(d[42]), "+f"(d[43]), "+f"(d[44]), "+f"(d[45]), "+f"(d[46]), "+f"(d[47]), "+f"(d[48]), "+f"(d[49]), "+f"(d[50]), "+f"(d[51]), "+f"(d[52]), "+f"(d[53]), "+f"(d[54]), "+f"(d[55]), "+f"(d[56]), "+f"(d[57]), "+f"(d[58]), "+f"(d[59]), "+f"(d[60]), "+f"(d[61]), "+f"(d[62]), "+f"(d[63]), "+f"(d[64]), "+f"(d[65]), "+f"(d[66]), "+f"(d[67]), "+f"(d[68]), "+f"(d[69]), "+f"(d[70]), "+f"(d[71]), "+f"(d[72]), "+f"(d[73]), "+f"(d[74]), "+f"(d[75]), "+f"(d[76]), "+f"(d[77]), "+f"(d[78]), "+f"(d[79]), "+f"(d[80]), "+f"(d[81]), "+f"(d[82]), "+f"(d[83]), "+f"(d[84]), "+f"(d[85]), "+f"(d[86]), "+f"(d[87]), "+f"(d[88]), "+f"(d[89]), "+f"(d[90]), "+f"(d[91]), "+f"(d[92]), "+f"(d[93]), "+f"(d[94]), "+f"(d[95])
    : "r"(a), "r"(b), "n"(AHI), "n"(BHI));
}
template<uint32_t AHI, uint32_t BHI> __device__ __forceinline__ void wg_ss_z_n192(float* d, uint32_t a, uint32_t b) {
  asm volatile("{\n.reg .pred p;\n.reg .b64 da, db;\nsetp.ne.b32 p, 0, 0;\nmov.b64 da, {%96, %98};\nmov.b64 db, {%97, %99};\n"
    "wgmma.mma_async.sync.aligned.m64n192k16.f32.bf16.bf16 {%0, %1, %2, %3, %4, %5, %6, %7, %8, %9, %10, %11, %12, %13, %14, %15, %16, %17, %18, %19, %20, %21, %22, %23, %24, %25, %26, %27, %28, %29, %30, %31, %32, %33, %34, %35, %36, %37, %38, %39, %40, %41, %42, %43, %44, %45, %46, %47, %48, %49, %50, %51, %52, %53, %54, %55, %56, %57, %58, %59, %60, %61, %62, %63, %64, %65, %66, %67, %68, %69, %70, %71, %72, %73, %74, %75, %76, %77, %78, %79, %80, %81, %82, %83, %84, %85, %86, %87, %88, %89, %90, %91, %92, %93, %94, %95}, da, db, p, 1, 1, 0, 1;\n}\n"
    : "=f"(d[0]), "=f"(d[1]), "=f"(d[2]), "=f"(d[3]), "=f"(d[4]), "=f"(d[5]), "=f"(d[6]), "=f"(d[7]), "=f"(d[8]), "=f"(d[9]), "=f"(d[10]), "=f"(d[11]), "=f"(d[12]), "=f"(d[13]), "=f"(d[14]), "=f"(d[15]), "=f"(d[16]), "=f"(d[17]), "=f"(d[18]), "=f"(d[19]), "=f"(d[20]), "=f"(d[21]), "=f"(d[22]), "=f"(d[23]), "=f"(d[24]), "=f"(d[25]), "=f"(d[26]), "=f"(d[27]), "=f"(d[28]), "=f"(d[29]), "=f"(d[30]), "=f"(d[31]), "=f"(d[32]), "=f"(d[33]), "=f"(d[34]), "=f"(d[35]), "=f"(d[36]), "=f"(d[37]), "=f"(d[38]), "=f"(d[39]), "=f"(d[40]), "=f"(d[41]), "=f"(d[42]), "=f"(d[43]), "=f"(d[44]), "=f"(d[45]), "=f"(d[46]), "=f"(d[47]), "=f"(d[48]), "=f"(d[49]), "=f"(d[50]), "=f"(d[51]), "=f"(d[52]), "=f"(d[53]), "=f"(d[54]), "=f"(d[55]), "=f"(d[56]), "=f"(d[57]), "=f"(d[58]), "=f"(d[59]), "=f"(d[60]), "=f"(d[61]), "=f"(d[62]), "=f"(d[63]), "=f"(d[64]), "=f"(d[65]), "=f"(d[66]), "=f"(d[67]), "=f"(d[68]), "=f"(d[69]), "=f"(d[70]), "=f"(d[71]), "=f"(d[72]), "=f"(d[73]), "=f"(d[74]), "=f"(d[75]), "=f"(d[76]), "=f"(d[77]), "=f"(d[78]), "=f"(d[79]), "=f"(d[80]), "=f"(d[81]), "=f"(d[82]), "=f"(d[83]), "=f"(d[84]), "=f"(d[85]), "=f"(d[86]), "=f"(d[87]), "=f"(d[88]), "=f"(d[89]), "=f"(d[90]), "=f"(d[91]), "=f"(d[92]), "=f"(d[93]), "=f"(d[94]), "=f"(d[95])
    : "r"(a), "r"(b), "n"(AHI), "n"(BHI));
}
template<uint32_t AHI, uint32_t BHI> __device__ __forceinline__ void wg_ss_n24(float* d, uint32_t a, uint32_t b) {
  asm volatile("{\n.reg .pred p;\n.reg .b64 da, db;\nsetp.ne.b32 p, 1, 0;\nmov.b64 da, {%12, %14};\nmov.b64 db, {%13, %15};\n"
    "wgmma.mma_async.sync.aligned.m64n24k16.f32.bf16.bf16 {%0, %1, %2, %3, %4, %5, %6, %7, %8, %9, %10, %11}, da, db, p, 1, 1, 0, 1;\n}\n"
    : "+f"(d[0]), "+f"(d[1]), "+f"(d[2]), "+f"(d[3]), "+f"(d[4]), "+f"(d[5]), "+f"(d[6]), "+f"(d[7]), "+f"(d[8]), "+f"(d[9]), "+f"(d[10]), "+f"(d[11])
    : "r"(a), "r"(b), "n"(AHI), "n"(BHI));
}
template<uint32_t AHI, uint32_t BHI> __device__ __forceinline__ void wg_ss_z_n24(float* d, uint32_t a, uint32_t b) {
  asm volatile("{\n.reg .pred p;\n.reg .b64 da, db;\nsetp.ne.b32 p, 0, 0;\nmov.b64 da, {%12, %14};\nmov.b64 db, {%13, %15};\n"
    "wgmma.mma_async.sync.aligned.m64n24k16.f32.bf16.bf16 {%0, %1, %2, %3, %4, %5, %6, %7, %8, %9, %10, %11}, da, db, p, 1, 1, 0, 1;\n}\n"
    : "=f"(d[0]), "=f"(d[1]), "=f"(d[2]), "=f"(d[3]), "=f"(d[4]), "=f"(d[5]), "=f"(d[6]), "=f"(d[7]), "=f"(d[8]), "=f"(d[9]), "=f"(d[10]), "=f"(d[11])
    : "r"(a), "r"(b), "n"(AHI), "n"(BHI));
}
template<uint32_t AHI, uint32_t BHI> __device__ __forceinline__ void wg_ss_n128(float* d, uint32_t a, uint32_t b) {
  asm volatile("{\n.reg .pred p;\n.reg .b64 da, db;\nsetp.ne.b32 p, 1, 0;\nmov.b64 da, {%64, %66};\nmov.b64 db, {%65, %67};\n"
    "wgmma.mma_async.sync.aligned.m64n128k16.f32.bf16.bf16 {%0, %1, %2, %3, %4, %5, %6, %7, %8, %9, %10, %11, %12, %13, %14, %15, %16, %17, %18, %19, %20, %21, %22, %23, %24, %25, %26, %27, %28, %29, %30, %31, %32, %33, %34, %35, %36, %37, %38, %39, %40, %41, %42, %43, %44, %45, %46, %47, %48, %49, %50, %51, %52, %53, %54, %55, %56, %57, %58, %59, %60, %61, %62, %63}, da, db, p, 1, 1, 0, 1;\n}\n"
    : "+f"(d[0]), "+f"(d[1]), "+f"(d[2]), "+f"(d[3]), "+f"(d[4]), "+f"(d[5]), "+f"(d[6]), "+f"(d[7]), "+f"(d[8]), "+f"(d[9]), "+f"(d[10]), "+f"(d[11]), "+f"(d[12]), "+f"(d[13]), "+f"(d[14]), "+f"(d[15]), "+f"(d[16]), "+f"(d[17]), "+f"(d[18]), "+f"(d[19]), "+f"(d[20]), "+f"(d[21]), "+f"(d[22]), "+f"(d[23]), "+f"(d[24]), "+f"(d[25]), "+f"(d[26]), "+f"(d[27]), "+f"(d[28]), "+f"(d[29]), "+f"(d[30]), "+f"(d[31]), "+f"(d[32]), "+f"(d[33]), "+f"(d[34]), "+f"(d[35]), "+f"(d[36]), "+f"(d[37]), "+f"(d[38]), "+f"(d[39]), "+f"(d[40]), "+f"(d[41]), "+f"(d[42]), "+f"(d[43]), "+f"(d[44]), "+f"(d[45]), "+f"(d[46]), "+f"(d[47]), "+f"(d[48]), "+f"(d[49]), "+f"(d[50]), "+f"(d[51]), "+f"(d[52]), "+f"(d[53]), "+f"(d[54]), "+f"(d[55]), "+f"(d[56]), "+f"(d[57]), "+f"(d[58]), "+f"(d[59]), "+f"(d[60]), "+f"(d[61]), "+f"(d[62]), "+f"(d[63])
    : "r"(a), "r"(b), "n"(AHI), "n"(BHI));
}
template<uint32_t AHI, uint32_t BHI> __device__ __forceinline__ void wg_ss_z_n128(float* d, uint32_t a, uint32_t b) {
  asm volatile("{\n.reg .pred p;\n.reg .b64 da, db;\nsetp.ne.b32 p, 0, 0;\nmov.b64 da, {%64, %66};\nmov.b64 db, {%65, %67};\n"
    "wgmma.mma_async.sync.aligned.m64n128k16.f32.bf16.bf16 {%0, %1, %2, %3, %4, %5, %6, %7, %8, %9, %10, %11, %12, %13, %14, %15, %16, %17, %18, %19, %20, %21, %22, %23, %24, %25, %26, %27, %28, %29, %30, %31, %32, %33, %34, %35, %36, %37, %38, %39, %40, %41, %42, %43, %44, %45, %46, %47, %48, %49, %50, %51, %52, %53, %54, %55, %56, %57, %58, %59, %60, %61, %62, %63}, da, db, p, 1, 1, 0, 1;\n}\n"
    : "=f"(d[0]), "=f"(d[1]), "=f"(d[2]), "=f"(d[3]), "=f"(d[4]), "=f"(d[5]), "=f"(d[6]), "=f"(d[7]), "=f"(d[8]), "=f"(d[9]), "=f"(d[10]), "=f"(d[11]), "=f"(d[12]), "=f"(d[13]), "=f"(d[14]), "=f"(d[15]), "=f"(d[16]), "=f"(d[17]), "=f"(d[18]), "=f"(d[19]), "=f"(d[20]), "=f"(d[21]), "=f"(d[22]), "=f"(d[23]), "=f"(d[24]), "=f"(d[25]), "=f"(d[26]), "=f"(d[27]), "=f"(d[28]), "=f"(d[29]), "=f"(d[30]), "=f"(d[31]), "=f"(d[32]), "=f"(d[33]), "=f"(d[34]), "=f"(d[35]), "=f"(d[36]), "=f"(d[37]), "=f"(d[38]), "=f"(d[39]), "=f"(d[40]), "=f"(d[41]), "=f"(d[42]), "=f"(d[43]), "=f"(d[44]), "=f"(d[45]), "=f"(d[46]), "=f"(d[47]), "=f"(d[48]), "=f"(d[49]), "=f"(d[50]), "=f"(d[51]), "=f"(d[52]), "=f"(d[53]), "=f"(d[54]), "=f"(d[55]), "=f"(d[56]), "=f"(d[57]), "=f"(d[58]), "=f"(d[59]), "=f"(d[60]), "=f"(d[61]), "=f"(d[62]), "=f"(d[63])
    : "r"(a), "r"(b), "n"(AHI), "n"(BHI));
}
template<uint32_t AHI, uint32_t BHI> __device__ __forceinline__ void wg_ss_n160(float* d, uint32_t a, uint32_t b) {
  asm volatile("{\n.reg .pred p;\n.reg .b64 da, db;\nsetp.ne.b32 p, 1, 0;\nmov.b64 da, {%80, %82};\nmov.b64 db, {%81, %83};\n"
    "wgmma.mma_async.sync.aligned.m64n160k16.f32.bf16.bf16 {%0, %1, %2, %3, %4, %5, %6, %7, %8, %9, %10, %11, %12, %13, %14, %15, %16, %17, %18, %19, %20, %21, %22, %23, %24, %25, %26, %27, %28, %29, %30, %31, %32, %33, %34, %35, %36, %37, %38, %39, %40, %41, %42, %43, %44, %45, %46, %47, %48, %49, %50, %51, %52, %53, %54, %55, %56, %57, %58, %59, %60, %61, %62, %63, %64, %65, %66, %67, %68, %69, %70, %71, %72, %73, %74, %75, %76, %77, %78, %79}, da, db, p, 1, 1, 0, 1;\n}\n"
    : "+f"(d[0]), "+f"(d[1]), "+f"(d[2]), "+f"(d[3]), "+f"(d[4]), "+f"(d[5]), "+f"(d[6]), "+f"(d[7]), "+f"(d[8]), "+f"(d[9]), "+f"(d[10]), "+f"(d[11]), "+f"(d[12]), "+f"(d[13]), "+f"(d[14]), "+f"(d[15]), "+f"(d[16]), "+f"(d[17]), "+f"(d[18]), "+f"(d[19]), "+f"(d[20]), "+f"(d[21]), "+f"(d[22]), "+f"(d[23]), "+f"(d[24]), "+f"(d[25]), "+f"(d[26]), "+f"(d[27]), "+f"(d[28]), "+f"(d[29]), "+f"(d[30]), "+f"(d[31]), "+f"(d[32]), "+f"(d[33]), "+f"(d[34]), "+f"(d[35]), "+f"(d[36]), "+f"(d[37]), "+f"(d[38]), "+f"(d[39]), "+f"(d[40]), "+f"(d[41]), "+f"(d[42]), "+f"(d[43]), "+f"(d[44]), "+f"(d[45]), "+f"(d[46]), "+f"(d[47]), "+f"(d[48]), "+f"(d[49]), "+f"(d[50]), "+f"(d[51]), "+f"(d[52]), "+f"(d[53]), "+f"(d[54]), "+f"(d[55]), "+f"(d[56]), "+f"(d[57]), "+f"(d[58]), "+f"(d[59]), "+f"(d[60]), "+f"(d[61]), "+f"(d[62]), "+f"(d[63]), "+f"(d[64]), "+f"(d[65]), "+f"(d[66]), "+f"(d[67]), "+f"(d[68]), "+f"(d[69]), "+f"(d[70]), "+f"(d[71]), "+f"(d[72]), "+f"(d[73]), "+f"(d[74]), "+f"(d[75]), "+f"(d[76]), "+f"(d[77]), "+f"(d[78]), "+f"(d[79])
    : "r"(a), "r"(b), "n"(AHI), "n"(BHI));
}
template<uint32_t AHI, uint32_t BHI> __device__ __forceinline__ void wg_ss_z_n160(float* d, uint32_t a, uint32_t b) {
  asm volatile("{\n.reg .pred p;\n.reg .b64 da, db;\nsetp.ne.b32 p, 0, 0;\nmov.b64 da, {%80, %82};\nmov.b64 db, {%81, %83};\n"
    "wgmma.mma_async.sync.aligned.m64n160k16.f32.bf16.bf16 {%0, %1, %2, %3, %4, %5, %6, %7, %8, %9, %10, %11, %12, %13, %14, %15, %16, %17, %18, %19, %20, %21, %22, %23, %24, %25, %26, %27, %28, %29, %30, %31, %32, %33, %34, %35, %36, %37, %38, %39, %40, %41, %42, %43, %44, %45, %46, %47, %48, %49, %50, %51, %52, %53, %54, %55, %56, %57, %58, %59, %60, %61, %62, %63, %64, %65, %66, %67, %68, %69, %70, %71, %72, %73, %74, %75, %76, %77, %78, %79}, da, db, p, 1, 1, 0, 1;\n}\n"
    : "=f"(d[0]), "=f"(d[1]), "=f"(d[2]), "=f"(d[3]), "=f"(d[4]), "=f"(d[5]), "=f"(d[6]), "=f"(d[7]), "=f"(d[8]), "=f"(d[9]), "=f"(d[10]), "=f"(d[11]), "=f"(d[12]), "=f"(d[13]), "=f"(d[14]), "=f"(d[15]), "=f"(d[16]), "=f"(d[17]), "=f"(d[18]), "=f"(d[19]), "=f"(d[20]), "=f"(d[21]), "=f"(d[22]), "=f"(d[23]), "=f"(d[24]), "=f"(d[25]), "=f"(d[26]), "=f"(d[27]), "=f"(d[28]), "=f"(d[29]), "=f"(d[30]), "=f"(d[31]), "=f"(d[32]), "=f"(d[33]), "=f"(d[34]), "=f"(d[35]), "=f"(d[36]), "=f"(d[37]), "=f"(d[38]), "=f"(d[39]), "=f"(d[40]), "=f"(d[41]), "=f"(d[42]), "=f"(d[43]), "=f"(d[44]), "=f"(d[45]), "=f"(d[46]), "=f"(d[47]), "=f"(d[48]), "=f"(d[49]), "=f"(d[50]), "=f"(d[51]), "=f"(d[52]), "=f"(d[53]), "=f"(d[54]), "=f"(d[55]), "=f"(d[56]), "=f"(d[57]), "=f"(d[58]), "=f"(d[59]), "=f"(d[60]), "=f"(d[61]), "=f"(d[62]), "=f"(d[63]), "=f"(d[64]), "=f"(d[65]), "=f"(d[66]), "=f"(d[67]), "=f"(d[68]), "=f"(d[69]), "=f"(d[70]), "=f"(d[71]), "=f"(d[72]), "=f"(d[73]), "=f"(d[74]), "=f"(d[75]), "=f"(d[76]), "=f"(d[77]), "=f"(d[78]), "=f"(d[79])
    : "r"(a), "r"(b), "n"(AHI), "n"(BHI));
}
template<uint32_t BHI> __device__ __forceinline__ void wg_rs_n64(float* d, uint32_t a0, uint32_t a1, uint32_t a2, uint32_t a3, uint32_t b) {
  asm volatile("{\n.reg .pred p;\n.reg .b64 db;\nsetp.ne.b32 p, 1, 0;\nmov.b64 db, {%36, %37};\n"
    "wgmma.mma_async.sync.aligned.m64n64k16.f32.bf16.bf16 {%0, %1, %2, %3, %4, %5, %6, %7, %8, %9, %10, %11, %12, %13, %14, %15, %16, %17, %18, %19, %20, %21, %22, %23, %24, %25, %26, %27, %28, %29, %30, %31}, {%32, %33, %34, %35}, db, p, 1, 1, 0;\n}\n"
    : "+f"(d[0]), "+f"(d[1]), "+f"(d[2]), "+f"(d[3]), "+f"(d[4]), "+f"(d[5]), "+f"(d[6]), "+f"(d[7]), "+f"(d[8]), "+f"(d[9]), "+f"(d[10]), "+f"(d[11]), "+f"(d[12]), "+f"(d[13]), "+f"(d[14]), "+f"(d[15]), "+f"(d[16]), "+f"(d[17]), "+f"(d[18]), "+f"(d[19]), "+f"(d[20]), "+f"(d[21]), "+f"(d[22]), "+f"(d[23]), "+f"(d[24]), "+f"(d[25]), "+f"(d[26]), "+f"(d[27]), "+f"(d[28]), "+f"(d[29]), "+f"(d[30]), "+f"(d[31])
    : "r"(a0), "r"(a1), "r"(a2), "r"(a3), "r"(b), "n"(BHI));
}
template<uint32_t BHI> __device__ __forceinline__ void wg_rs_z_n64(float* d, uint32_t a0, uint32_t a1, uint32_t a2, uint32_t a3, uint32_t b) {
  asm volatile("{\n.reg .pred p;\n.reg .b64 db;\nsetp.ne.b32 p, 0, 0;\nmov.b64 db, {%36, %37};\n"
    "wgmma.mma_async.sync.aligned.m64n64k16.f32.bf16.bf16 {%0, %1, %2, %3, %4, %5, %6, %7, %8, %9, %10, %11, %12, %13, %14, %15, %16, %17, %18, %19, %20, %21, %22, %23, %24, %25, %26, %27, %28, %29, %30, %31}, {%32, %33, %34, %35}, db, p, 1, 1, 0;\n}\n"
    : "=f"(d[0]), "=f"(d[1]), "=f"(d[2]), "=f"(d[3]), "=f"(d[4]), "=f"(d[5]), "=f"(d[6]), "=f"(d[7]), "=f"(d[8]), "=f"(d[9]), "=f"(d[10]), "=f"(d[11]), "=f"(d[12]), "=f"(d[13]), "=f"(d[14]), "=f"(d[15]), "=f"(d[16]), "=f"(d[17]), "=f"(d[18]), "=f"(d[19]), "=f"(d[20]), "=f"(d[21]), "=f"(d[22]), "=f"(d[23]), "=f"(d[24]), "=f"(d[25]), "=f"(d[26]), "=f"(d[27]), "=f"(d[28]), "=f"(d[29]), "=f"(d[30]), "=f"(d[31])
    : "r"(a0), "r"(a1), "r"(a2), "r"(a3), "r"(b), "n"(BHI));
}
template<uint32_t BHI> __device__ __forceinline__ void wg_rs_n24(float* d, uint32_t a0, uint32_t a1, uint32_t a2, uint32_t a3, uint32_t b) {
  asm volatile("{\n.reg .pred p;\n.reg .b64 db;\nsetp.ne.b32 p, 1, 0;\nmov.b64 db, {%16, %17};\n"
    "wgmma.mma_async.sync.aligned.m64n24k16.f32.bf16.bf16 {%0, %1, %2, %3, %4, %5, %6, %7, %8, %9, %10, %11}, {%12, %13, %14, %15}, db, p, 1, 1, 1;\n}\n"
    : "+f"(d[0]), "+f"(d[1]), "+f"(d[2]), "+f"(d[3]), "+f"(d[4]), "+f"(d[5]), "+f"(d[6]), "+f"(d[7]), "+f"(d[8]), "+f"(d[9]), "+f"(d[10]), "+f"(d[11])
    : "r"(a0), "r"(a1), "r"(a2), "r"(a3), "r"(b), "n"(BHI));
}
template<uint32_t BHI> __device__ __forceinline__ void wg_rs_z_n24(float* d, uint32_t a0, uint32_t a1, uint32_t a2, uint32_t a3, uint32_t b) {
  asm volatile("{\n.reg .pred p;\n.reg .b64 db;\nsetp.ne.b32 p, 0, 0;\nmov.b64 db, {%16, %17};\n"
    "wgmma.mma_async.sync.aligned.m64n24k16.f32.bf16.bf16 {%0, %1, %2, %3, %4, %5, %6, %7, %8, %9, %10, %11}, {%12, %13, %14, %15}, db, p, 1, 1, 1;\n}\n"
    : "=f"(d[0]), "=f"(d[1]), "=f"(d[2]), "=f"(d[3]), "=f"(d[4]), "=f"(d[5]), "=f"(d[6]), "=f"(d[7]), "=f"(d[8]), "=f"(d[9]), "=f"(d[10]), "=f"(d[11])
    : "r"(a0), "r"(a1), "r"(a2), "r"(a3), "r"(b), "n"(BHI));
}

__device__ __forceinline__ void wg_fence() { asm volatile("wgmma.fence.sync.aligned;" ::: "memory"); }
__device__ __forceinline__ void wg_commit() { asm volatile("wgmma.commit_group.sync.aligned;" ::: "memory"); }
template <int N> __device__ __forceinline__ void wg_wait() { asm volatile("wgmma.wait_group.sync.aligned %0;" ::"n"(N) : "memory"); }
template <int R> __device__ __forceinline__ void pin(float* d) {
#pragma unroll
  for (int i = 0; i < R; i++) asm volatile("" : "+f"(d[i])::"memory");
}
template <int R> __device__ __forceinline__ void pin(uint32_t* d) {
#pragma unroll
  for (int i = 0; i < R; i++) asm volatile("" : "+r"(d[i])::"memory");
}
__device__ __forceinline__ float ex2(float x) { float y; asm("ex2.approx.ftz.f32 %0, %1;" : "=f"(y) : "f"(x)); return y; }
__device__ __forceinline__ float tanh_fast(float x) { float y; asm("tanh.approx.f32 %0, %1;" : "=f"(y) : "f"(x)); return y; }
__device__ __forceinline__ uint32_t pack(float lo, float hi) { uint32_t r; asm("cvt.rn.bf16x2.f32 %0, %1, %2;" : "=r"(r) : "f"(hi), "f"(lo)); return r; }
__device__ __forceinline__ float bf_lo(uint32_t v) { return __uint_as_float(v << 16); }
__device__ __forceinline__ float bf_hi(uint32_t v) { return __uint_as_float(v & 0xffff0000u); }
__device__ __forceinline__ float bf_round(float x) { return bf_lo(pack(x, 0.f)); }

__device__ __forceinline__ void mbar_init(uint32_t bar, uint32_t cnt) { asm volatile("mbarrier.init.shared::cta.b64 [%0], %1;" ::"r"(bar), "r"(cnt) : "memory"); }
__device__ __forceinline__ void mbar_expect(uint32_t bar, uint32_t bytes) { asm volatile("mbarrier.arrive.expect_tx.shared::cta.b64 _, [%0], %1;" ::"r"(bar), "r"(bytes) : "memory"); }
__device__ __forceinline__ void mbar_arrive(uint32_t bar) { asm volatile("mbarrier.arrive.shared::cta.b64 _, [%0];" ::"r"(bar) : "memory"); }
__device__ __forceinline__ void mbar_wait(uint32_t bar, uint32_t parity) {
  asm volatile(
      "{\n.reg .pred p;\n.reg .u32 c;\n"
      "mbarrier.try_wait.parity.shared::cta.b64 p, [%0], %1;\n"
      "@p bra.uni DONE;\n"
      "mov.u32 c, 0;\n"
      "LOOP:\n"
      "mbarrier.try_wait.parity.shared::cta.b64 p, [%0], %1;\n"
      "@p bra.uni DONE;\n"
      "add.u32 c, c, 1;\n"
      "setp.lt.u32 p, c, 0x4000000;\n"
      "@p bra.uni LOOP;\n"
      "trap;\n"
      "DONE:\n}\n" ::"r"(bar), "r"(parity) : "memory");
}
__device__ __forceinline__ uint32_t mbar_test(uint32_t bar, uint32_t parity) {
  uint32_t ok;
  asm volatile("{\n.reg .pred p;\nmbarrier.test_wait.parity.shared::cta.b64 p, [%1], %2;\nselp.u32 %0, 1, 0, p;\n}\n" : "=r"(ok) : "r"(bar), "r"(parity) : "memory");
  return ok;
}
__device__ __forceinline__ void mbar_arrive_if(uint32_t bar, uint32_t cond) {
  asm volatile("{\n.reg .pred p;\nsetp.ne.u32 p, %1, 0;\n@p mbarrier.arrive.shared::cta.b64 _, [%0];\n}\n" ::"r"(bar), "r"(cond) : "memory");
}
__device__ __forceinline__ uint32_t bsub2(uint32_t a, uint32_t b) { uint32_t d; asm("sub.rn.bf16x2 %0, %1, %2;" : "=r"(d) : "r"(a), "r"(b)); return d; }
__device__ __forceinline__ uint32_t bscale2(uint32_t d, uint32_t hi, uint32_t lo) {
  uint32_t t, r;
  asm("mul.rn.bf16x2 %0, %1, %2;" : "=r"(t) : "r"(d), "r"(lo));
  asm("fma.rn.bf16x2 %0, %1, %2, %3;" : "=r"(r) : "r"(d), "r"(hi), "r"(t));
  return r;
}
__device__ __forceinline__ void flag_wait(const uint32_t* f, uint32_t target) {
  asm volatile(
      "{\n.reg .pred p;\n.reg .u32 c, v;\n"
      "mov.u32 c, 0;\n"
      "LOOP:\n"
      "ld.acquire.gpu.global.u32 v, [%0];\n"
      "setp.ge.u32 p, v, %1;\n"
      "@p bra DONE;\n"
      "add.u32 c, c, 1;\n"
      "setp.lt.u32 p, c, 0x1000000;\n"
      "@p bra LOOP;\n"
      "trap;\n"
      "DONE:\n}\n" ::"l"(f), "r"(target) : "memory");
}
__device__ __forceinline__ uint32_t flag_wait_v(const uint32_t* f, uint32_t target) {
  uint32_t v;
  asm volatile(
      "{\n.reg .pred p;\n.reg .u32 c;\n"
      "mov.u32 c, 0;\n"
      "LOOP:\n"
      "ld.acquire.gpu.global.u32 %0, [%1];\n"
      "setp.ge.u32 p, %0, %2;\n"
      "@p bra DONE;\n"
      "add.u32 c, c, 1;\n"
      "setp.lt.u32 p, c, 0x1000000;\n"
      "@p bra LOOP;\n"
      "trap;\n"
      "DONE:\n}\n" : "=&r"(v) : "l"(f), "r"(target) : "memory");
  return v;
}
__device__ __forceinline__ float rcp_fast(float x) { float y; asm("rcp.approx.ftz.f32 %0, %1;" : "=f"(y) : "f"(x)); return y; }
__device__ __forceinline__ void ldsm4(uint32_t* v, uint32_t addr) {
  asm volatile("ldmatrix.sync.aligned.m8n8.x4.shared.b16 {%0,%1,%2,%3}, [%4];" : "=r"(v[0]), "=r"(v[1]), "=r"(v[2]), "=r"(v[3]) : "r"(addr) : "memory");
}
__device__ __forceinline__ void stsm4(uint32_t addr, uint32_t a, uint32_t b, uint32_t c, uint32_t d) {
  asm volatile("stmatrix.sync.aligned.m8n8.x4.shared.b16 [%0], {%1,%2,%3,%4};" ::"r"(addr), "r"(a), "r"(b), "r"(c), "r"(d) : "memory");
}
__device__ __forceinline__ void flag_add(uint32_t* f) { asm volatile("red.relaxed.gpu.global.add.u32 [%0], 1;" ::"l"(f) : "memory"); }
__device__ __forceinline__ void fence_gpu() { asm volatile("fence.acq_rel.gpu;" ::: "memory"); }
__device__ __forceinline__ void fence_async() { asm volatile("fence.proxy.async;" ::: "memory"); }
__device__ __forceinline__ void tma2d(uint32_t dst, const CUtensorMap* tm, uint32_t bar, int c0, int c1) {
  asm volatile("cp.async.bulk.tensor.2d.shared::cluster.global.mbarrier::complete_tx::bytes [%0], [%1, {%3, %4}], [%2];" ::"r"(dst), "l"(tm), "r"(bar), "r"(c0), "r"(c1) : "memory");
}
__device__ __forceinline__ void tma5d(uint32_t dst, const CUtensorMap* tm, uint32_t bar, int c0, int c4) {
  asm volatile("cp.async.bulk.tensor.5d.shared::cluster.global.mbarrier::complete_tx::bytes [%0], [%1, {%3, %5, %5, %5, %4}], [%2];" ::"r"(dst), "l"(tm), "r"(bar), "r"(c0), "r"(c4), "r"(0) : "memory");
}
__device__ __forceinline__ void tma3d(uint32_t dst, const CUtensorMap* tm, uint32_t bar, int c0, int c2) {
  asm volatile("cp.async.bulk.tensor.3d.shared::cluster.global.mbarrier::complete_tx::bytes [%0], [%1, {%3, %5, %4}], [%2];" ::"r"(dst), "l"(tm), "r"(bar), "r"(c0), "r"(c2), "r"(0) : "memory");
}
__device__ __forceinline__ void bulk_g2s(uint32_t dst, const void* src, uint32_t bytes, uint32_t bar) {
  asm volatile("cp.async.bulk.shared::cluster.global.mbarrier::complete_tx::bytes [%0], [%1], %2, [%3];" ::"r"(dst), "l"(src), "r"(bytes), "r"(bar) : "memory");
}
__device__ __forceinline__ void pf3d(const CUtensorMap* tm, int c0, int c2) {
  asm volatile("cp.async.bulk.prefetch.tensor.3d.L2.global [%0, {%1, %3, %2}];" ::"l"(tm), "r"(c0), "r"(c2), "r"(0) : "memory");
}
__device__ __forceinline__ void pf2d(const CUtensorMap* tm, int c0, int c1) {
  asm volatile("cp.async.bulk.prefetch.tensor.2d.L2.global [%0, {%1, %2}];" ::"l"(tm), "r"(c0), "r"(c1) : "memory");
}
__device__ __forceinline__ void pf5d(const CUtensorMap* tm, int c0, int c4) {
  asm volatile("cp.async.bulk.prefetch.tensor.5d.L2.global [%0, {%1, %3, %3, %3, %2}];" ::"l"(tm), "r"(c0), "r"(c4), "r"(0) : "memory");
}

struct Att {
  float s[32];
  float o[12];
  uint32_t p[16];
  uint32_t q[8];
};

__device__ __forceinline__ void attn_slow_rows(int cta, int j, int hp, int lrow_base, int tid_base) {
  const int lane = threadIdx.x & 31;
  const uint32_t* kv = g_KV + (size_t)(4 * j + hp) * SEQ * 20;
#pragma unroll 1
  for (int r = 0; r < 16; r++) {
    float q[18], acc[18];
#pragma unroll
    for (int v = 0; v < 9; v++) {
      uint32_t u = g_Q[(((cta * 4 + hp) * 2 + (v >> 3)) * 256 + tid_base + (r & 7) * 4 + ((v + hp) & 3)) * 4 + 2 * ((v >> 2) & 1) + (r >> 3)];
      q[2 * v] = bf_lo(u); q[2 * v + 1] = bf_hi(u);
      acc[2 * v] = 0.f; acc[2 * v + 1] = 0.f;
    }
    float mx = -INFINITY, l = 0.f;
#pragma unroll 1
    for (int key = lane; key < SEQ; key += 32) {
      const uint32_t* kr = kv + (key >> 3) * 160 + (key & 7) * 4;
      float s = 0.f;
#pragma unroll
      for (int v = 0; v < 9; v++) {
        uint32_t u = kr[(v >> 2) * 32 + ((v + hp) & 3)];
        s = fmaf(q[2 * v], bf_lo(u), s); s = fmaf(q[2 * v + 1], bf_hi(u), s);
      }
      float mn = fmaxf(mx, s), c = exp2f(mx - mn), p = exp2f(s - mn);
      mx = mn; l = l * c + p;
#pragma unroll
      for (int v = 0; v < 9; v++) {
        uint32_t u = v < 8 ? kr[(3 + (v >> 2)) * 32 + (v & 3)] : kr[2 * 32 + ((hp + 2) & 3)];
        acc[2 * v] = fmaf(p, bf_lo(u), acc[2 * v] * c); acc[2 * v + 1] = fmaf(p, bf_hi(u), acc[2 * v + 1] * c);
      }
    }
    float gm = mx;
#pragma unroll
    for (int d = 16; d; d >>= 1) gm = fmaxf(gm, __shfl_xor_sync(0xffffffffu, gm, d));
    float c = exp2f(mx - gm);
    l *= c;
#pragma unroll
    for (int d = 16; d; d >>= 1) l += __shfl_xor_sync(0xffffffffu, l, d);
    uint32_t* orow = g_O + cta * 9 * 512 + (lrow_base + r) * 4;
#pragma unroll
    for (int v = 0; v < 9; v++) {
      float a = acc[2 * v] * c, b = acc[2 * v + 1] * c;
#pragma unroll
      for (int d = 16; d; d >>= 1) { a += __shfl_xor_sync(0xffffffffu, a, d); b += __shfl_xor_sync(0xffffffffu, b, d); }
      if (lane == 0) orow[v < 8 ? (2 * hp + (v >> 2)) * 512 + (v & 3) : 8 * 512 + hp] = pack(2.f * (a / l), 2.f * (b / l));
    }
  }
}

__device__ __forceinline__ bool o_epilogue(float* o, uint32_t& x0, uint32_t& x1, int hp, uint32_t* odst, int lane) {
  const int src = (lane & ~3) | ((hp + 1) & 3);
  float l0 = __shfl_sync(0xffffffffu, o[0], src), l1 = __shfl_sync(0xffffffffu, o[2], src);
  float sa = 0.f;
#pragma unroll
  for (int i = 0; i < 12; i++) sa += fabsf(o[i]);
  bool ok = (l0 <= 1.329228e36f) && (l1 <= 1.329228e36f) && (l0 > 0.f) && (l1 > 0.f) && (sa <= 3.0e38f);
  float i0 = 2.f * rcp_fast(l0), i1 = 2.f * rcp_fast(l1);
  uint32_t* d = odst + hp * 1024;
  d[0] = pack(o[4] * i0, o[5] * i0);
  d[32] = pack(o[6] * i1, o[7] * i1);
  d[512] = pack(o[8] * i0, o[9] * i0);
  d[544] = pack(o[10] * i1, o[11] * i1);
  if ((lane & 3) == ((hp + 2) & 3)) { x0 = pack(o[0] * i0, o[1] * i0); x1 = pack(o[2] * i1, o[3] * i1); }
  return __any_sync(0xffffffffu, !ok);
}

__device__ __forceinline__ void issue_pv(Att& a, uint32_t kdesc) {
  const uint32_t vdesc = kdesc + 192 + (LO_V - LO_K);
#pragma unroll
  for (int k = 0; k < 4; k++) wg_rs_n24<HI_V>(a.o, a.p[4 * k], a.p[4 * k + 1], a.p[4 * k + 2], a.p[4 * k + 3], vdesc + k * 48);
}
__device__ __forceinline__ void issue_att(Att& a, uint32_t kdesc) {
  issue_pv(a, kdesc);
  wg_rs_z_n64<HI_K>(a.s, a.q[0], a.q[1], a.q[2], a.q[3], kdesc);
  wg_rs_n64<HI_K>(a.s, a.q[4], a.q[5], a.q[6], a.q[7], kdesc + 16);
}
__device__ __forceinline__ void softmax_tile(Att& a) {
#pragma unroll
  for (int i = 0; i < 16; i++) a.p[i] = pack(ex2(a.s[2 * i]), ex2(a.s[2 * i + 1]));
  pin<16>(a.p);
}
__device__ __forceinline__ void first_tile(Att& a, int hp, int lane) {
  float m0 = fmaxf(a.s[0], a.s[1]), m1 = fmaxf(a.s[2], a.s[3]);
#pragma unroll
  for (int i = 4; i < 32; i += 4) { m0 = fmaxf(m0, fmaxf(a.s[i], a.s[i + 1])); m1 = fmaxf(m1, fmaxf(a.s[i + 2], a.s[i + 3])); }
  m0 = fmaxf(m0, __shfl_xor_sync(0xffffffffu, m0, 1)); m1 = fmaxf(m1, __shfl_xor_sync(0xffffffffu, m1, 1));
  m0 = fmaxf(m0, __shfl_xor_sync(0xffffffffu, m0, 2)); m1 = fmaxf(m1, __shfl_xor_sync(0xffffffffu, m1, 2));
  float n0 = -(m0 + MOFF), n1 = -(m1 + MOFF);
  float h0 = bf_round(n0), h1 = bf_round(n1);
  uint32_t e0 = pack(h0, n0 - h0), e1 = pack(h1, n1 - h1);
  n0 = h0 + bf_hi(e0); n1 = h1 + bf_hi(e1);
  if ((lane & 3) == ((hp + 1) & 3)) { a.q[4] = e0; a.q[5] = e1; }
#pragma unroll
  for (int i = 0; i < 32; i += 4) { a.s[i] += n0; a.s[i + 1] += n0; a.s[i + 2] += n1; a.s[i + 3] += n1; }
#pragma unroll
  for (int i = 0; i < 12; i++) a.o[i] = 0.f;
  pin<12>(a.o); pin<8>(a.q);
}
__device__ __forceinline__ void load_q(Att& a, int cta, int hp, int tid) {
  const uint4* src = reinterpret_cast<const uint4*>(g_Q) + (cta * 4 + hp) * 512 + tid;
  const uint4 u = __ldcg(src), v = __ldcg(src + 256);
  a.q[0] = u.x; a.q[1] = u.y; a.q[2] = u.z; a.q[3] = u.w; a.q[4] = v.x; a.q[5] = v.y; a.q[6] = v.z; a.q[7] = v.w;
}
__device__ __forceinline__ void h_epilogue(float* acc, __nv_bfloat16* dst) {
#pragma unroll
  for (int b = 0; b < 2; b++) {
    uint32_t w0[4], w1[4];
#pragma unroll
    for (int i = 0; i < 4; i++) {
      float h[4];
#pragma unroll
      for (int e = 0; e < 4; e++) {
        float g = acc[(4 * b + i) * 4 + e], u = acc[32 + (4 * b + i) * 4 + e];
        h[e] = fmaf(tanh_fast(0.5f * g), u, u);
      }
      w0[i] = pack(h[0], h[1]); w1[i] = pack(h[2], h[3]);
    }
    *reinterpret_cast<uint4*>(dst + 32 * b) = make_uint4(w0[0], w0[1], w0[2], w0[3]);
    *reinterpret_cast<uint4*>(dst + 32 * b + 8 * FF) = make_uint4(w1[0], w1[1], w1[2], w1[3]);
  }
}

__host__ __device__ constexpr int B0(int q) { return q == 0 ? 0 : q == 1 ? 10 : q == 2 ? 18 : q == 3 ? 28 : 36; }
template <int D> __device__ __forceinline__ void send_part(const float* acc, uint4* pw, uint32_t tag) {
  constexpr int NV = (B0(D + 1) - B0(D)) / 2, OFF = 4 * B0(D);
#pragma unroll
  for (int i = 0; i < NV; i++) {
    const float* v = acc + OFF + 8 * i;
    asm volatile("st.relaxed.gpu.global.v4.b32 [%0], {%1,%2,%3,%4};" ::"l"(pw + (D * 5 + i) * 256), "r"((pack(v[0], v[1]) & ~1u) | tag),
                 "r"((pack(v[2], v[3]) & ~1u) | tag), "r"((pack(v[4], v[5]) & ~1u) | tag), "r"((pack(v[6], v[7]) & ~1u) | tag) : "memory");
  }
}
template <int Q> __device__ __forceinline__ void final_exchange(const float* acc, const uint32_t* xr, uint32_t* orow, int m, int hh, int tid, uint32_t tag) {
  constexpr int NB = B0(Q + 1) - B0(Q), BQ = B0(Q);
  uint4* pw = g_P + (size_t)((m * 2 + hh) * 16 + Q * 4) * 5 * 256 + tid;
  send_part<(Q + 1) & 3>(acc, pw, tag);
  send_part<(Q + 2) & 3>(acc, pw, tag);
  send_part<(Q + 3) & 3>(acc, pw, tag);
  uint32_t xv[2 * NB];
#pragma unroll
  for (int i = 0; i < NB; i++) { xv[2 * i] = __ldg(xr + 4 * (BQ + i)); xv[2 * i + 1] = __ldg(xr + 4 * (BQ + i) + 8 * (DM / 2)); }
  const uint4* pr = g_P + (size_t)((m * 2 + hh) * 16 + Q) * 5 * 256 + tid;
  uint32_t v[3][2 * NB];
  uint32_t tries = 0;
  while (true) {
    uint32_t all = 1, any = 0;
#pragma unroll
    for (int d = 0; d < 3; d++)
#pragma unroll
      for (int i = 0; i < NB / 2; i++)
        asm volatile("ld.relaxed.gpu.global.v4.b32 {%0,%1,%2,%3}, [%4];" : "=r"(v[d][4 * i]), "=r"(v[d][4 * i + 1]), "=r"(v[d][4 * i + 2]), "=r"(v[d][4 * i + 3])
                     : "l"(pr + (((Q + 3 - d) & 3) * 20 + i) * 256) : "memory");
#pragma unroll
    for (int d = 0; d < 3; d++)
#pragma unroll
      for (int i = 0; i < 2 * NB; i++) { all &= v[d][i]; any |= v[d][i]; }
    if (__all_sync(0xffffffffu, ((tag ? all : ~any) & 1) != 0)) break;
    if (++tries > 0x100000u) asm volatile("trap;");
  }
  uint32_t r[2 * NB];
#pragma unroll
  for (int i = 0; i < 2 * NB; i++) {
    const float lo = acc[4 * BQ + 2 * i] + ((bf_lo(v[0][i]) + bf_lo(v[1][i])) + bf_lo(v[2][i]));
    const float hi = acc[4 * BQ + 2 * i + 1] + ((bf_hi(v[0][i]) + bf_hi(v[1][i])) + bf_hi(v[2][i]));
    r[i] = pack(fmaf(lo, 0.5f, bf_lo(xv[i])), fmaf(hi, 0.5f, bf_hi(xv[i])));
  }
  const bool odd = tid & 1;
  uint2* o2 = reinterpret_cast<uint2*>(orow + 4 * BQ + (odd ? 3 : 0));
#pragma unroll
  for (int i = 0; i < NB / 2; i++)
#pragma unroll
    for (int rh = 0; rh < 2; rh++) {
      const uint32_t A = r[4 * i + rh], B = r[4 * i + 2 + rh];
      const uint32_t y = __shfl_xor_sync(0xffffffffu, odd ? A : B, 1);
      o2[4 * i + rh * 8 * (DM / 4)] = odd ? make_uint2(y, B) : make_uint2(A, y);
    }
}

__global__ void __launch_bounds__(384, 1) fused_kernel(const __grid_constant__ Params prm) {
  extern __shared__ __align__(1024) uint8_t smem[];
  const uint32_t sb = (uint32_t)__cvta_generic_to_shared(smem);
  const uint32_t bar = sb + SM_BAR;
  const int m = blockIdx.x & 15, j = blockIdx.x >> 4;
  const int cta = m * 8 + j;
  const int wr = __shfl_sync(0xffffffffu, (int)(threadIdx.x >> 5), 0);
  const int wg = wr >> 2;
  const int lane = threadIdx.x & 31;
  STAMP(0);
  if (wr == 8) {
    if (lane == 0) {
#pragma unroll
      for (int c = 0; c < 9; c++) mbar_init(bar + 8 * (B_X + c), 1);
      asm volatile("fence.proxy.async.shared::cta;" ::: "memory");
    }
    __syncwarp();
    asm volatile("bar.arrive 3, 384;" ::: "memory");
    if (lane < 9) {
      mbar_expect(bar + 8 * (B_X + lane), 16384);
      tma2d(sb + SM_XN + lane * 16384, &prm.xm, bar + 8 * (B_X + lane), 64 * lane, 128 * m);
    }
    __syncwarp();
    asm volatile("bar.sync 4, 64;" ::: "memory");
  } else {
    if (threadIdx.x == 288) {
      if (sb & 1023) asm volatile("trap;");
#pragma unroll
      for (int i = 0; i < 3; i++) { mbar_init(bar + 8 * (B_QF + i), 1); mbar_init(bar + 8 * (B_QE + i), 8); mbar_init(bar + 8 * (B_GF + i), 1); mbar_init(bar + 8 * (B_GE + i), 8); mbar_init(bar + 8 * (B_KF + i), 1); mbar_init(bar + 8 * (B_KE + i), 8); }
#pragma unroll
      for (int i = 0; i < 5; i++) { mbar_init(bar + 8 * (B_BF + i), 1); mbar_init(bar + 8 * (B_BE + i), 8); }
      mbar_init(bar + 8 * B_SKV, 8); mbar_init(bar + 8 * B_SH, 8); mbar_init(bar + 8 * B_SO1, 8); mbar_init(bar + 8 * B_SO2, 8); mbar_init(bar + 8 * B_OL, 1);
      mbar_init(bar + 8 * B_NR, 4); mbar_init(bar + 8 * (B_NR + 1), 4);
      asm volatile("fence.proxy.async.shared::cta;" ::: "memory");
    }
    if (wr == 11 && lane < 6 && m < 9) pf2d((lane & 1) ? &prm.wqkv8 : &prm.wqkv64, 576 * (lane >> 1) + 72 * j + 64 * (lane & 1), 64 * m);
    __syncwarp();
    if (wr == 9) asm volatile("bar.arrive 4, 64;" ::: "memory");
    asm volatile("bar.sync 3, 384;" ::: "memory");
  }

  if (wg == 2) {
    asm volatile("setmaxnreg.dec.sync.aligned.u32 24;");
    const int pw = wr & 3;
    if (lane == 0) {
      if (pw == 0) {
#pragma unroll 1
        for (int kb = 0; kb < 9; kb++) {
          const int s = kb % 3;
          if (kb >= 3) mbar_wait(bar + 8 * (B_QE + s), (kb / 3 - 1) & 1);
          const uint32_t fb = bar + 8 * (B_QF + s), dst = sb + SM_RING + s * QST;
          mbar_expect(fb, QST);
#pragma unroll
          for (int p = 0; p < 3; p++) {
            tma2d(dst + p * 8192, &prm.wqkv64, fb, 576 * p + 72 * j, 64 * kb);
            tma2d(dst + 24576 + p * 1024, &prm.wqkv8, fb, 576 * p + 72 * j + 64, 64 * kb);
          }
        }
        int col = 576 * j, kr = 0, slot = 0, ph = 1;
#pragma unroll 1
        for (int s = 0; s < 108; s++) {
          if (s >= 5) mbar_wait(bar + 8 * (B_BE + slot), ph);
          else if (!(s & 1)) mbar_wait(bar + 8 * (B_QE + (s >> 1)), 0);
          const uint32_t fb = bar + 8 * (B_BF + slot), dst = sb + SM_RING + slot * BST;
          mbar_expect(fb, BST);
          tma2d(dst, &prm.wg, fb, col, kr);
          tma2d(dst + 6144, &prm.wu, fb, col, kr);
          if ((kr += 48) == 576) { kr = 0; col += 64; }
          if (++slot == 5) { slot = 0; ph ^= 1; }
        }
        mbar_arrive(bar + 8 * (B_BF + 3));
        const int hh = j & 1;
        uint32_t seen = 0;
#pragma unroll 1
        for (int b = 0; b < 20; b++) {
          const int st = b % 3;
          if (b >= 3) mbar_wait(bar + 8 * (B_GE + st), (b / 3 - 1) & 1);
          else if (b == 1) mbar_wait(bar + 8 * (B_BE + 0), 1);
          else if (b == 2) mbar_wait(bar + 8 * (B_BE + 2), 1);
          const uint32_t fb = bar + 8 * (B_GF + st), dst = sb + st * G2ST;
          if (b == 0) STAMPW(16);
          if (b < 18) {
            mbar_expect(fb, G2ST);
            const int own = (b < 8 || b == 16), tile = b < 16 ? (b & 7) : 8;
            const int jj = own ? j : (j ^ 1);
            const int kc = 576 * jj + 64 * tile;
            if (b == 8 || b >= 16) seen = 0;
            if (seen <= tile) { seen = flag_wait_v(FLAG_H(m * 8 + jj), tile + 1); fence_async(); }
            tma2d(dst, &prm.h, fb, kc, 128 * m);
#pragma unroll
            for (int a = 0; a < 5; a++) tma5d(dst + 16384 + a * 8192, &prm.wd[hh], fb, 64 * a, kc >> 5);
          } else {
            mbar_expect(fb, b == 18 ? 53248 : 63488);
#pragma unroll
            for (int a = 0; a < 5; a++) tma3d(dst + 16384 + a * 8192, &prm.wo[hh], fb, 64 * a, 4 * ((j & 6) + b - 18));
            if (b == 19) {
#pragma unroll
              for (int a = 0; a < 5; a++) tma3d(sb + SM_W16 + a * 2048, &prm.wo16[hh], fb, 64 * a, 4 * (j & 6));
            }
            const int src = (cta & ~1) + b - 18;
            flag_wait(FLAG_O(src), 1);
            fence_async();
            bulk_g2s(dst + (b - 18) * 4096, g_O + src * 9 * 512 + (b - 18) * 1024, 12288, fb);
          }
          if (b == 0) STAMPW(17);
        }
      } else if (pw == 1) {
        flag_wait(FLAG_KV(j), 16);
        fence_async();
        STAMPW(18);
        int slot = 0, ph = 1, vrow = 0;
        const int hx = (j & 1) * 3;
#pragma unroll 1
        for (int u = 0; u <= 128; u++) {
          if (u >= 3) mbar_wait(bar + 8 * (B_KE + slot), ph);
          const uint32_t fb = bar + 8 * (B_KF + slot), dst = sb + SM_KV + slot * KVST;
          const int krow = (4 * j + ((u >> 5) ^ hx)) * 256 + ((u + 2 * m) & 31) * 8;
          if (u == 0) vrow = krow;
          mbar_expect(fb, u < 128 ? KVST : KVST / 2);
          if (u < 128) tma2d(dst, &prm.kv, fb, 0, krow);
          tma2d(dst + 3072, &prm.kv, fb, 128, vrow);
          vrow = krow;
          if (++slot == 3) { slot = 0; ph ^= 1; }
        }
        mbar_expect(bar + 8 * B_OL, 12288);
#pragma unroll 1
        for (int e = 0; e < 2; e++) {
          const int r = (cta & 1) ^ e;
          const uint32_t* src = g_O + ((cta & ~1) + r) * 9 * 512;
          flag_wait(FLAG_O((cta & ~1) + r), 2);
          fence_async();
          bulk_g2s(sb + r * G2ST + (r ? 0 : 12288), src + (r ? 0 : 3072), 4096, bar + 8 * B_OL);
          bulk_g2s(sb + SM_OL + r * 2048, src + 4096, 2048, bar + 8 * B_OL);
        }
        STAMPW(19);
      } else if (pw == 2) {
        mbar_wait(bar + 8 * B_SKV, 0);
        STAMPW(22);
        fence_gpu(); flag_add(FLAG_KV(j));
        STAMPW(20);
#pragma unroll 1
        for (int t = 0; t < 9; t++) { mbar_wait(bar + 8 * B_SH, t & 1); fence_gpu(); flag_add(FLAG_H(cta)); }
        mbar_wait(bar + 8 * B_SO1, 0);
        fence_gpu(); flag_add(FLAG_O(cta));
        mbar_wait(bar + 8 * B_SO2, 0);
        fence_gpu(); flag_add(FLAG_O(cta));
        STAMPW(21);
      } else {
        mbar_wait(bar + 8 * (B_X + 8), 0);
#pragma unroll 1
        for (int b = m; b < 216; b += 16) {
          const int s = b >> 1;
          pf2d((b & 1) ? &prm.wu : &prm.wg, 576 * j + 64 * (s / 12), 48 * (s % 12));
        }
        mbar_wait(bar + 8 * B_SH, 0);
#pragma unroll 1
        for (int b = m; b < 90; b += 16) pf5d(&prm.wd[j & 1], 64 * (b % 5), 36 * (j >> 1) + 2 * (b / 5));
        if (m < 10) pf3d(&prm.wo[j & 1], 64 * (m % 5), 4 * ((j & 6) + m / 5));
        else if (m < 15) pf3d(&prm.wo16[j & 1], 64 * (m % 5), 4 * (j & 6));
      }
    }
  } else {
    const int tid = threadIdx.x;
    const int t = lane & 3;
    const int row0 = 128 * m + 16 * wr + (lane >> 2);
    const uint32_t l0 = lane == 0;
    const uint32_t adesc = (((sb + SM_XN + wg * 8192) & 0x3FFFF) >> 4) | LO_A;
    const uint32_t bdesc = (((sb + SM_RING) & 0x3FFFF) >> 4) | LO_B48;
    const uint32_t kdesc0 = (((sb + SM_KV) & 0x3FFFF) >> 4) | LO_K;
    const int hx = (j & 1) * 3;
    float accA[64], accB[64];
    Att a;
    uint32_t badmask = 0;
#define AOFF(K) ((K) * 2 + ((K) >> 2) * 1016)
#define G1_ISSUE(ACC, I) _Pragma("unroll") for (int k = 0; k < 3; k++) wg_ss_n128<HI_SW128, HI_SW128>(ACC, adesc + AOFF(3 * (I) + k), bdesc + bslot * 768 + k * 128);
#define G1_ISSUE_Z(ACC)                                                                                        \
  wg_ss_z_n128<HI_SW128, HI_SW128>(ACC, adesc, bdesc + bslot * 768);                                           \
  _Pragma("unroll") for (int k = 1; k < 3; k++) wg_ss_n128<HI_SW128, HI_SW128>(ACC, adesc + k * 2, bdesc + bslot * 768 + k * 128);
    uint32_t bslot = 0, bph = 0, bprev = 0;
#define B_ADVANCE() { bprev = bslot; if (++bslot == 5) { bslot = 0; bph ^= 1; } }
    {
      const int lr = wr * 16 + (lane & 15);
      uint32_t ra[4];
#pragma unroll
      for (int k = 0; k < 4; k++) ra[k] = sb + SM_XN + lr * 128 + (((2 * k + (lane >> 4)) ^ (lr & 7)) << 4);
      float pv0 = 0.f, pv1 = 0.f, s0 = 0.f, s1 = 0.f, s2 = 0.f, s3 = 0.f, q0 = 0.f, q1 = 0.f, q2 = 0.f, q3 = 0.f;
#pragma unroll 1
      for (int c = 0; c < 9; c++) {
        mbar_wait(bar + 8 * (B_X + c), 0);
        uint32_t v[4][4];
#pragma unroll
        for (int k = 0; k < 4; k++) ldsm4(v[k], ra[k] + c * 16384);
        if (c == 0) { pv0 = __shfl_sync(0xffffffffu, bf_lo(v[0][0]), lane & ~3); pv1 = __shfl_sync(0xffffffffu, bf_lo(v[0][1]), lane & ~3); }
#pragma unroll
        for (int k = 0; k < 4; k++)
#pragma unroll
          for (int e = 0; e < 4; e += 2) {
            const float x0 = bf_lo(v[k][e]) - pv0, x1 = bf_hi(v[k][e]) - pv0, y0 = bf_lo(v[k][e + 1]) - pv1, y1 = bf_hi(v[k][e + 1]) - pv1;
            s0 += x0; s1 += x1; s2 += y0; s3 += y1;
            q0 = fmaf(x0, x0, q0); q1 = fmaf(x1, x1, q1); q2 = fmaf(y0, y0, q2); q3 = fmaf(y1, y1, q3);
          }
      }
      STAMP(11);
      asm volatile("setmaxnreg.inc.sync.aligned.u32 240;");
      s0 += s1; s2 += s3; q0 += q1; q2 += q3;
#pragma unroll
      for (int d = 1; d < 4; d <<= 1) {
        s0 += __shfl_xor_sync(0xffffffffu, s0, d); s2 += __shfl_xor_sync(0xffffffffu, s2, d);
        q0 += __shfl_xor_sync(0xffffffffu, q0, d); q2 += __shfl_xor_sync(0xffffffffu, q2, d);
      }
      s0 *= (1.f / 576.f); s2 *= (1.f / 576.f);
      const float var0 = fmaxf(fmaf(q0, 1.f / 576.f, -s0 * s0), 0.f), var1 = fmaxf(fmaf(q2, 1.f / 576.f, -s2 * s2), 0.f);
      const float inv0 = 1.f / bf_round(sqrtf(bf_round(bf_round(var0) + 1e-5f))), inv1 = 1.f / bf_round(sqrtf(bf_round(bf_round(var1) + 1e-5f)));
      const uint32_t mb0 = pack(pv0 + s0, pv0 + s0), mb1 = pack(pv1 + s2, pv1 + s2);
      const uint32_t h0 = pack(inv0, inv0), h1 = pack(inv1, inv1);
      const uint32_t e0 = pack(inv0 - bf_lo(h0), inv0 - bf_lo(h0)), e1 = pack(inv1 - bf_lo(h1), inv1 - bf_lo(h1));
#define NORM_STORE(C)                                                                                          \
  {                                                                                                            \
    _Pragma("unroll") for (int k = 0; k < 4; k++)                                                              \
      stsm4(ra[k] + (C) * 16384, bscale2(bsub2(v[k][0], mb0), h0, e0), bscale2(bsub2(v[k][1], mb1), h1, e1),   \
            bscale2(bsub2(v[k][2], mb0), h0, e0), bscale2(bsub2(v[k][3], mb1), h1, e1));                       \
    asm volatile("fence.proxy.async.shared::cta;" ::: "memory");                                               \
    __syncwarp();                                                                                              \
    mbar_arrive_if(bar + 8 * B_NR + 8 * wg, l0);                                                               \
  }
      float aq[96], ar[12];
      {
        uint32_t v[4][4];
#pragma unroll
        for (int k = 0; k < 4; k++) ldsm4(v[k], ra[k]);
        NORM_STORE(0)
      }
#pragma unroll
      for (int i = 0; i < 96; i++) aq[i] = 0.f;
#pragma unroll
      for (int i = 0; i < 12; i++) ar[i] = 0.f;
      pin<96>(aq); pin<12>(ar);
      STAMP(1);
      const uint32_t qdesc = (((sb + SM_RING) & 0x3FFFF) >> 4) | LO_B;
      const uint32_t rdesc = (((sb + SM_RING + 24576) & 0x3FFFF) >> 4) | LO_R;
      uint32_t s = 0, ph = 0;
#pragma unroll 1
      for (int kb = 0; kb < 9; kb++) {
        uint32_t v[4][4];
        const int cn = kb < 8 ? kb + 1 : 8;
#pragma unroll
        for (int k = 0; k < 4; k++) ldsm4(v[k], ra[k] + cn * 16384);
        mbar_wait(bar + 8 * B_QF + 8 * s, ph);
        mbar_wait(bar + 8 * B_NR + 8 * wg, kb & 1);
        wg_fence();
#pragma unroll
        for (int k = 0; k < 4; k++) {
          wg_ss_n192<HI_SW128, HI_SW128>(aq, adesc + kb * 1024 + k * 2, qdesc + s * (QST >> 4) + k * 128);
          wg_ss_n24<HI_SW128, HI_R>(ar, adesc + kb * 1024 + k * 2, rdesc + s * (QST >> 4) + k * 16);
        }
        wg_commit();
        if (kb < 8) NORM_STORE(cn)
        wg_wait<1>();
        mbar_arrive_if(bar + 8 * B_QE + (s == 0 ? 16 : 8 * s - 8), l0 & (kb > 0));
        if (++s == 3) { s = 0; ph ^= 1; }
      }
      wg_wait<0>();
      pin<96>(aq); pin<12>(ar);
      mbar_arrive_if(bar + 8 * (B_QE + 2), l0);
      STAMP(2);
      uint32_t* kvp = g_KV + (size_t)(4 * j) * SEQ * 20 + (row0 >> 3) * 160 + lane;
      {
        uint32_t pk[2][9][2];
#pragma unroll
        for (int p = 0; p < 2; p++)
#pragma unroll
          for (int i = 0; i < 9; i++) {
            const float* src = i < 8 ? &aq[(8 * (p + 1) + i) * 4] : &ar[4 * (p + 1)];
            pk[p][i][0] = pack(src[0], src[1]); pk[p][i][1] = pack(src[2], src[3]);
          }
#pragma unroll
        for (int hp = 0; hp < 4; hp++) {
          const bool up = t < hp;
#pragma unroll
          for (int rh = 0; rh < 2; rh++) {
            uint32_t* d = kvp + hp * SEQ * 20 + rh * 160;
            d[0] = up ? pk[0][2 * hp + 1][rh] : pk[0][2 * hp][rh];
            d[32] = up ? pk[0][2 * hp + 2][rh] : pk[0][2 * hp + 1][rh];
            d[96 + ((t - hp) & 3) - t] = up ? pk[1][2 * hp + 1][rh] : pk[1][2 * hp][rh];
            d[128 + ((t - hp) & 3) - t] = up ? pk[1][2 * hp + 2][rh] : pk[1][2 * hp + 1][rh];
            const uint32_t v9 = __shfl_sync(0xffffffffu, pk[1][2 * hp + 2][rh], (lane & ~3) | hp);
            d[64] = t == hp ? pk[0][2 * hp + 2][rh] : t == ((hp + 1) & 3) ? 0x3f803f80u : t == ((hp + 2) & 3) ? v9 : 0u;
          }
        }
      }
      __syncwarp();
      mbar_arrive_if(bar + 8 * B_SKV, l0);
      STAMP(3);
      mbar_wait(bar + 8 * B_BF, 0);
      wg_fence();
      G1_ISSUE_Z(accA)
      wg_commit();
      B_ADVANCE()
      uint32_t pq[9][2];
#pragma unroll
      for (int i = 0; i < 9; i++) {
        const float* src = i < 8 ? &aq[i * 4] : &ar[0];
        pq[i][0] = pack(bf_round(src[0]) * QSCALE, bf_round(src[1]) * QSCALE); pq[i][1] = pack(bf_round(src[2]) * QSCALE, bf_round(src[3]) * QSCALE);
      }
      uint4* qp = reinterpret_cast<uint4*>(g_Q) + cta * 4 * 512 + tid;
#pragma unroll
      for (int hp = 0; hp < 4; hp++) {
        const bool up = t < hp;
        qp[hp * 512] = make_uint4(up ? pq[2 * hp + 1][0] : pq[2 * hp][0], up ? pq[2 * hp + 1][1] : pq[2 * hp][1],
                                                               up ? pq[2 * hp + 2][0] : pq[2 * hp + 1][0], up ? pq[2 * hp + 2][1] : pq[2 * hp + 1][1]);
        qp[hp * 512 + 256] = make_uint4(t == hp ? pq[2 * hp + 2][0] : 0u, t == hp ? pq[2 * hp + 2][1] : 0u, 0u, 0u);
      }
      load_q(a, cta, hx, tid);
#pragma unroll
      for (int i = 0; i < 16; i++) a.p[i] = 0;
#pragma unroll
      for (int i = 0; i < 12; i++) a.o[i] = 0.f;
      pin<16>(a.p); pin<12>(a.o);
    }
#pragma unroll 1
    for (int i = 1; i < NG0; i++) {
      mbar_wait(bar + 8 * B_BF + 8 * bslot, bph);
      wg_fence();
      G1_ISSUE(accA, i)
      wg_commit();
      wg_wait<1>();
      mbar_arrive_if(bar + 8 * B_BE + 8 * bprev, l0);
      B_ADVANCE()
    }
    pin<8>(a.q);
    STAMP(4);
    mbar_wait(bar + 8 * B_BF + 8 * bslot, bph);
    mbar_wait(bar + 8 * B_KF, 0);
    STAMP(23);
    uint32_t k8 = 0, kph = 0, kd = kdesc0;
    uint32_t it = 0;
    uint32_t ox0 = 0, ox1 = 0;
    bool early_o = false, special = true;
    __nv_bfloat16* hdst = g_H + (size_t)row0 * FF + 576 * j + 8 * t;
    uint32_t ao = adesc + AOFF(3 * NG0), a1 = adesc + AOFF(3 * NG0 + 1), a2 = adesc + AOFF(3 * NG0 + 2), bd = bdesc + bslot * 768;

#define ITEM_SWITCH()                                                                                          \
  if (__builtin_expect(special, 0)) {                                                                          \
    if (it & 1) {                                                                                              \
      load_q(a, cta, (((it >> 5) + 1) & 3) ^ hx, tid);                                                         \
    } else {                                                                                                   \
      pin<12>(a.o);                                                                                            \
      if (it != 0) badmask |= (uint32_t)o_epilogue(a.o, ox0, ox1, ((it >> 5) - 1) ^ hx, g_O + cta * 9 * 512 + wr * 64 + lane, lane) << (((it >> 5) - 1) ^ hx); \
      if (it == 96) { __syncwarp(); mbar_arrive_if(bar + 8 * B_SO1, l0 & (badmask == 0)); early_o = badmask == 0; } \
      first_tile(a, (it >> 5) ^ hx, lane);                                                                     \
    }                                                                                                          \
  }
#define KV_ADVANCE() { kd += 384; k8 += 8; if (k8 == 24) { k8 = 0; kd = kdesc0; kph ^= 1; } it++; special = ((it + 1) & 31) < 2; }
#define WAIT_UNLESS(OK, BA, PA, BB, PB) if (__builtin_expect(!__all_sync(0xffffffffu, OK), 0)) { mbar_wait(BA, PA); mbar_wait(BB, PB); }
#define EPI_STEP(ACCN, ACCO)                                                                                   \
  {                                                                                                            \
    wg_fence();                                                                                                \
    wg_ss_z_n128<HI_SW128, HI_SW128>(ACCN, adesc, bd);                                                         \
    wg_ss_n128<HI_SW128, HI_SW128>(ACCN, adesc + 2, bd + 128);                                                 \
    wg_ss_n128<HI_SW128, HI_SW128>(ACCN, adesc + 4, bd + 256);                                                 \
    wg_commit();                                                                                               \
    wg_wait<1>();                                                                                              \
    pin<64>(ACCO);                                                                                             \
    mbar_arrive_if(bar + 8 * B_BE + 8 * bprev, l0);                                                            \
    B_ADVANCE()                                                                                                \
    bd = bdesc + bslot * 768; ao = adesc + AOFF(3); a1 = adesc + AOFF(4); a2 = adesc + AOFF(5);                \
    const uint32_t ok = mbar_test(bar + 8 * B_BF + 8 * bslot, bph);                                            \
    h_epilogue(ACCO, hdst);                                                                                    \
    hdst += 64;                                                                                                \
    __syncwarp();                                                                                              \
    mbar_arrive_if(bar + 8 * B_SH, l0);                                                                        \
    WAIT_UNLESS(ok, bar + 8 * B_BF + 8 * bslot, bph, bar + 8 * B_BF + 8 * bslot, bph)                          \
  }
#define ATT_LOOP1(ACC)                                                                                         \
  do {                                                                                                         \
    wg_fence();                                                                                                \
    issue_att(a, kd);                                                                                          \
    wg_commit();                                                                                               \
    wg_ss_n128<HI_SW128, HI_SW128>(ACC, ao, bd);                                                               \
    wg_ss_n128<HI_SW128, HI_SW128>(ACC, a1, bd + 128);                                                         \
    wg_ss_n128<HI_SW128, HI_SW128>(ACC, a2, bd + 256);                                                         \
    wg_commit();                                                                                               \
    wg_wait<1>();                                                                                              \
    pin<32>(a.s);                                                                                              \
    mbar_arrive_if(bar + 8 * B_BE + 8 * bprev, l0);                                                            \
    mbar_arrive_if(bar + 8 * B_KE + k8, l0);                                                                   \
    ITEM_SWITCH()                                                                                              \
    B_ADVANCE()                                                                                                \
    KV_ADVANCE()                                                                                               \
    kk += 3;                                                                                                   \
    bd = bdesc + bslot * 768; ao = adesc + AOFF(kk); a1 = adesc + AOFF(kk + 1); a2 = adesc + AOFF(kk + 2);     \
    const uint32_t ok = mbar_test(bar + 8 * B_BF + 8 * bslot, bph) & mbar_test(bar + 8 * B_KF + k8, kph);      \
    softmax_tile(a);                                                                                           \
    pin<8>(a.q);                                                                                               \
    WAIT_UNLESS(ok, bar + 8 * B_BF + 8 * bslot, bph, bar + 8 * B_KF + k8, kph)                                 \
  } while (kk != 36);
    {
      uint32_t kk = 3 * NG0;
#pragma unroll 1
      for (int pr = 0;; pr++) {
        ATT_LOOP1(accA)
        if (pr == 4) break;
        EPI_STEP(accB, accA)
        kk = 3;
        ATT_LOOP1(accB)
        EPI_STEP(accA, accB)
        kk = 3;
      }
    }
    STAMP(5);
    wg_wait<0>();
    pin<64>(accA);
    mbar_arrive_if(bar + 8 * B_BE + 8 * bprev, l0);
    h_epilogue(accA, hdst);
    __syncwarp();
    mbar_arrive_if(bar + 8 * B_SH, l0);
    STAMP(6);
    mbar_wait(bar + 8 * B_GF, 0);
    STAMP(12);

    float acc2[144];
    const uint32_t a2desc = (((sb + wg * 8192) & 0x3FFFF) >> 4) | LO_A;
    const uint32_t b2desc = (((sb + 16384) & 0x3FFFF) >> 4) | LO_B;
    uint32_t g8 = 0, gph = 0, gprev = 0, h2 = 0, ad = a2desc, bd2 = b2desc;
#define G2_MMA(AHI, AD, BD, NOFF)                                                                              \
  wg_ss_n128<AHI, HI_SW128>(acc2, AD, BD);                                                                     \
  wg_ss_n160<AHI, HI_SW128>(acc2 + 64, AD, (BD) + (NOFF));
#define ATT_STEP2(ZERO)                                                                                        \
  {                                                                                                            \
    wg_fence();                                                                                                \
    issue_att(a, kd);                                                                                          \
    wg_commit();                                                                                               \
    if (ZERO) {                                                                                                \
      wg_ss_z_n128<HI_SW128, HI_SW128>(acc2, ad, bd2);                                                         \
      wg_ss_z_n160<HI_SW128, HI_SW128>(acc2 + 64, ad, bd2 + 1024);                                             \
    } else { G2_MMA(HI_SW128, ad, bd2, 1024) }                                                                 \
    G2_MMA(HI_SW128, ad + 2, bd2 + 128, 1024)                                                                  \
    wg_commit();                                                                                               \
    wg_wait<1>();                                                                                              \
    pin<32>(a.s);                                                                                              \
    mbar_arrive_if(bar + 8 * B_KE + k8, l0);                                                                   \
    if (!(ZERO)) { mbar_arrive_if(bar + 8 * B_GE + gprev, l0 & (h2 ^ 1)); ITEM_SWITCH() }                      \
    KV_ADVANCE()                                                                                               \
    if (h2) { gprev = g8; g8 += 8; if (g8 == 24) { g8 = 0; gph ^= 1; } }                                       \
    h2 ^= 1;                                                                                                   \
    ad = a2desc + g8 * 448 + h2 * 4; bd2 = b2desc + g8 * 448 + h2 * 256;                                       \
    const uint32_t ok = mbar_test(bar + 8 * B_GF + g8, gph) & mbar_test(bar + 8 * B_KF + k8, kph);             \
    softmax_tile(a);                                                                                           \
    pin<8>(a.q);                                                                                               \
    WAIT_UNLESS(ok, bar + 8 * B_GF + g8, gph, bar + 8 * B_KF + k8, kph)                                        \
  }
    static_assert(NG0 == 7, "tail code below assumes 35 GEMM2 slots");
    ATT_STEP2(true);
    do ATT_STEP2(false) while (it != 128);
    STAMP(7);
    wg_fence();
    issue_pv(a, kd);
    wg_commit();
    G2_MMA(HI_SW128, a2desc + 7168 + 4, b2desc + 7168 + 256, 1024)
    G2_MMA(HI_SW128, a2desc + 7168 + 6, b2desc + 7168 + 384, 1024)
    wg_commit();
    wg_wait<1>();
    pin<12>(a.o);
    {
      uint32_t* od = g_O + cta * 9 * 512 + wr * 64 + lane;
      badmask |= (uint32_t)o_epilogue(a.o, ox0, ox1, 3 ^ hx, od, lane) << (3 ^ hx);
      od += 4096 + ((t + 2) & 3) - t;
      od[0] = ox0; od[32] = ox1;
    }
    __syncwarp();
    mbar_arrive_if(bar + 8 * B_SO2, l0 & (badmask == 0));
    if (__builtin_expect(badmask != 0, 0)) {
      wg_wait<0>();
#pragma unroll 1
      for (int hp = 0; hp < 4; hp++)
        if ((badmask >> hp) & 1) attn_slow_rows(cta, j, hp, 16 * wr, tid & ~31);
      __syncwarp();
      mbar_arrive_if(bar + 8 * B_SO1, l0 & !early_o);
      mbar_arrive_if(bar + 8 * B_SO2, l0);
    }
    STAMP(8);
    const uint32_t odesc = (((sb + wg * 1024) & 0x3FFFF) >> 4) | LO_O;
    mbar_wait(bar + 8 * (B_GF + 0), 0);
    wg_fence();
#pragma unroll
    for (int k = 0; k < 3; k++) { G2_MMA(HI_O, odesc + k * 256, b2desc + k * 128, 1024) }
    wg_commit();
    mbar_wait(bar + 8 * (B_GF + 1), 0);
    wg_fence();
#pragma unroll
    for (int k = 1; k < 4; k++) { G2_MMA(HI_O, odesc + 3584 + k * 256, b2desc + 3584 + k * 128, 1024) }
    wg_commit();
    STAMP(13);
    const uint32_t tag = (*(volatile uint32_t*)FLAG_EPOCH + 1) & 1;
    mbar_wait(bar + 8 * B_OL, 0);
    STAMP(14);
    wg_fence();
    G2_MMA(HI_O, odesc + 768, b2desc + 384, 1024)
    G2_MMA(HI_O, odesc + 3584, b2desc + 3584, 1024)
    G2_MMA(HI_O, odesc + (SM_OL >> 4), (((sb + SM_W16) & 0x3FFFF) >> 4) | LO_B16, 256)
    wg_commit();
    int tid2, bid2;
    asm volatile("mov.u32 %0, %%tid.x;" : "=r"(tid2));
    asm volatile("mov.u32 %0, %%ctaid.x;" : "=r"(bid2));
    const int m2 = bid2 & 15, j2 = bid2 >> 4;
    const size_t xoff = (size_t)(128 * m2 + (tid2 >> 5) * 16 + ((tid2 & 31) >> 2)) * DM + 288 * (j2 & 1) + 2 * (tid2 & 3);
    const uint32_t* xr = reinterpret_cast<const uint32_t*>(prm.x + xoff);
    uint32_t* orow = reinterpret_cast<uint32_t*>(prm.out + xoff);
    wg_wait<0>();
    pin<144>(acc2);
    STAMP(9);
    switch (j2 >> 1) {
      case 0: final_exchange<0>(acc2, xr, orow, m2, j2 & 1, tid2, tag); break;
      case 1: final_exchange<1>(acc2, xr, orow, m2, j2 & 1, tid2, tag); break;
      case 2: final_exchange<2>(acc2, xr, orow, m2, j2 & 1, tid2, tag); break;
      default: final_exchange<3>(acc2, xr, orow, m2, j2 & 1, tid2, tag); break;
    }
    STAMP(10);
    __syncwarp();
    if (lane == 0) {
      if (atomicInc(FLAG_DONE, NCTA * 8 - 1) == NCTA * 8 - 1) {
        for (int i = 0; i < 8; i++) *FLAG_KV(i) = 0;
        for (int i = 0; i < NCTA; i++) { *FLAG_H(i) = 0; *FLAG_O(i) = 0; }
        *FLAG_EPOCH = tag;
      }
    }
  }
}

typedef CUresult (*EncodeFn)(CUtensorMap*, CUtensorMapDataType, cuuint32_t, void*, const cuuint64_t*, const cuuint64_t*, const cuuint32_t*, const cuuint32_t*,
                             CUtensorMapInterleave, CUtensorMapSwizzle, CUtensorMapL2promotion, CUtensorMapFloatOOBfill);

void enc2d(EncodeFn enc, CUtensorMap* tm, const void* base, uint64_t w, uint64_t h, uint64_t pitch_elems, uint32_t bw, uint32_t bh, CUtensorMapSwizzle sw) {
  cuuint64_t dims[2] = {w, h}, str[1] = {pitch_elems * 2};
  cuuint32_t box[2] = {bw, bh}, es[2] = {1, 1};
  enc(tm, CU_TENSOR_MAP_DATA_TYPE_BFLOAT16, 2, const_cast<void*>(base), dims, str, box, es, CU_TENSOR_MAP_INTERLEAVE_NONE, sw,
      CU_TENSOR_MAP_L2_PROMOTION_L2_128B, CU_TENSOR_MAP_FLOAT_OOB_FILL_NONE);
}

}

extern "C" void kernel_launch(void* const* d_in, const int* in_sizes, int n_in, void* d_out, int out_size) {
  (void)in_sizes; (void)n_in; (void)out_size;
  const __nv_bfloat16* x = (const __nv_bfloat16*)d_in[0];
  const __nv_bfloat16* wqkv = (const __nv_bfloat16*)d_in[1];
  const __nv_bfloat16* wo = (const __nv_bfloat16*)d_in[2];
  const __nv_bfloat16* wg = (const __nv_bfloat16*)d_in[4];
  const __nv_bfloat16* wu = (const __nv_bfloat16*)d_in[5];
  const __nv_bfloat16* wd = (const __nv_bfloat16*)d_in[6];
  void* fn = nullptr;
  cudaDriverEntryPointQueryResult qr;
  cudaGetDriverEntryPoint("cuTensorMapEncodeTiled", &fn, cudaEnableDefault, &qr);
  EncodeFn enc = (EncodeFn)fn;
  void *hp = nullptr, *kvp = nullptr;
  cudaGetSymbolAddress(&kvp, g_KV);
  cudaGetSymbolAddress(&hp, g_H);
  Params p;
  enc2d(enc, &p.xm, x, DM, SEQ, DM, 64, 128, CU_TENSOR_MAP_SWIZZLE_128B);
  enc2d(enc, &p.kv, kvp, 320, 32 * 256, 320, 192, 8, CU_TENSOR_MAP_SWIZZLE_NONE);
  enc2d(enc, &p.wqkv64, wqkv, 3 * DM, DM, 3 * DM, 64, 64, CU_TENSOR_MAP_SWIZZLE_128B);
  enc2d(enc, &p.wqkv8, wqkv, 3 * DM, DM, 3 * DM, 8, 64, CU_TENSOR_MAP_SWIZZLE_NONE);
  enc2d(enc, &p.wg, wg, FF, DM, FF, 64, 48, CU_TENSOR_MAP_SWIZZLE_128B);
  enc2d(enc, &p.wu, wu, FF, DM, FF, 64, 48, CU_TENSOR_MAP_SWIZZLE_128B);
  enc2d(enc, &p.h, hp, FF, SEQ, FF, 64, 128, CU_TENSOR_MAP_SWIZZLE_128B);
  for (int hh = 0; hh < 2; hh++) {
    for (int e = 0; e < 2; e++) {
      cuuint64_t d3[3] = {288, e ? 2u : 16u, 32}, s3[2] = {DM * 2, 18 * DM * 2};
      cuuint32_t b3[3] = {64, e ? 2u : 16u, e ? 8u : 4u}, e3[3] = {1, 1, 1};
      enc(e ? &p.wo16[hh] : &p.wo[hh], CU_TENSOR_MAP_DATA_TYPE_BFLOAT16, 3, (void*)(wo + 288 * hh + (e ? 16 * DM : 0)), d3, s3, b3, e3,
          CU_TENSOR_MAP_INTERLEAVE_NONE, CU_TENSOR_MAP_SWIZZLE_128B, CU_TENSOR_MAP_L2_PROMOTION_L2_128B, CU_TENSOR_MAP_FLOAT_OOB_FILL_NONE);
    }
    cuuint64_t dims[5] = {288, 2, 4, 4, FF / 32}, str[4] = {DM * 2, 8 * DM * 2, 2 * DM * 2, 32 * DM * 2};
    cuuint32_t box[5] = {64, 2, 4, 4, 2}, es[5] = {1, 1, 1, 1, 1};
    enc(&p.wd[hh], CU_TENSOR_MAP_DATA_TYPE_BFLOAT16, 5, (void*)(wd + 288 * hh), dims, str, box, es, CU_TENSOR_MAP_INTERLEAVE_NONE,
        CU_TENSOR_MAP_SWIZZLE_128B, CU_TENSOR_MAP_L2_PROMOTION_L2_128B, CU_TENSOR_MAP_FLOAT_OOB_FILL_NONE);
  }
  p.x = x;
  p.out = (__nv_bfloat16*)d_out;
  cudaFuncSetAttribute(fused_kernel, cudaFuncAttributeMaxDynamicSharedMemorySize, SM_TOTAL);
  fused_kernel<<<NCTA, 384, SM_TOTAL, cudaStreamPerThread>>>(p);
}
```

```cpp
#include <cuda_runtime.h>
#include <cuda.h>
#include <cuda_bf16.h>
#include <stdint.h>

namespace {

constexpr int SEQ = 2048, DM = 576, FF = 4608;
constexpr int NCTA = 128;

constexpr uint32_t SM_XN = 0;
constexpr uint32_t SM_RING = 147456;
constexpr uint32_t SM_KV = 208896;
constexpr uint32_t QST = 27648, BST = 12288, KVST = 6144, G2ST = 57344;
constexpr uint32_t SM_OL = 172032;
constexpr uint32_t SM_W16 = SM_OL + 4096;
constexpr uint32_t SM_BAR = 232064;
constexpr uint32_t SM_TOTAL = 232448;
enum { B_QF = 0, B_QE = 3, B_BF = 6, B_BE = 11, B_GF = 16, B_GE = 19, B_KF = 22, B_KE = 25, B_SKV = 28, B_SH = 29, B_SO1 = 30, B_SO2 = 31,
       B_OL = 32, B_X = 33, B_NR = 42, B_N = 44 };
constexpr int NG0 = 7;

constexpr uint32_t HI_SW128 = 0x40000040u;
constexpr uint32_t LO_A = 1u << 16;
constexpr uint32_t LO_B = 512u << 16;
constexpr uint32_t HI_R = 64u, LO_R = 8u << 16;
constexpr uint32_t HI_K = 24u, LO_K = 8u << 16;
constexpr uint32_t HI_V = 8u, LO_V = 24u << 16;
constexpr uint32_t LO_B48 = 384u << 16;
constexpr uint32_t HI_O = 8u, LO_O = 128u << 16;
constexpr uint32_t LO_B16 = 128u << 16;

constexpr float QSCALE = 0.23570226039551584f * 1.4426950408889634f;
constexpr float MOFF = 90.f;

struct __align__(64) Params {
  CUtensorMap xm, wqkv64, wqkv8, wg, wu, h, wd[2], wo[2], wo16[2], kv;
  const __nv_bfloat16* x;
  __nv_bfloat16* out;
};

__device__ __align__(1024) __nv_bfloat16 g_H[SEQ * FF];
__device__ __align__(1024) uint32_t g_O[NCTA * 9 * 512];
__device__ __align__(1024) uint32_t g_KV[32 * SEQ * 20];
__device__ __align__(1024) uint32_t g_Q[NCTA * 4 * 256 * 8];
__device__ __align__(1024) uint4 g_P[32 * 16 * 5 * 256];
__device__ uint32_t g_flags[8 * 32 + NCTA * 32 * 3 + 32];
#define FLAG_KV(j) (&g_flags[(j) * 32])
#define FLAG_H(c) (&g_flags[8 * 32 + (c) * 32])
#define FLAG_O(c) (&g_flags[8 * 32 + NCTA * 32 + (c) * 32])
#define FLAG_P(c) (&g_flags[8 * 32 + NCTA * 64 + (c) * 32])
#define FLAG_DONE (&g_flags[8 * 32 + NCTA * 96])
#define FLAG_EPOCH (&g_flags[8 * 32 + NCTA * 96 + 16])
#define STAMP(i)
#define STAMPW(i)

template<uint32_t AHI, uint32_t BHI> __device__ __forceinline__ void wg_ss_n192(float* d, uint32_t a, uint32_t b) {
  asm volatile("{\n.reg .pred p;\n.reg .b64 da, db;\nsetp.ne.b32 p, 1, 0;\nmov.b64 da, {%96, %98};\nmov.b64 db, {%97, %99};\n"
    "wgmma.mma_async.sync.aligned.m64n192k16.f32.bf16.bf16 {%0, %1, %2, %3, %4, %5, %6, %7, %8, %9, %10, %11, %12, %13, %14, %15, %16, %17, %18, %19, %20, %21, %22, %23, %24, %25, %26, %27, %28, %29, %30, %31, %32, %33, %34, %35, %36, %37, %38, %39, %40, %41, %42, %43, %44, %45, %46, %47, %48, %49, %50, %51, %52, %53, %54, %55, %56, %57, %58, %59, %60, %61, %62, %63, %64, %65, %66, %67, %68, %69, %70, %71, %72, %73, %74, %75, %76, %77, %78, %79, %80, %81, %82, %83, %84, %85, %86, %87, %88, %89, %90, %91, %92, %93, %94, %95}, da, db, p, 1, 1, 0, 1;\n}\n"
    : "+f"(d[0]), "+f"(d[1]), "+f"(d[2]), "+f"(d[3]), "+f"(d[4]), "+f"(d[5]), "+f"(d[6]), "+f"(d[7]), "+f"(d[8]), "+f"(d[9]), "+f"(d[10]), "+f"(d[11]), "+f"(d[12]), "+f"(d[13]), "+f"(d[14]), "+f"(d[15]), "+f"(d[16]), "+f"(d[17]), "+f"(d[18]), "+f"(d[19]), "+f"(d[20]), "+f"(d[21]), "+f"(d[22]), "+f"(d[23]), "+f"(d[24]), "+f"(d[25]), "+f"(d[26]), "+f"(d[27]), "+f"(d[28]), "+f"(d[29]), "+f"(d[30]), "+f"(d[31]), "+f"(d[32]), "+f"(d[33]), "+f"(d[34]), "+f"(d[35]), "+f"(d[36]), "+f"(d[37]), "+f"(d[38]), "+f"(d[39]), "+f"(d[40]), "+f"(d[41]), "+f"(d[42]), "+f"(d[43]), "+f"(d[44]), "+f"(d[45]), "+f"(d[46]), "+f"(d[47]), "+f"(d[48]), "+f"(d[49]), "+f"(d[50]), "+f"(d[51]), "+f"(d[52]), "+f"(d[53]), "+f"(d[54]), "+f"(d[55]), "+f"(d[56]), "+f"(d[57]), "+f"(d[58]), "+f"(d[59]), "+f"(d[60]), "+f"(d[61]), "+f"(d[62]), "+f"(d[63]), "+f"(d[64]), "+f"(d[65]), "+f"(d[66]), "+f"(d[67]), "+f"(d[68]), "+f"(d[69]), "+f"(d[70]), "+f"(d[71]), "+f"(d[72]), "+f"(d[73]), "+f"(d[74]), "+f"(d[75]), "+f"(d[76]), "+f"(d[77]), "+f"(d[78]), "+f"(d[79]), "+f"(d[80]), "+f"(d[81]), "+f"(d[82]), "+f"(d[83]), "+f"(d[84]), "+f"(d[85]), "+f"(d[86]), "+f"(d[87]), "+f"(d[88]), "+f"(d[89]), "+f"(d[90]), "+f"(d[91]), "+f"(d[92]), "+f"(d[93]), "+f"(d[94]), "+f"(d[95])
    : "r"(a), "r"(b), "n"(AHI), "n"(BHI));
}
template<uint32_t AHI, uint32_t BHI> __device__ __forceinline__ void wg_ss_z_n192(float* d, uint32_t a, uint32_t b) {
  asm volatile("{\n.reg .pred p;\n.reg .b64 da, db;\nsetp.ne.b32 p, 0, 0;\nmov.b64 da, {%96, %98};\nmov.b64 db, {%97, %99};\n"
    "wgmma.mma_async.sync.aligned.m64n192k16.f32.bf16.bf16 {%0, %1, %2, %3, %4, %5, %6, %7, %8, %9, %10, %11, %12, %13, %14, %15, %16, %17, %18, %19, %20, %21, %22, %23, %24, %25, %26, %27, %28, %29, %30, %31, %32, %33, %34, %35, %36, %37, %38, %39, %40, %41, %42, %43, %44, %45, %46, %47, %48, %49, %50, %51, %52, %53, %54, %55, %56, %57, %58, %59, %60, %61, %62, %63, %64, %65, %66, %67, %68, %69, %70, %71, %72, %73, %74, %75, %76, %77, %78, %79, %80, %81, %82, %83, %84, %85, %86, %87, %88, %89, %90, %91, %92, %93, %94, %95}, da, db, p, 1, 1, 0, 1;\n}\n"
    : "=f"(d[0]), "=f"(d[1]), "=f"(d[2]), "=f"(d[3]), "=f"(d[4]), "=f"(d[5]), "=f"(d[6]), "=f"(d[7]), "=f"(d[8]), "=f"(d[9]), "=f"(d[10]), "=f"(d[11]), "=f"(d[12]), "=f"(d[13]), "=f"(d[14]), "=f"(d[15]), "=f"(d[16]), "=f"(d[17]), "=f"(d[18]), "=f"(d[19]), "=f"(d[20]), "=f"(d[21]), "=f"(d[22]), "=f"(d[23]), "=f"(d[24]), "=f"(d[25]), "=f"(d[26]), "=f"(d[27]), "=f"(d[28]), "=f"(d[29]), "=f"(d[30]), "=f"(d[31]), "=f"(d[32]), "=f"(d[33]), "=f"(d[34]), "=f"(d[35]), "=f"(d[36]), "=f"(d[37]), "=f"(d[38]), "=f"(d[39]), "=f"(d[40]), "=f"(d[41]), "=f"(d[42]), "=f"(d[43]), "=f"(d[44]), "=f"(d[45]), "=f"(d[46]), "=f"(d[47]), "=f"(d[48]), "=f"(d[49]), "=f"(d[50]), "=f"(d[51]), "=f"(d[52]), "=f"(d[53]), "=f"(d[54]), "=f"(d[55]), "=f"(d[56]), "=f"(d[57]), "=f"(d[58]), "=f"(d[59]), "=f"(d[60]), "=f"(d[61]), "=f"(d[62]), "=f"(d[63]), "=f"(d[64]), "=f"(d[65]), "=f"(d[66]), "=f"(d[67]), "=f"(d[68]), "=f"(d[69]), "=f"(d[70]), "=f"(d[71]), "=f"(d[72]), "=f"(d[73]), "=f"(d[74]), "=f"(d[75]), "=f"(d[76]), "=f"(d[77]), "=f"(d[78]), "=f"(d[79]), "=f"(d[80]), "=f"(d[81]), "=f"(d[82]), "=f"(d[83]), "=f"(d[84]), "=f"(d[85]), "=f"(d[86]), "=f"(d[87]), "=f"(d[88]), "=f"(d[89]), "=f"(d[90]), "=f"(d[91]), "=f"(d[92]), "=f"(d[93]), "=f"(d[94]), "=f"(d[95])
    : "r"(a), "r"(b), "n"(AHI), "n"(BHI));
}
template<uint32_t AHI, uint32_t BHI> __device__ __forceinline__ void wg_ss_n24(float* d, uint32_t a, uint32_t b) {
  asm volatile("{\n.reg .pred p;\n.reg .b64 da, db;\nsetp.ne.b32 p, 1, 0;\nmov.b64 da, {%12, %14};\nmov.b64 db, {%13, %15};\n"
    "wgmma.mma_async.sync.aligned.m64n24k16.f32.bf16.bf16 {%0, %1, %2, %3, %4, %5, %6, %7, %8, %9, %10, %11}, da, db, p, 1, 1, 0, 1;\n}\n"
    : "+f"(d[0]), "+f"(d[1]), "+f"(d[2]), "+f"(d[3]), "+f"(d[4]), "+f"(d[5]), "+f"(d[6]), "+f"(d[7]), "+f"(d[8]), "+f"(d[9]), "+f"(d[10]), "+f"(d[11])
    : "r"(a), "r"(b), "n"(AHI), "n"(BHI));
}
template<uint32_t AHI, uint32_t BHI> __device__ __forceinline__ void wg_ss_z_n24(float* d, uint32_t a, uint32_t b) {
  asm volatile("{\n.reg .pred p;\n.reg .b64 da, db;\nsetp.ne.b32 p, 0, 0;\nmov.b64 da, {%12, %14};\nmov.b64 db, {%13, %15};\n"
    "wgmma.mma_async.sync.aligned.m64n24k16.f32.bf16.bf16 {%0, %1, %2, %3, %4, %5, %6, %7, %8, %9, %10, %11}, da, db, p, 1, 1, 0, 1;\n}\n"
    : "=f"(d[0]), "=f"(d[1]), "=f"(d[2]), "=f"(d[3]), "=f"(d[4]), "=f"(d[5]), "=f"(d[6]), "=f"(d[7]), "=f"(d[8]), "=f"(d[9]), "=f"(d[10]), "=f"(d[11])
    : "r"(a), "r"(b), "n"(AHI), "n"(BHI));
}
template<uint32_t AHI, uint32_t BHI> __device__ __forceinline__ void wg_ss_n128(float* d, uint32_t a, uint32_t b) {
  asm volatile("{\n.reg .pred p;\n.reg .b64 da, db;\nsetp.ne.b32 p, 1, 0;\nmov.b64 da, {%64, %66};\nmov.b64 db, {%65, %67};\n"
    "wgmma.mma_async.sync.aligned.m64n128k16.f32.bf16.bf16 {%0, %1, %2, %3, %4, %5, %6, %7, %8, %9, %10, %11, %12, %13, %14, %15, %16, %17, %18, %19, %20, %21, %22, %23, %24, %25, %26, %27, %28, %29, %30, %31, %32, %33, %34, %35, %36, %37, %38, %39, %40, %41, %42, %43, %44, %45, %46, %47, %48, %49, %50, %51, %52, %53, %54, %55, %56, %57, %58, %59, %60, %61, %62, %63}, da, db, p, 1, 1, 0, 1;\n}\n"
    : "+f"(d[0]), "+f"(d[1]), "+f"(d[2]), "+f"(d[3]), "+f"(d[4]), "+f"(d[5]), "+f"(d[6]), "+f"(d[7]), "+f"(d[8]), "+f"(d[9]), "+f"(d[10]), "+f"(d[11]), "+f"(d[12]), "+f"(d[13]), "+f"(d[14]), "+f"(d[15]), "+f"(d[16]), "+f"(d[17]), "+f"(d[18]), "+f"(d[19]), "+f"(d[20]), "+f"(d[21]), "+f"(d[22]), "+f"(d[23]), "+f"(d[24]), "+f"(d[25]), "+f"(d[26]), "+f"(d[27]), "+f"(d[28]), "+f"(d[29]), "+f"(d[30]), "+f"(d[31]), "+f"(d[32]), "+f"(d[33]), "+f"(d[34]), "+f"(d[35]), "+f"(d[36]), "+f"(d[37]), "+f"(d[38]), "+f"(d[39]), "+f"(d[40]), "+f"(d[41]), "+f"(d[42]), "+f"(d[43]), "+f"(d[44]), "+f"(d[45]), "+f"(d[46]), "+f"(d[47]), "+f"(d[48]), "+f"(d[49]), "+f"(d[50]), "+f"(d[51]), "+f"(d[52]), "+f"(d[53]), "+f"(d[54]), "+f"(d[55]), "+f"(d[56]), "+f"(d[57]), "+f"(d[58]), "+f"(d[59]), "+f"(d[60]), "+f"(d[61]), "+f"(d[62]), "+f"(d[63])
    : "r"(a), "r"(b), "n"(AHI), "n"(BHI));
}
template<uint32_t AHI, uint32_t BHI> __device__ __forceinline__ void wg_ss_z_n128(float* d, uint32_t a, uint32_t b) {
  asm volatile("{\n.reg .pred p;\n.reg .b64 da, db;\nsetp.ne.b32 p, 0, 0;\nmov.b64 da, {%64, %66};\nmov.b64 db, {%65, %67};\n"
    "wgmma.mma_async.sync.aligned.m64n128k16.f32.bf16.bf16 {%0, %1, %2, %3, %4, %5, %6, %7, %8, %9, %10, %11, %12, %13, %14, %15, %16, %17, %18, %19, %20, %21, %22, %23, %24, %25, %26, %27, %28, %29, %30, %31, %32, %33, %34, %35, %36, %37, %38, %39, %40, %41, %42, %43, %44, %45, %46, %47, %48, %49, %50, %51, %52, %53, %54, %55, %56, %57, %58, %59, %60, %61, %62, %63}, da, db, p, 1, 1, 0, 1;\n}\n"
    : "=f"(d[0]), "=f"(d[1]), "=f"(d[2]), "=f"(d[3]), "=f"(d[4]), "=f"(d[5]), "=f"(d[6]), "=f"(d[7]), "=f"(d[8]), "=f"(d[9]), "=f"(d[10]), "=f"(d[11]), "=f"(d[12]), "=f"(d[13]), "=f"(d[14]), "=f"(d[15]), "=f"(d[16]), "=f"(d[17]), "=f"(d[18]), "=f"(d[19]), "=f"(d[20]), "=f"(d[21]), "=f"(d[22]), "=f"(d[23]), "=f"(d[24]), "=f"(d[25]), "=f"(d[26]), "=f"(d[27]), "=f"(d[28]), "=f"(d[29]), "=f"(d[30]), "=f"(d[31]), "=f"(d[32]), "=f"(d[33]), "=f"(d[34]), "=f"(d[35]), "=f"(d[36]), "=f"(d[37]), "=f"(d[38]), "=f"(d[39]), "=f"(d[40]), "=f"(d[41]), "=f"(d[42]), "=f"(d[43]), "=f"(d[44]), "=f"(d[45]), "=f"(d[46]), "=f"(d[47]), "=f"(d[48]), "=f"(d[49]), "=f"(d[50]), "=f"(d[51]), "=f"(d[52]), "=f"(d[53]), "=f"(d[54]), "=f"(d[55]), "=f"(d[56]), "=f"(d[57]), "=f"(d[58]), "=f"(d[59]), "=f"(d[60]), "=f"(d[61]), "=f"(d[62]), "=f"(d[63])
    : "r"(a), "r"(b), "n"(AHI), "n"(BHI));
}
template<uint32_t AHI, uint32_t BHI> __device__ __forceinline__ void wg_ss_n160(float* d, uint32_t a, uint32_t b) {
  asm volatile("{\n.reg .pred p;\n.reg .b64 da, db;\nsetp.ne.b32 p, 1, 0;\nmov.b64 da, {%80, %82};\nmov.b64 db, {%81, %83};\n"
    "wgmma.mma_async.sync.aligned.m64n160k16.f32.bf16.bf16 {%0, %1, %2, %3, %4, %5, %6, %7, %8, %9, %10, %11, %12, %13, %14, %15, %16, %17, %18, %19, %20, %21, %22, %23, %24, %25, %26, %27, %28, %29, %30, %31, %32, %33, %34, %35, %36, %37, %38, %39, %40, %41, %42, %43, %44, %45, %46, %47, %48, %49, %50, %51, %52, %53, %54, %55, %56, %57, %58, %59, %60, %61, %62, %63, %64, %65, %66, %67, %68, %69, %70, %71, %72, %73, %74, %75, %76, %77, %78, %79}, da, db, p, 1, 1, 0, 1;\n}\n"
    : "+f"(d[0]), "+f"(d[1]), "+f"(d[2]), "+f"(d[3]), "+f"(d[4]), "+f"(d[5]), "+f"(d[6]), "+f"(d[7]), "+f"(d[8]), "+f"(d[9]), "+f"(d[10]), "+f"(d[11]), "+f"(d[12]), "+f"(d[13]), "+f"(d[14]), "+f"(d[15]), "+f"(d[16]), "+f"(d[17]), "+f"(d[18]), "+f"(d[19]), "+f"(d[20]), "+f"(d[21]), "+f"(d[22]), "+f"(d[23]), "+f"(d[24]), "+f"(d[25]), "+f"(d[26]), "+f"(d[27]), "+f"(d[28]), "+f"(d[29]), "+f"(d[30]), "+f"(d[31]), "+f"(d[32]), "+f"(d[33]), "+f"(d[34]), "+f"(d[35]), "+f"(d[36]), "+f"(d[37]), "+f"(d[38]), "+f"(d[39]), "+f"(d[40]), "+f"(d[41]), "+f"(d[42]), "+f"(d[43]), "+f"(d[44]), "+f"(d[45]), "+f"(d[46]), "+f"(d[47]), "+f"(d[48]), "+f"(d[49]), "+f"(d[50]), "+f"(d[51]), "+f"(d[52]), "+f"(d[53]), "+f"(d[54]), "+f"(d[55]), "+f"(d[56]), "+f"(d[57]), "+f"(d[58]), "+f"(d[59]), "+f"(d[60]), "+f"(d[61]), "+f"(d[62]), "+f"(d[63]), "+f"(d[64]), "+f"(d[65]), "+f"(d[66]), "+f"(d[67]), "+f"(d[68]), "+f"(d[69]), "+f"(d[70]), "+f"(d[71]), "+f"(d[72]), "+f"(d[73]), "+f"(d[74]), "+f"(d[75]), "+f"(d[76]), "+f"(d[77]), "+f"(d[78]), "+f"(d[79])
    : "r"(a), "r"(b), "n"(AHI), "n"(BHI));
}
template<uint32_t AHI, uint32_t BHI> __device__ __forceinline__ void wg_ss_z_n160(float* d, uint32_t a, uint32_t b) {
  asm volatile("{\n.reg .pred p;\n.reg .b64 da, db;\nsetp.ne.b32 p, 0, 0;\nmov.b64 da, {%80, %82};\nmov.b64 db, {%81, %83};\n"
    "wgmma.mma_async.sync.aligned.m64n160k16.f32.bf16.bf16 {%0, %1, %2, %3, %4, %5, %6, %7, %8, %9, %10, %11, %12, %13, %14, %15, %16, %17, %18, %19, %20, %21, %22, %23, %24, %25, %26, %27, %28, %29, %30, %31, %32, %33, %34, %35, %36, %37, %38, %39, %40, %41, %42, %43, %44, %45, %46, %47, %48, %49, %50, %51, %52, %53, %54, %55, %56, %57, %58, %59, %60, %61, %62, %63, %64, %65, %66, %67, %68, %69, %70, %71, %72, %73, %74, %75, %76, %77, %78, %79}, da, db, p, 1, 1, 0, 1;\n}\n"
    : "=f"(d[0]), "=f"(d[1]), "=f"(d[2]), "=f"(d[3]), "=f"(d[4]), "=f"(d[5]), "=f"(d[6]), "=f"(d[7]), "=f"(d[8]), "=f"(d[9]), "=f"(d[10]), "=f"(d[11]), "=f"(d[12]), "=f"(d[13]), "=f"(d[14]), "=f"(d[15]), "=f"(d[16]), "=f"(d[17]), "=f"(d[18]), "=f"(d[19]), "=f"(d[20]), "=f"(d[21]), "=f"(d[22]), "=f"(d[23]), "=f"(d[24]), "=f"(d[25]), "=f"(d[26]), "=f"(d[27]), "=f"(d[28]), "=f"(d[29]), "=f"(d[30]), "=f"(d[31]), "=f"(d[32]), "=f"(d[33]), "=f"(d[34]), "=f"(d[35]), "=f"(d[36]), "=f"(d[37]), "=f"(d[38]), "=f"(d[39]), "=f"(d[40]), "=f"(d[41]), "=f"(d[42]), "=f"(d[43]), "=f"(d[44]), "=f"(d[45]), "=f"(d[46]), "=f"(d[47]), "=f"(d[48]), "=f"(d[49]), "=f"(d[50]), "=f"(d[51]), "=f"(d[52]), "=f"(d[53]), "=f"(d[54]), "=f"(d[55]), "=f"(d[56]), "=f"(d[57]), "=f"(d[58]), "=f"(d[59]), "=f"(d[60]), "=f"(d[61]), "=f"(d[62]), "=f"(d[63]), "=f"(d[64]), "=f"(d[65]), "=f"(d[66]), "=f"(d[67]), "=f"(d[68]), "=f"(d[69]), "=f"(d[70]), "=f"(d[71]), "=f"(d[72]), "=f"(d[73]), "=f"(d[74]), "=f"(d[75]), "=f"(d[76]), "=f"(d[77]), "=f"(d[78]), "=f"(d[79])
    : "r"(a), "r"(b), "n"(AHI), "n"(BHI));
}
template<uint32_t BHI> __device__ __forceinline__ void wg_rs_n64(float* d, uint32_t a0, uint32_t a1, uint32_t a2, uint32_t a3, uint32_t b) {
  asm volatile("{\n.reg .pred p;\n.reg .b64 db;\nsetp.ne.b32 p, 1, 0;\nmov.b64 db, {%36, %37};\n"
    "wgmma.mma_async.sync.aligned.m64n64k16.f32.bf16.bf16 {%0, %1, %2, %3, %4, %5, %6, %7, %8, %9, %10, %11, %12, %13, %14, %15, %16, %17, %18, %19, %20, %21, %22, %23, %24, %25, %26, %27, %28, %29, %30, %31}, {%32, %33, %34, %35}, db, p, 1, 1, 0;\n}\n"
    : "+f"(d[0]), "+f"(d[1]), "+f"(d[2]), "+f"(d[3]), "+f"(d[4]), "+f"(d[5]), "+f"(d[6]), "+f"(d[7]), "+f"(d[8]), "+f"(d[9]), "+f"(d[10]), "+f"(d[11]), "+f"(d[12]), "+f"(d[13]), "+f"(d[14]), "+f"(d[15]), "+f"(d[16]), "+f"(d[17]), "+f"(d[18]), "+f"(d[19]), "+f"(d[20]), "+f"(d[21]), "+f"(d[22]), "+f"(d[23]), "+f"(d[24]), "+f"(d[25]), "+f"(d[26]), "+f"(d[27]), "+f"(d[28]), "+f"(d[29]), "+f"(d[30]), "+f"(d[31])
    : "r"(a0), "r"(a1), "r"(a2), "r"(a3), "r"(b), "n"(BHI));
}
template<uint32_t BHI> __device__ __forceinline__ void wg_rs_z_n64(float* d, uint32_t a0, uint32_t a1, uint32_t a2, uint32_t a3, uint32_t b) {
  asm volatile("{\n.reg .pred p;\n.reg .b64 db;\nsetp.ne.b32 p, 0, 0;\nmov.b64 db, {%36, %37};\n"
    "wgmma.mma_async.sync.aligned.m64n64k16.f32.bf16.bf16 {%0, %1, %2, %3, %4, %5, %6, %7, %8, %9, %10, %11, %12, %13, %14, %15, %16, %17, %18, %19, %20, %21, %22, %23, %24, %25, %26, %27, %28, %29, %30, %31}, {%32, %33, %34, %35}, db, p, 1, 1, 0;\n}\n"
    : "=f"(d[0]), "=f"(d[1]), "=f"(d[2]), "=f"(d[3]), "=f"(d[4]), "=f"(d[5]), "=f"(d[6]), "=f"(d[7]), "=f"(d[8]), "=f"(d[9]), "=f"(d[10]), "=f"(d[11]), "=f"(d[12]), "=f"(d[13]), "=f"(d[14]), "=f"(d[15]), "=f"(d[16]), "=f"(d[17]), "=f"(d[18]), "=f"(d[19]), "=f"(d[20]), "=f"(d[21]), "=f"(d[22]), "=f"(d[23]), "=f"(d[24]), "=f"(d[25]), "=f"(d[26]), "=f"(d[27]), "=f"(d[28]), "=f"(d[29]), "=f"(d[30]), "=f"(d[31])
    : "r"(a0), "r"(a1), "r"(a2), "r"(a3), "r"(b), "n"(BHI));
}
template<uint32_t BHI> __device__ __forceinline__ void wg_rs_n24(float* d, uint32_t a0, uint32_t a1, uint32_t a2, uint32_t a3, uint32_t b) {
  asm volatile("{\n.reg .pred p;\n.reg .b64 db;\nsetp.ne.b32 p, 1, 0;\nmov.b64 db, {%16, %17};\n"
    "wgmma.mma_async.sync.aligned.m64n24k16.f32.bf16.bf16 {%0, %1, %2, %3, %4, %5, %6, %7, %8, %9, %10, %11}, {%12, %13, %14, %15}, db, p, 1, 1, 1;\n}\n"
    : "+f"(d[0]), "+f"(d[1]), "+f"(d[2]), "+f"(d[3]), "+f"(d[4]), "+f"(d[5]), "+f"(d[6]), "+f"(d[7]), "+f"(d[8]), "+f"(d[9]), "+f"(d[10]), "+f"(d[11])
    : "r"(a0), "r"(a1), "r"(a2), "r"(a3), "r"(b), "n"(BHI));
}
template<uint32_t BHI> __device__ __forceinline__ void wg_rs_z_n24(float* d, uint32_t a0, uint32_t a1, uint32_t a2, uint32_t a3, uint32_t b) {
  asm volatile("{\n.reg .pred p;\n.reg .b64 db;\nsetp.ne.b32 p, 0, 0;\nmov.b64 db, {%16, %17};\n"
    "wgmma.mma_async.sync.aligned.m64n24k16.f32.bf16.bf16 {%0, %1, %2, %3, %4, %5, %6, %7, %8, %9, %10, %11}, {%12, %13, %14, %15}, db, p, 1, 1, 1;\n}\n"
    : "=f"(d[0]), "=f"(d[1]), "=f"(d[2]), "=f"(d[3]), "=f"(d[4]), "=f"(d[5]), "=f"(d[6]), "=f"(d[7]), "=f"(d[8]), "=f"(d[9]), "=f"(d[10]), "=f"(d[11])
    : "r"(a0), "r"(a1), "r"(a2), "r"(a3), "r"(b), "n"(BHI));
}

__device__ __forceinline__ void wg_fence() { asm volatile("wgmma.fence.sync.aligned;" ::: "memory"); }
__device__ __forceinline__ void wg_commit() { asm volatile("wgmma.commit_group.sync.aligned;" ::: "memory"); }
template <int N> __device__ __forceinline__ void wg_wait() { asm volatile("wgmma.wait_group.sync.aligned %0;" ::"n"(N) : "memory"); }
template <int R> __device__ __forceinline__ void pin(float* d) {
#pragma unroll
  for (int i = 0; i < R; i++) asm volatile("" : "+f"(d[i])::"memory");
}
template <int R> __device__ __forceinline__ void pin(uint32_t* d) {
#pragma unroll
  for (int i = 0; i < R; i++) asm volatile("" : "+r"(d[i])::"memory");
}
__device__ __forceinline__ float ex2(float x) { float y; asm("ex2.approx.ftz.f32 %0, %1;" : "=f"(y) : "f"(x)); return y; }
__device__ __forceinline__ float tanh_fast(float x) { float y; asm("tanh.approx.f32 %0, %1;" : "=f"(y) : "f"(x)); return y; }
__device__ __forceinline__ uint32_t pack(float lo, float hi) { uint32_t r; asm("cvt.rn.bf16x2.f32 %0, %1, %2;" : "=r"(r) : "f"(hi), "f"(lo)); return r; }
__device__ __forceinline__ float bf_lo(uint32_t v) { return __uint_as_float(v << 16); }
__device__ __forceinline__ float bf_hi(uint32_t v) { return __uint_as_float(v & 0xffff0000u); }
__device__ __forceinline__ float bf_round(float x) { return bf_lo(pack(x, 0.f)); }

__device__ __forceinline__ void mbar_init(uint32_t bar, uint32_t cnt) { asm volatile("mbarrier.init.shared::cta.b64 [%0], %1;" ::"r"(bar), "r"(cnt) : "memory"); }
__device__ __forceinline__ void mbar_expect(uint32_t bar, uint32_t bytes) { asm volatile("mbarrier.arrive.expect_tx.shared::cta.b64 _, [%0], %1;" ::"r"(bar), "r"(bytes) : "memory"); }
__device__ __forceinline__ void mbar_arrive(uint32_t bar) { asm volatile("mbarrier.arrive.shared::cta.b64 _, [%0];" ::"r"(bar) : "memory"); }
__device__ __forceinline__ void mbar_wait(uint32_t bar, uint32_t parity) {
  asm volatile(
      "{\n.reg .pred p;\n.reg .u32 c;\n"
      "mbarrier.try_wait.parity.shared::cta.b64 p, [%0], %1;\n"
      "@p bra.uni DONE;\n"
      "mov.u32 c, 0;\n"
      "LOOP:\n"
      "mbarrier.try_wait.parity.shared::cta.b64 p, [%0], %1;\n"
      "@p bra.uni DONE;\n"
      "add.u32 c, c, 1;\n"
      "setp.lt.u32 p, c, 0x4000000;\n"
      "@p bra.uni LOOP;\n"
      "trap;\n"
      "DONE:\n}\n" ::"r"(bar), "r"(parity) : "memory");
}
__device__ __forceinline__ uint32_t mbar_test(uint32_t bar, uint32_t parity) {
  uint32_t ok;
  asm volatile("{\n.reg .pred p;\nmbarrier.test_wait.parity.shared::cta.b64 p, [%1], %2;\nselp.u32 %0, 1, 0, p;\n}\n" : "=r"(ok) : "r"(bar), "r"(parity) : "memory");
  return ok;
}
__device__ __forceinline__ void mbar_arrive_if(uint32_t bar, uint32_t cond) {
  asm volatile("{\n.reg .pred p;\nsetp.ne.u32 p, %1, 0;\n@p mbarrier.arrive.shared::cta.b64 _, [%0];\n}\n" ::"r"(bar), "r"(cond) : "memory");
}
__device__ __forceinline__ uint32_t bsub2(uint32_t a, uint32_t b) { uint32_t d; asm("sub.rn.bf16x2 %0, %1, %2;" : "=r"(d) : "r"(a), "r"(b)); return d; }
__device__ __forceinline__ uint32_t bscale2(uint32_t d, uint32_t hi, uint32_t lo) {
  uint32_t t, r;
  asm("mul.rn.bf16x2 %0, %1, %2;" : "=r"(t) : "r"(d), "r"(lo));
  asm("fma.rn.bf16x2 %0, %1, %2, %3;" : "=r"(r) : "r"(d), "r"(hi), "r"(t));
  return r;
}
__device__ __forceinline__ void flag_wait(const uint32_t* f, uint32_t target) {
  asm volatile(
      "{\n.reg .pred p;\n.reg .u32 c, v;\n"
      "mov.u32 c, 0;\n"
      "LOOP:\n"
      "ld.acquire.gpu.global.u32 v, [%0];\n"
      "setp.ge.u32 p, v, %1;\n"
      "@p bra DONE;\n"
      "add.u32 c, c, 1;\n"
      "setp.lt.u32 p, c, 0x1000000;\n"
      "@p bra LOOP;\n"
      "trap;\n"
      "DONE:\n}\n" ::"l"(f), "r"(target) : "memory");
}
__device__ __forceinline__ uint32_t flag_wait_v(const uint32_t* f, uint32_t target) {
  uint32_t v;
  asm volatile(
      "{\n.reg .pred p;\n.reg .u32 c;\n"
      "mov.u32 c, 0;\n"
      "LOOP:\n"
      "ld.acquire.gpu.global.u32 %0, [%1];\n"
      "setp.ge.u32 p, %0, %2;\n"
      "@p bra DONE;\n"
      "add.u32 c, c, 1;\n"
      "setp.lt.u32 p, c, 0x1000000;\n"
      "@p bra LOOP;\n"
      "trap;\n"
      "DONE:\n}\n" : "=&r"(v) : "l"(f), "r"(target) : "memory");
  return v;
}
__device__ __forceinline__ float rcp_fast(float x) { float y; asm("rcp.approx.ftz.f32 %0, %1;" : "=f"(y) : "f"(x)); return y; }
__device__ __forceinline__ void ldsm4(uint32_t* v, uint32_t addr) {
  asm volatile("ldmatrix.sync.aligned.m8n8.x4.shared.b16 {%0,%1,%2,%3}, [%4];" : "=r"(v[0]), "=r"(v[1]), "=r"(v[2]), "=r"(v[3]) : "r"(addr) : "memory");
}
__device__ __forceinline__ void stsm4(uint32_t addr, uint32_t a, uint32_t b, uint32_t c, uint32_t d) {
  asm volatile("stmatrix.sync.aligned.m8n8.x4.shared.b16 [%0], {%1,%2,%3,%4};" ::"r"(addr), "r"(a), "r"(b), "r"(c), "r"(d) : "memory");
}
__device__ __forceinline__ void flag_add(uint32_t* f) { asm volatile("red.relaxed.gpu.global.add.u32 [%0], 1;" ::"l"(f) : "memory"); }
__device__ __forceinline__ void fence_gpu() { asm volatile("fence.acq_rel.gpu;" ::: "memory"); }
__device__ __forceinline__ void fence_async() { asm volatile("fence.proxy.async;" ::: "memory"); }
__device__ __forceinline__ void tma2d(uint32_t dst, const CUtensorMap* tm, uint32_t bar, int c0, int c1) {
  asm volatile("cp.async.bulk.tensor.2d.shared::cluster.global.mbarrier::complete_tx::bytes [%0], [%1, {%3, %4}], [%2];" ::"r"(dst), "l"(tm), "r"(bar), "r"(c0), "r"(c1) : "memory");
}
__device__ __forceinline__ void tma5d(uint32_t dst, const CUtensorMap* tm, uint32_t bar, int c0, int c4) {
  asm volatile("cp.async.bulk.tensor.5d.shared::cluster.global.mbarrier::complete_tx::bytes [%0], [%1, {%3, %5, %5, %5, %4}], [%2];" ::"r"(dst), "l"(tm), "r"(bar), "r"(c0), "r"(c4), "r"(0) : "memory");
}
__device__ __forceinline__ void tma3d(uint32_t dst, const CUtensorMap* tm, uint32_t bar, int c0, int c2) {
  asm volatile("cp.async.bulk.tensor.3d.shared::cluster.global.mbarrier::complete_tx::bytes [%0], [%1, {%3, %5, %4}], [%2];" ::"r"(dst), "l"(tm), "r"(bar), "r"(c0), "r"(c2), "r"(0) : "memory");
}
__device__ __forceinline__ void bulk_g2s(uint32_t dst, const void* src, uint32_t bytes, uint32_t bar) {
  asm volatile("cp.async.bulk.shared::cluster.global.mbarrier::complete_tx::bytes [%0], [%1], %2, [%3];" ::"r"(dst), "l"(src), "r"(bytes), "r"(bar) : "memory");
}
__device__ __forceinline__ void pf3d(const CUtensorMap* tm, int c0, int c2) {
  asm volatile("cp.async.bulk.prefetch.tensor.3d.L2.global [%0, {%1, %3, %2}];" ::"l"(tm), "r"(c0), "r"(c2), "r"(0) : "memory");
}
__device__ __forceinline__ void pf2d(const CUtensorMap* tm, int c0, int c1) {
  asm volatile("cp.async.bulk.prefetch.tensor.2d.L2.global [%0, {%1, %2}];" ::"l"(tm), "r"(c0), "r"(c1) : "memory");
}
__device__ __forceinline__ void pf5d(const CUtensorMap* tm, int c0, int c4) {
  asm volatile("cp.async.bulk.prefetch.tensor.5d.L2.global [%0, {%1, %3, %3, %3, %2}];" ::"l"(tm), "r"(c0), "r"(c4), "r"(0) : "memory");
}

struct Att {
  float s[32];
  float o[12];
  uint32_t p[16];
  uint32_t q[8];
};

__device__ __forceinline__ void attn_slow_rows(int cta, int j, int hp, int lrow_base, int tid_base) {
  const int lane = threadIdx.x & 31;
  const uint32_t* kv = g_KV + (size_t)(4 * j + hp) * SEQ * 20;
#pragma unroll 1
  for (int r = 0; r < 16; r++) {
    float q[18], acc[18];
#pragma unroll
    for (int v = 0; v < 9; v++) {
      uint32_t u = g_Q[(((cta * 4 + hp) * 2 + (v >> 3)) * 256 + tid_base + (r & 7) * 4 + ((v + hp) & 3)) * 4 + 2 * ((v >> 2) & 1) + (r >> 3)];
      q[2 * v] = bf_lo(u); q[2 * v + 1] = bf_hi(u);
      acc[2 * v] = 0.f; acc[2 * v + 1] = 0.f;
    }
    float mx = -INFINITY, l = 0.f;
#pragma unroll 1
    for (int key = lane; key < SEQ; key += 32) {
      const uint32_t* kr = kv + (key >> 3) * 160 + (key & 7) * 4;
      float s = 0.f;
#pragma unroll
      for (int v = 0; v < 9; v++) {
        uint32_t u = kr[(v >> 2) * 32 + ((v + hp) & 3)];
        s = fmaf(q[2 * v], bf_lo(u), s); s = fmaf(q[2 * v + 1], bf_hi(u), s);
      }
      float mn = fmaxf(mx, s), c = exp2f(mx - mn), p = exp2f(s - mn);
      mx = mn; l = l * c + p;
#pragma unroll
      for (int v = 0; v < 9; v++) {
        uint32_t u = v < 8 ? kr[(3 + (v >> 2)) * 32 + (v & 3)] : kr[2 * 32 + ((hp + 2) & 3)];
        acc[2 * v] = fmaf(p, bf_lo(u), acc[2 * v] * c); acc[2 * v + 1] = fmaf(p, bf_hi(u), acc[2 * v + 1] * c);
      }
    }
    float gm = mx;
#pragma unroll
    for (int d = 16; d; d >>= 1) gm = fmaxf(gm, __shfl_xor_sync(0xffffffffu, gm, d));
    float c = exp2f(mx - gm);
    l *= c;
#pragma unroll
    for (int d = 16; d; d >>= 1) l += __shfl_xor_sync(0xffffffffu, l, d);
    uint32_t* orow = g_O + cta * 9 * 512 + (lrow_base + r) * 4;
#pragma unroll
    for (int v = 0; v < 9; v++) {
      float a = acc[2 * v] * c, b = acc[2 * v + 1] * c;
#pragma unroll
      for (int d = 16; d; d >>= 1) { a += __shfl_xor_sync(0xffffffffu, a, d); b += __shfl_xor_sync(0xffffffffu, b, d); }
      if (lane == 0) orow[v < 8 ? (2 * hp + (v >> 2)) * 512 + (v & 3) : 8 * 512 + hp] = pack(2.f * (a / l), 2.f * (b / l));
    }
  }
}

__device__ __forceinline__ bool o_epilogue(float* o, uint32_t& x0, uint32_t& x1, int hp, uint32_t* odst, int lane) {
  const int src = (lane & ~3) | ((hp + 1) & 3);
  float l0 = __shfl_sync(0xffffffffu, o[0], src), l1 = __shfl_sync(0xffffffffu, o[2], src);
  float sa = 0.f;
#pragma unroll
  for (int i = 0; i < 12; i++) sa += fabsf(o[i]);
  bool ok = (l0 <= 1.329228e36f) && (l1 <= 1.329228e36f) && (l0 > 0.f) && (l1 > 0.f) && (sa <= 3.0e38f);
  float i0 = 2.f * rcp_fast(l0), i1 = 2.f * rcp_fast(l1);
  uint32_t* d = odst + hp * 1024;
  d[0] = pack(o[4] * i0, o[5] * i0);
  d[32] = pack(o[6] * i1, o[7] * i1);
  d[512] = pack(o[8] * i0, o[9] * i0);
  d[544] = pack(o[10] * i1, o[11] * i1);
  if ((lane & 3) == ((hp + 2) & 3)) { x0 = pack(o[0] * i0, o[1] * i0); x1 = pack(o[2] * i1, o[3] * i1); }
  return __any_sync(0xffffffffu, !ok);
}

__device__ __forceinline__ void issue_pv(Att& a, uint32_t kdesc) {
  const uint32_t vdesc = kdesc + 192 + (LO_V - LO_K);
#pragma unroll
  for (int k = 0; k < 4; k++) wg_rs_n24<HI_V>(a.o, a.p[4 * k], a.p[4 * k + 1], a.p[4 * k + 2], a.p[4 * k + 3], vdesc + k * 48);
}
__device__ __forceinline__ void issue_att(Att& a, uint32_t kdesc) {
  issue_pv(a, kdesc);
  wg_rs_z_n64<HI_K>(a.s, a.q[0], a.q[1], a.q[2], a.q[3], kdesc);
  wg_rs_n64<HI_K>(a.s, a.q[4], a.q[5], a.q[6], a.q[7], kdesc + 16);
}
__device__ __forceinline__ void softmax_a(Att& a) {
#pragma unroll
  for (int i = 0; i < 9; i++) a.p[i] = pack(ex2(a.s[2 * i]), ex2(a.s[2 * i + 1]));
  a.s[18] = ex2(a.s[18]); a.s[19] = ex2(a.s[19]);
  pin<9>(a.p); pin<2>(a.s + 18);
}
__device__ __forceinline__ void softmax_b(Att& a) {
  a.p[9] = pack(a.s[18], a.s[19]);
#pragma unroll
  for (int i = 10; i < 16; i++) a.p[i] = pack(ex2(a.s[2 * i]), ex2(a.s[2 * i + 1]));
  pin<7>(a.p + 9);
}
__device__ __forceinline__ void first_tile(Att& a, int hp, int lane) {
  float m0 = fmaxf(a.s[0], a.s[1]), m1 = fmaxf(a.s[2], a.s[3]);
#pragma unroll
  for (int i = 4; i < 32; i += 4) { m0 = fmaxf(m0, fmaxf(a.s[i], a.s[i + 1])); m1 = fmaxf(m1, fmaxf(a.s[i + 2], a.s[i + 3])); }
  m0 = fmaxf(m0, __shfl_xor_sync(0xffffffffu, m0, 1)); m1 = fmaxf(m1, __shfl_xor_sync(0xffffffffu, m1, 1));
  m0 = fmaxf(m0, __shfl_xor_sync(0xffffffffu, m0, 2)); m1 = fmaxf(m1, __shfl_xor_sync(0xffffffffu, m1, 2));
  float n0 = -(m0 + MOFF), n1 = -(m1 + MOFF);
  float h0 = bf_round(n0), h1 = bf_round(n1);
  uint32_t e0 = pack(h0, n0 - h0), e1 = pack(h1, n1 - h1);
  n0 = h0 + bf_hi(e0); n1 = h1 + bf_hi(e1);
  if ((lane & 3) == ((hp + 1) & 3)) { a.q[4] = e0; a.q[5] = e1; }
#pragma unroll
  for (int i = 0; i < 32; i += 4) { a.s[i] += n0; a.s[i + 1] += n0; a.s[i + 2] += n1; a.s[i + 3] += n1; }
#pragma unroll
  for (int i = 0; i < 12; i++) a.o[i] = 0.f;
  pin<12>(a.o); pin<8>(a.q);
}
__device__ __forceinline__ void load_q(Att& a, int cta, int hp, int tid) {
  const uint4* src = reinterpret_cast<const uint4*>(g_Q) + (cta * 4 + hp) * 512 + tid;
  const uint4 u = __ldcg(src), v = __ldcg(src + 256);
  a.q[0] = u.x; a.q[1] = u.y; a.q[2] = u.z; a.q[3] = u.w; a.q[4] = v.x; a.q[5] = v.y; a.q[6] = v.z; a.q[7] = v.w;
}
__device__ __forceinline__ void h_epilogue(float* acc, __nv_bfloat16* dst) {
#pragma unroll
  for (int b = 0; b < 2; b++) {
    uint32_t w0[4], w1[4];
#pragma unroll
    for (int i = 0; i < 4; i++) {
      float h[4];
#pragma unroll
      for (int e = 0; e < 4; e++) {
        float g = acc[(4 * b + i) * 4 + e], u = acc[32 + (4 * b + i) * 4 + e];
        h[e] = fmaf(tanh_fast(0.5f * g), u, u);
      }
      w0[i] = pack(h[0], h[1]); w1[i] = pack(h[2], h[3]);
    }
    *reinterpret_cast<uint4*>(dst + 32 * b) = make_uint4(w0[0], w0[1], w0[2], w0[3]);
    *reinterpret_cast<uint4*>(dst + 32 * b + 8 * FF) = make_uint4(w1[0], w1[1], w1[2], w1[3]);
  }
}

__device__ __forceinline__ uint32_t tagged(float a, float b, uint32_t tag) { return (pack(a, b) & ~1u) | tag; }
__device__ __forceinline__ void final_exchange(const float* acc, const Params& prm, int m, int hh, int q, int tid, uint32_t tag) {
  uint4* grp = g_P + (size_t)(m * 2 + hh) * 16 * 5 * 256;
#pragma unroll
  for (int a = 1; a < 4; a++) {
    uint4* pw = grp + ((q * 4 + ((q + a) & 3)) * 5) * 256 + tid;
#pragma unroll
    for (int i = 0; i < 4; i++) {
      const float* v = acc + 32 * a + 8 * i;
      asm volatile("st.relaxed.gpu.global.v4.b32 [%0], {%1,%2,%3,%4};" ::"l"(pw + i * 256), "r"(tagged(v[0], v[1], tag)), "r"(tagged(v[2], v[3], tag)),
                   "r"(tagged(v[4], v[5], tag)), "r"(tagged(v[6], v[7], tag)) : "memory");
    }
  }
#pragma unroll
  for (int d = 0; d < 4; d++) {
    const float* v = acc + 128 + 8 * (d & 1) + 2 * (d >> 1);
    asm volatile("st.relaxed.gpu.global.v2.b32 [%0], {%1,%2};" ::"l"(reinterpret_cast<uint2*>(grp + ((q * 4 + d) * 5 + 4) * 256) + tid),
                 "r"(tagged(v[0], v[1], tag)), "r"(tagged(v[4], v[5], tag)) : "memory");
  }
  const size_t off = (size_t)(128 * m + (tid >> 5) * 16 + ((tid & 31) >> 2)) * DM + 288 * hh + 2 * (tid & 3);
  const size_t off2 = off + 256 + 16 * (q & 1) + (size_t)(q >> 1) * 8 * DM;
  const uint32_t* xr = reinterpret_cast<const uint32_t*>(prm.x + off + 64 * q);
  const uint32_t* xr2 = reinterpret_cast<const uint32_t*>(prm.x + off2);
  uint32_t xv[18];
#pragma unroll
  for (int i = 0; i < 8; i++) { xv[2 * i] = __ldg(xr + 4 * i); xv[2 * i + 1] = __ldg(xr + 4 * i + 8 * (DM / 2)); }
  xv[16] = __ldg(xr2); xv[17] = __ldg(xr2 + 4);
  float own[4];
#pragma unroll
  for (int e = 0; e < 4; e++) {
    const int o = 128 + (e & 1) + 4 * (e >> 1);
    const float s0 = (q & 2) ? acc[o + 2] : acc[o], s1 = (q & 2) ? acc[o + 10] : acc[o + 8];
    own[e] = (q & 1) ? s1 : s0;
  }
  uint32_t v[3][18];
  uint32_t tries = 0;
  while (true) {
    uint32_t all = 1, any = 0;
#pragma unroll
    for (int d = 0; d < 3; d++)
      asm volatile("ld.relaxed.gpu.global.v2.b32 {%0,%1}, [%2];" : "=r"(v[d][16]), "=r"(v[d][17])
                   : "l"(reinterpret_cast<const uint2*>(grp + ((((q + 1 + d) & 3) * 4 + q) * 5 + 4) * 256) + tid) : "memory");
#pragma unroll
    for (int d = 0; d < 3; d++) { all &= v[d][16] & v[d][17]; any |= v[d][16] | v[d][17]; }
    if (__all_sync(0xffffffffu, ((tag ? all : ~any) & 1) != 0)) {
#pragma unroll
      for (int d = 0; d < 3; d++)
#pragma unroll
        for (int i = 0; i < 4; i++)
          asm volatile("ld.relaxed.gpu.global.v4.b32 {%0,%1,%2,%3}, [%4];" : "=r"(v[d][4 * i]), "=r"(v[d][4 * i + 1]), "=r"(v[d][4 * i + 2]), "=r"(v[d][4 * i + 3])
                       : "l"(grp + ((((q + 1 + d) & 3) * 4 + q) * 5 + i) * 256 + tid) : "memory");
#pragma unroll
      for (int d = 0; d < 3; d++)
#pragma unroll
        for (int i = 0; i < 16; i++) { all &= v[d][i]; any |= v[d][i]; }
      if (__all_sync(0xffffffffu, ((tag ? all : ~any) & 1) != 0)) break;
    }
    if (++tries > 0x400000u) asm volatile("trap;");
  }
  uint32_t r[18];
#pragma unroll
  for (int i = 0; i < 18; i++) {
    const float lo = (i < 16 ? acc[2 * i] : own[2 * (i - 16)]) + ((bf_lo(v[0][i]) + bf_lo(v[1][i])) + bf_lo(v[2][i]));
    const float hi = (i < 16 ? acc[2 * i + 1] : own[2 * (i - 16) + 1]) + ((bf_hi(v[0][i]) + bf_hi(v[1][i])) + bf_hi(v[2][i]));
    r[i] = pack(fmaf(lo, 0.5f, bf_lo(xv[i])), fmaf(hi, 0.5f, bf_hi(xv[i])));
  }
  const bool odd = tid & 1;
  uint2* o2 = reinterpret_cast<uint2*>(reinterpret_cast<uint32_t*>(prm.out + off + 64 * q) + (odd ? 3 : 0));
#pragma unroll
  for (int i = 0; i < 4; i++)
#pragma unroll
    for (int rh = 0; rh < 2; rh++) {
      const uint32_t A = r[4 * i + rh], B = r[4 * i + 2 + rh];
      const uint32_t y = __shfl_xor_sync(0xffffffffu, odd ? A : B, 1);
      o2[4 * i + rh * 8 * (DM / 4)] = odd ? make_uint2(y, B) : make_uint2(A, y);
    }
  const uint32_t y = __shfl_xor_sync(0xffffffffu, odd ? r[16] : r[17], 1);
  *reinterpret_cast<uint2*>(reinterpret_cast<uint32_t*>(prm.out + off2) + (odd ? 3 : 0)) = odd ? make_uint2(y, r[17]) : make_uint2(r[16], y);
}

__global__ void __launch_bounds__(384, 1) fused_kernel(const __grid_constant__ Params prm) {
  extern __shared__ __align__(1024) uint8_t smem[];
  const uint32_t sb = (uint32_t)__cvta_generic_to_shared(smem);
  const uint32_t bar = sb + SM_BAR;
  const int m = blockIdx.x & 15, j = blockIdx.x >> 4;
  const int cta = m * 8 + j;
  const int wr = __shfl_sync(0xffffffffu, (int)(threadIdx.x >> 5), 0);
  const int wg = wr >> 2;
  const int lane = threadIdx.x & 31;
  STAMP(0);
  if (wr == 8) {
    if (lane == 0) {
#pragma unroll
      for (int c = 0; c < 9; c++) mbar_init(bar + 8 * (B_X + c), 1);
      asm volatile("fence.proxy.async.shared::cta;" ::: "memory");
    }
    __syncwarp();
    asm volatile("bar.arrive 3, 384;" ::: "memory");
    if (lane < 9) {
      mbar_expect(bar + 8 * (B_X + lane), 16384);
      tma2d(sb + SM_XN + lane * 16384, &prm.xm, bar + 8 * (B_X + lane), 64 * lane, 128 * m);
    }
    __syncwarp();
    asm volatile("bar.sync 4, 64;" ::: "memory");
  } else {
    if (threadIdx.x == 288) {
      if (sb & 1023) asm volatile("trap;");
#pragma unroll
      for (int i = 0; i < 3; i++) { mbar_init(bar + 8 * (B_QF + i), 1); mbar_init(bar + 8 * (B_QE + i), 8); mbar_init(bar + 8 * (B_GF + i), 1); mbar_init(bar + 8 * (B_GE + i), 8); mbar_init(bar + 8 * (B_KF + i), 1); mbar_init(bar + 8 * (B_KE + i), 8); }
#pragma unroll
      for (int i = 0; i < 5; i++) { mbar_init(bar + 8 * (B_BF + i), 1); mbar_init(bar + 8 * (B_BE + i), 8); }
      mbar_init(bar + 8 * B_SKV, 8); mbar_init(bar + 8 * B_SH, 8); mbar_init(bar + 8 * B_SO1, 8); mbar_init(bar + 8 * B_SO2, 8); mbar_init(bar + 8 * B_OL, 1);
      mbar_init(bar + 8 * B_NR, 4); mbar_init(bar + 8 * (B_NR + 1), 4);
      asm volatile("fence.proxy.async.shared::cta;" ::: "memory");
    }
    if (wr == 11 && lane < 6 && m < 9) pf2d((lane & 1) ? &prm.wqkv8 : &prm.wqkv64, 576 * (lane >> 1) + 72 * j + 64 * (lane & 1), 64 * m);
    __syncwarp();
    if (wr == 9) asm volatile("bar.arrive 4, 64;" ::: "memory");
    asm volatile("bar.sync 3, 384;" ::: "memory");
  }

  if (wg == 2) {
    asm volatile("setmaxnreg.dec.sync.aligned.u32 24;");
    const int pw = wr & 3;
    if (lane == 0) {
      if (pw == 0) {
#pragma unroll 1
        for (int kb = 0; kb < 9; kb++) {
          const int s = kb % 3;
          if (kb >= 3) mbar_wait(bar + 8 * (B_QE + s), (kb / 3 - 1) & 1);
          const uint32_t fb = bar + 8 * (B_QF + s), dst = sb + SM_RING + s * QST;
          mbar_expect(fb, QST);
#pragma unroll
          for (int p = 0; p < 3; p++) {
            tma2d(dst + p * 8192, &prm.wqkv64, fb, 576 * p + 72 * j, 64 * kb);
            tma2d(dst + 24576 + p * 1024, &prm.wqkv8, fb, 576 * p + 72 * j + 64, 64 * kb);
          }
        }
        int col = 576 * j, kr = 0, slot = 0, ph = 1;
#pragma unroll 1
        for (int s = 0; s < 108; s++) {
          if (s >= 5) mbar_wait(bar + 8 * (B_BE + slot), ph);
          else if (!(s & 1)) mbar_wait(bar + 8 * (B_QE + (s >> 1)), 0);
          const uint32_t fb = bar + 8 * (B_BF + slot), dst = sb + SM_RING + slot * BST;
          mbar_expect(fb, BST);
          tma2d(dst, &prm.wg, fb, col, kr);
          tma2d(dst + 6144, &prm.wu, fb, col, kr);
          if ((kr += 48) == 576) { kr = 0; col += 64; }
          if (++slot == 5) { slot = 0; ph ^= 1; }
        }
        mbar_arrive(bar + 8 * (B_BF + 3));
        const int hh = j & 1;
#define ACOL(A) ((A) < 4 ? 64 * (((j >> 1) + (A)) & 3) : 256)
        uint32_t seen = 0;
#pragma unroll 1
        for (int b = 0; b < 20; b++) {
          const int st = b % 3;
          if (b >= 3) mbar_wait(bar + 8 * (B_GE + st), (b / 3 - 1) & 1);
          else if (b == 1) mbar_wait(bar + 8 * (B_BE + 0), 1);
          else if (b == 2) mbar_wait(bar + 8 * (B_BE + 2), 1);
          const uint32_t fb = bar + 8 * (B_GF + st), dst = sb + st * G2ST;
          if (b == 0) STAMPW(16);
          if (b < 18) {
            mbar_expect(fb, G2ST);
            const int own = (b < 8 || b == 16), tile = b < 16 ? (b & 7) : 8;
            const int jj = own ? j : (j ^ 1);
            const int kc = 576 * jj + 64 * tile;
            if (b == 8 || b >= 16) seen = 0;
            if (seen <= tile) { seen = flag_wait_v(FLAG_H(m * 8 + jj), tile + 1); fence_async(); }
            tma2d(dst, &prm.h, fb, kc, 128 * m);
#pragma unroll
            for (int a = 0; a < 5; a++) tma5d(dst + 16384 + a * 8192, &prm.wd[hh], fb, ACOL(a), kc >> 5);
          } else {
            mbar_expect(fb, 53248);
            bulk_g2s(dst + (b - 18) * 4096, g_O + ((cta & ~1) + b - 18) * 9 * 512 + (b - 18) * 1024, 12288, fb);
#pragma unroll
            for (int a = 0; a < 5; a++) tma3d(dst + 16384 + a * 8192, &prm.wo[hh], fb, ACOL(a), 4 * ((j & 6) + b - 18));
          }
          if (b == 3) {
            mbar_expect(bar + 8 * B_OL, 10240 + 12288);
#pragma unroll
            for (int a = 0; a < 5; a++) tma3d(sb + SM_W16 + a * 2048, &prm.wo16[hh], bar + 8 * B_OL, ACOL(a), 4 * (j & 6));
          }
          if (b == 17) { flag_wait(FLAG_O(cta), 1); flag_wait(FLAG_O(cta ^ 1), 1); fence_async(); }
          if (b == 0) STAMPW(17);
        }
      } else if (pw == 1) {
        flag_wait(FLAG_KV(j), 16);
        fence_async();
        STAMPW(18);
        int slot = 0, ph = 1, vrow = 0;
        const int hx = (j & 1) * 3;
#pragma unroll 1
        for (int u = 0; u <= 128; u++) {
          if (u >= 3) mbar_wait(bar + 8 * (B_KE + slot), ph);
          const uint32_t fb = bar + 8 * (B_KF + slot), dst = sb + SM_KV + slot * KVST;
          const int krow = (4 * j + ((u >> 5) ^ hx)) * 256 + ((u + 2 * m) & 31) * 8;
          if (u == 0) vrow = krow;
          mbar_expect(fb, u < 128 ? KVST : KVST / 2);
          if (u < 128) tma2d(dst, &prm.kv, fb, 0, krow);
          tma2d(dst + 3072, &prm.kv, fb, 128, vrow);
          vrow = krow;
          if (++slot == 3) { slot = 0; ph ^= 1; }
        }
#pragma unroll 1
        for (int e = 0; e < 2; e++) {
          const int r = (cta & 1) ^ e;
          const uint32_t* src = g_O + ((cta & ~1) + r) * 9 * 512;
          flag_wait(FLAG_O((cta & ~1) + r), 2);
          fence_async();
          bulk_g2s(sb + r * G2ST + (r ? 0 : 12288), src + (r ? 0 : 3072), 4096, bar + 8 * B_OL);
          bulk_g2s(sb + SM_OL + r * 2048, src + 4096, 2048, bar + 8 * B_OL);
        }
        STAMPW(19);
      } else if (pw == 2) {
        mbar_wait(bar + 8 * B_SKV, 0);
        STAMPW(22);
        fence_gpu(); flag_add(FLAG_KV(j));
        STAMPW(20);
#pragma unroll 1
        for (int t = 0; t < 9; t++) { mbar_wait(bar + 8 * B_SH, t & 1); fence_gpu(); flag_add(FLAG_H(cta)); }
        mbar_wait(bar + 8 * B_SO1, 0);
        fence_gpu(); flag_add(FLAG_O(cta));
        mbar_wait(bar + 8 * B_SO2, 0);
        fence_gpu(); flag_add(FLAG_O(cta));
        STAMPW(21);
      } else {
        mbar_wait(bar + 8 * (B_X + 8), 0);
#pragma unroll 1
        for (int b = m; b < 216; b += 16) {
          const int s = b >> 1;
          pf2d((b & 1) ? &prm.wu : &prm.wg, 576 * j + 64 * (s / 12), 48 * (s % 12));
        }
        mbar_wait(bar + 8 * B_SH, 0);
#pragma unroll 1
        for (int b = m; b < 90; b += 16) pf5d(&prm.wd[j & 1], 64 * (b % 5), 36 * (j >> 1) + 2 * (b / 5));
        if (m < 10) pf3d(&prm.wo[j & 1], 64 * (m % 5), 4 * ((j & 6) + m / 5));
        else if (m < 15) pf3d(&prm.wo16[j & 1], 64 * (m % 5), 4 * (j & 6));
      }
    }
  } else {
    const int tid = threadIdx.x;
    const int t = lane & 3;
    const int row0 = 128 * m + 16 * wr + (lane >> 2);
    const uint32_t l0 = lane == 0;
    const uint32_t adesc = (((sb + SM_XN + wg * 8192) & 0x3FFFF) >> 4) | LO_A;
    const uint32_t bdesc = (((sb + SM_RING) & 0x3FFFF) >> 4) | LO_B48;
    const uint32_t kdesc0 = (((sb + SM_KV) & 0x3FFFF) >> 4) | LO_K;
    const int hx = (j & 1) * 3;
    float accA[64], accB[64];
    Att a;
    uint32_t badmask = 0;
#define AOFF(K) ((K) * 2 + ((K) >> 2) * 1016)
#define G1_ISSUE(ACC, I) _Pragma("unroll") for (int k = 0; k < 3; k++) wg_ss_n128<HI_SW128, HI_SW128>(ACC, adesc + AOFF(3 * (I) + k), bdesc + bslot * 768 + k * 128);
#define G1_ISSUE_Z(ACC)                                                                                        \
  wg_ss_z_n128<HI_SW128, HI_SW128>(ACC, adesc, bdesc + bslot * 768);                                           \
  _Pragma("unroll") for (int k = 1; k < 3; k++) wg_ss_n128<HI_SW128, HI_SW128>(ACC, adesc + k * 2, bdesc + bslot * 768 + k * 128);
    uint32_t bslot = 0, bph = 0, bprev = 0;
#define B_ADVANCE() { bprev = bslot; if (++bslot == 5) { bslot = 0; bph ^= 1; } }
    {
      const int lr = wr * 16 + (lane & 15);
      uint32_t ra[4];
#pragma unroll
      for (int k = 0; k < 4; k++) ra[k] = sb + SM_XN + lr * 128 + (((2 * k + (lane >> 4)) ^ (lr & 7)) << 4);
      float pv0 = 0.f, pv1 = 0.f, s0 = 0.f, s1 = 0.f, s2 = 0.f, s3 = 0.f, q0 = 0.f, q1 = 0.f, q2 = 0.f, q3 = 0.f;
#pragma unroll 1
      for (int c = 0; c < 9; c++) {
        mbar_wait(bar + 8 * (B_X + c), 0);
        uint32_t v[4][4];
#pragma unroll
        for (int k = 0; k < 4; k++) ldsm4(v[k], ra[k] + c * 16384);
        if (c == 0) { pv0 = __shfl_sync(0xffffffffu, bf_lo(v[0][0]), lane & ~3); pv1 = __shfl_sync(0xffffffffu, bf_lo(v[0][1]), lane & ~3); }
#pragma unroll
        for (int k = 0; k < 4; k++)
#pragma unroll
          for (int e = 0; e < 4; e += 2) {
            const float x0 = bf_lo(v[k][e]) - pv0, x1 = bf_hi(v[k][e]) - pv0, y0 = bf_lo(v[k][e + 1]) - pv1, y1 = bf_hi(v[k][e + 1]) - pv1;
            s0 += x0; s1 += x1; s2 += y0; s3 += y1;
            q0 = fmaf(x0, x0, q0); q1 = fmaf(x1, x1, q1); q2 = fmaf(y0, y0, q2); q3 = fmaf(y1, y1, q3);
          }
      }
      STAMP(11);
      asm volatile("setmaxnreg.inc.sync.aligned.u32 240;");
      s0 += s1; s2 += s3; q0 += q1; q2 += q3;
#pragma unroll
      for (int d = 1; d < 4; d <<= 1) {
        s0 += __shfl_xor_sync(0xffffffffu, s0, d); s2 += __shfl_xor_sync(0xffffffffu, s2, d);
        q0 += __shfl_xor_sync(0xffffffffu, q0, d); q2 += __shfl_xor_sync(0xffffffffu, q2, d);
      }
      s0 *= (1.f / 576.f); s2 *= (1.f / 576.f);
      const float var0 = fmaxf(fmaf(q0, 1.f / 576.f, -s0 * s0), 0.f), var1 = fmaxf(fmaf(q2, 1.f / 576.f, -s2 * s2), 0.f);
      const float inv0 = 1.f / bf_round(sqrtf(bf_round(bf_round(var0) + 1e-5f))), inv1 = 1.f / bf_round(sqrtf(bf_round(bf_round(var1) + 1e-5f)));
      const uint32_t mb0 = pack(pv0 + s0, pv0 + s0), mb1 = pack(pv1 + s2, pv1 + s2);
      const uint32_t h0 = pack(inv0, inv0), h1 = pack(inv1, inv1);
      const uint32_t e0 = pack(inv0 - bf_lo(h0), inv0 - bf_lo(h0)), e1 = pack(inv1 - bf_lo(h1), inv1 - bf_lo(h1));
#define NORM_STORE(C)                                                                                          \
  {                                                                                                            \
    _Pragma("unroll") for (int k = 0; k < 4; k++)                                                              \
      stsm4(ra[k] + (C) * 16384, bscale2(bsub2(v[k][0], mb0), h0, e0), bscale2(bsub2(v[k][1], mb1), h1, e1),   \
            bscale2(bsub2(v[k][2], mb0), h0, e0), bscale2(bsub2(v[k][3], mb1), h1, e1));                       \
    asm volatile("fence.proxy.async.shared::cta;" ::: "memory");                                               \
    __syncwarp();                                                                                              \
    mbar_arrive_if(bar + 8 * B_NR + 8 * wg, l0);                                                               \
  }
      float aq[96], ar[12];
      {
        uint32_t v[4][4];
#pragma unroll
        for (int k = 0; k < 4; k++) ldsm4(v[k], ra[k]);
        NORM_STORE(0)
      }
#pragma unroll
      for (int i = 0; i < 96; i++) aq[i] = 0.f;
#pragma unroll
      for (int i = 0; i < 12; i++) ar[i] = 0.f;
      pin<96>(aq); pin<12>(ar);
      STAMP(1);
      const uint32_t qdesc = (((sb + SM_RING) & 0x3FFFF) >> 4) | LO_B;
      const uint32_t rdesc = (((sb + SM_RING + 24576) & 0x3FFFF) >> 4) | LO_R;
      uint32_t s = 0, ph = 0;
#pragma unroll 1
      for (int kb = 0; kb < 9; kb++) {
        uint32_t v[4][4];
        const int cn = kb < 8 ? kb + 1 : 8;
#pragma unroll
        for (int k = 0; k < 4; k++) ldsm4(v[k], ra[k] + cn * 16384);
        mbar_wait(bar + 8 * B_QF + 8 * s, ph);
        mbar_wait(bar + 8 * B_NR + 8 * wg, kb & 1);
        wg_fence();
#pragma unroll
        for (int k = 0; k < 4; k++) {
          wg_ss_n192<HI_SW128, HI_SW128>(aq, adesc + kb * 1024 + k * 2, qdesc + s * (QST >> 4) + k * 128);
          wg_ss_n24<HI_SW128, HI_R>(ar, adesc + kb * 1024 + k * 2, rdesc + s * (QST >> 4) + k * 16);
        }
        wg_commit();
        if (kb < 8) NORM_STORE(cn)
        wg_wait<1>();
        mbar_arrive_if(bar + 8 * B_QE + (s == 0 ? 16 : 8 * s - 8), l0 & (kb > 0));
        if (++s == 3) { s = 0; ph ^= 1; }
      }
      wg_wait<0>();
      pin<96>(aq); pin<12>(ar);
      mbar_arrive_if(bar + 8 * (B_QE + 2), l0);
      STAMP(2);
      uint32_t* kvp = g_KV + (size_t)(4 * j) * SEQ * 20 + (row0 >> 3) * 160 + lane;
      {
        uint32_t pk[2][9][2];
#pragma unroll
        for (int p = 0; p < 2; p++)
#pragma unroll
          for (int i = 0; i < 9; i++) {
            const float* src = i < 8 ? &aq[(8 * (p + 1) + i) * 4] : &ar[4 * (p + 1)];
            pk[p][i][0] = pack(src[0], src[1]); pk[p][i][1] = pack(src[2], src[3]);
          }
#pragma unroll
        for (int hp = 0; hp < 4; hp++) {
          const bool up = t < hp;
#pragma unroll
          for (int rh = 0; rh < 2; rh++) {
            uint32_t* d = kvp + hp * SEQ * 20 + rh * 160;
            d[0] = up ? pk[0][2 * hp + 1][rh] : pk[0][2 * hp][rh];
            d[32] = up ? pk[0][2 * hp + 2][rh] : pk[0][2 * hp + 1][rh];
            d[96 + ((t - hp) & 3) - t] = up ? pk[1][2 * hp + 1][rh] : pk[1][2 * hp][rh];
            d[128 + ((t - hp) & 3) - t] = up ? pk[1][2 * hp + 2][rh] : pk[1][2 * hp + 1][rh];
            const uint32_t v9 = __shfl_sync(0xffffffffu, pk[1][2 * hp + 2][rh], (lane & ~3) | hp);
            d[64] = t == hp ? pk[0][2 * hp + 2][rh] : t == ((hp + 1) & 3) ? 0x3f803f80u : t == ((hp + 2) & 3) ? v9 : 0u;
          }
        }
      }
      __syncwarp();
      mbar_arrive_if(bar + 8 * B_SKV, l0);
      STAMP(3);
      mbar_wait(bar + 8 * B_BF, 0);
      wg_fence();
      G1_ISSUE_Z(accA)
      wg_commit();
      B_ADVANCE()
      uint32_t pq[9][2];
#pragma unroll
      for (int i = 0; i < 9; i++) {
        const float* src = i < 8 ? &aq[i * 4] : &ar[0];
        pq[i][0] = pack(bf_round(src[0]) * QSCALE, bf_round(src[1]) * QSCALE); pq[i][1] = pack(bf_round(src[2]) * QSCALE, bf_round(src[3]) * QSCALE);
      }
      uint4* qp = reinterpret_cast<uint4*>(g_Q) + cta * 4 * 512 + tid;
#pragma unroll
      for (int hp = 0; hp < 4; hp++) {
        const bool up = t < hp;
        qp[hp * 512] = make_uint4(up ? pq[2 * hp + 1][0] : pq[2 * hp][0], up ? pq[2 * hp + 1][1] : pq[2 * hp][1],
                                                               up ? pq[2 * hp + 2][0] : pq[2 * hp + 1][0], up ? pq[2 * hp + 2][1] : pq[2 * hp + 1][1]);
        qp[hp * 512 + 256] = make_uint4(t == hp ? pq[2 * hp + 2][0] : 0u, t == hp ? pq[2 * hp + 2][1] : 0u, 0u, 0u);
      }
      load_q(a, cta, hx, tid);
#pragma unroll
      for (int i = 0; i < 16; i++) a.p[i] = 0;
#pragma unroll
      for (int i = 0; i < 12; i++) a.o[i] = 0.f;
      pin<16>(a.p); pin<12>(a.o);
    }
#pragma unroll 1
    for (int i = 1; i < NG0; i++) {
      mbar_wait(bar + 8 * B_BF + 8 * bslot, bph);
      wg_fence();
      G1_ISSUE(accA, i)
      wg_commit();
      wg_wait<1>();
      mbar_arrive_if(bar + 8 * B_BE + 8 * bprev, l0);
      B_ADVANCE()
    }
    pin<8>(a.q);
    STAMP(4);
    mbar_wait(bar + 8 * B_BF + 8 * bslot, bph);
    mbar_wait(bar + 8 * B_KF, 0);
    STAMP(23);
    uint32_t k8 = 0, kph = 0, kd = kdesc0;
    uint32_t it = 0;
    uint32_t ox0 = 0, ox1 = 0;
    bool early_o = false, special = true;
    __nv_bfloat16* hdst = g_H + (size_t)row0 * FF + 576 * j + 8 * t;
    uint32_t ao = adesc + AOFF(3 * NG0), a1 = adesc + AOFF(3 * NG0 + 1), a2 = adesc + AOFF(3 * NG0 + 2), bd = bdesc + bslot * 768;

#define ITEM_SWITCH()                                                                                          \
  if (__builtin_expect(special, 0)) {                                                                          \
    if (it & 1) {                                                                                              \
      load_q(a, cta, (((it >> 5) + 1) & 3) ^ hx, tid);                                                         \
    } else {                                                                                                   \
      pin<12>(a.o);                                                                                            \
      if (it != 0) badmask |= (uint32_t)o_epilogue(a.o, ox0, ox1, ((it >> 5) - 1) ^ hx, g_O + cta * 9 * 512 + wr * 64 + lane, lane) << (((it >> 5) - 1) ^ hx); \
      if (it == 96) { __syncwarp(); mbar_arrive_if(bar + 8 * B_SO1, l0 & (badmask == 0)); early_o = badmask == 0; } \
      first_tile(a, (it >> 5) ^ hx, lane);                                                                     \
    }                                                                                                          \
  }
#define KV_ADVANCE() { kd += 384; k8 += 8; if (k8 == 24) { k8 = 0; kd = kdesc0; kph ^= 1; } it++; special = ((it + 1) & 31) < 2; }
#define WAIT_UNLESS(OK, BA, PA, BB, PB) if (__builtin_expect(!__all_sync(0xffffffffu, OK), 0)) { mbar_wait(BA, PA); mbar_wait(BB, PB); }
#define EPI_STEP(ACCN, ACCO)                                                                                   \
  {                                                                                                            \
    wg_fence();                                                                                                \
    wg_ss_z_n128<HI_SW128, HI_SW128>(ACCN, adesc, bd);                                                         \
    wg_ss_n128<HI_SW128, HI_SW128>(ACCN, adesc + 2, bd + 128);                                                 \
    wg_ss_n128<HI_SW128, HI_SW128>(ACCN, adesc + 4, bd + 256);                                                 \
    wg_commit();                                                                                               \
    wg_wait<1>();                                                                                              \
    pin<64>(ACCO);                                                                                             \
    mbar_arrive_if(bar + 8 * B_BE + 8 * bprev, l0);                                                            \
    B_ADVANCE()                                                                                                \
    bd = bdesc + bslot * 768; ao = adesc + AOFF(3); a1 = adesc + AOFF(4); a2 = adesc + AOFF(5);                \
    const uint32_t ok = mbar_test(bar + 8 * B_BF + 8 * bslot, bph);                                            \
    h_epilogue(ACCO, hdst);                                                                                    \
    hdst += 64;                                                                                                \
    __syncwarp();                                                                                              \
    mbar_arrive_if(bar + 8 * B_SH, l0);                                                                        \
    WAIT_UNLESS(ok, bar + 8 * B_BF + 8 * bslot, bph, bar + 8 * B_BF + 8 * bslot, bph)                          \
  }
#define ATT_LOOP1(ACC)                                                                                         \
  do {                                                                                                         \
    wg_fence();                                                                                                \
    issue_att(a, kd);                                                                                          \
    wg_commit();                                                                                               \
    wg_ss_n128<HI_SW128, HI_SW128>(ACC, ao, bd);                                                               \
    wg_ss_n128<HI_SW128, HI_SW128>(ACC, a1, bd + 128);                                                         \
    wg_ss_n128<HI_SW128, HI_SW128>(ACC, a2, bd + 256);                                                         \
    wg_commit();                                                                                               \
    wg_wait<1>();                                                                                              \
    pin<32>(a.s);                                                                                              \
    mbar_arrive_if(bar + 8 * B_BE + 8 * bprev, l0);                                                            \
    mbar_arrive_if(bar + 8 * B_KE + k8, l0);                                                                   \
    ITEM_SWITCH()                                                                                              \
    B_ADVANCE()                                                                                                \
    KV_ADVANCE()                                                                                               \
    kk += 3;                                                                                                   \
    bd = bdesc + bslot * 768; ao = adesc + AOFF(kk); a1 = adesc + AOFF(kk + 1); a2 = adesc + AOFF(kk + 2);     \
    const uint32_t ok = mbar_test(bar + 8 * B_BF + 8 * bslot, bph) & mbar_test(bar + 8 * B_KF + k8, kph);      \
    softmax_a(a);                                                                                              \
    WAIT_UNLESS(ok, bar + 8 * B_BF + 8 * bslot, bph, bar + 8 * B_KF + k8, kph)                                 \
    softmax_b(a);                                                                                              \
    pin<8>(a.q);                                                                                               \
  } while (kk != 36);
    {
      uint32_t kk = 3 * NG0;
#pragma unroll 1
      for (int pr = 0;; pr++) {
        ATT_LOOP1(accA)
        if (pr == 4) break;
        EPI_STEP(accB, accA)
        kk = 3;
        ATT_LOOP1(accB)
        EPI_STEP(accA, accB)
        kk = 3;
      }
    }
    STAMP(5);
    wg_wait<0>();
    pin<64>(accA);
    mbar_arrive_if(bar + 8 * B_BE + 8 * bprev, l0);
    h_epilogue(accA, hdst);
    __syncwarp();
    mbar_arrive_if(bar + 8 * B_SH, l0);
    STAMP(6);
    mbar_wait(bar + 8 * B_GF, 0);
    STAMP(12);

    float acc2[144];
    const uint32_t a2desc = (((sb + wg * 8192) & 0x3FFFF) >> 4) | LO_A;
    const uint32_t b2desc = (((sb + 16384) & 0x3FFFF) >> 4) | LO_B;
    uint32_t g8 = 0, gph = 0, gprev = 0, h2 = 0, ad = a2desc, bd2 = b2desc;
#define G2_MMA(AHI, AD, BD, NOFF)                                                                              \
  wg_ss_n128<AHI, HI_SW128>(acc2, AD, BD);                                                                     \
  wg_ss_n160<AHI, HI_SW128>(acc2 + 64, AD, (BD) + (NOFF));
#define ATT_STEP2(ZERO)                                                                                        \
  {                                                                                                            \
    wg_fence();                                                                                                \
    issue_att(a, kd);                                                                                          \
    wg_commit();                                                                                               \
    if (ZERO) {                                                                                                \
      wg_ss_z_n128<HI_SW128, HI_SW128>(acc2, ad, bd2);                                                         \
      wg_ss_z_n160<HI_SW128, HI_SW128>(acc2 + 64, ad, bd2 + 1024);                                             \
    } else { G2_MMA(HI_SW128, ad, bd2, 1024) }                                                                 \
    G2_MMA(HI_SW128, ad + 2, bd2 + 128, 1024)                                                                  \
    wg_commit();                                                                                               \
    wg_wait<1>();                                                                                              \
    pin<32>(a.s);                                                                                              \
    mbar_arrive_if(bar + 8 * B_KE + k8, l0);                                                                   \
    if (!(ZERO)) { mbar_arrive_if(bar + 8 * B_GE + gprev, l0 & (h2 ^ 1)); ITEM_SWITCH() }                      \
    KV_ADVANCE()                                                                                               \
    if (h2) { gprev = g8; g8 += 8; if (g8 == 24) { g8 = 0; gph ^= 1; } }                                       \
    h2 ^= 1;                                                                                                   \
    ad = a2desc + g8 * 448 + h2 * 4; bd2 = b2desc + g8 * 448 + h2 * 256;                                       \
    const uint32_t ok = mbar_test(bar + 8 * B_GF + g8, gph) & mbar_test(bar + 8 * B_KF + k8, kph);             \
    softmax_a(a);                                                                                              \
    WAIT_UNLESS(ok, bar + 8 * B_GF + g8, gph, bar + 8 * B_KF + k8, kph)                                        \
    softmax_b(a);                                                                                              \
    pin<8>(a.q);                                                                                               \
  }
    static_assert(NG0 == 7, "tail code below assumes 35 GEMM2 slots");
    ATT_STEP2(true);
    do ATT_STEP2(false) while (it != 128);
    STAMP(7);
    wg_fence();
    issue_pv(a, kd);
    wg_commit();
    G2_MMA(HI_SW128, a2desc + 7168 + 4, b2desc + 7168 + 256, 1024)
    G2_MMA(HI_SW128, a2desc + 7168 + 6, b2desc + 7168 + 384, 1024)
    wg_commit();
    wg_wait<1>();
    pin<12>(a.o);
    {
      uint32_t* od = g_O + cta * 9 * 512 + wr * 64 + lane;
      badmask |= (uint32_t)o_epilogue(a.o, ox0, ox1, 3 ^ hx, od, lane) << (3 ^ hx);
      od += 4096 + ((t + 2) & 3) - t;
      od[0] = ox0; od[32] = ox1;
    }
    __syncwarp();
    mbar_arrive_if(bar + 8 * B_SO2, l0 & (badmask == 0));
    if (__builtin_expect(badmask != 0, 0)) {
      wg_wait<0>();
#pragma unroll 1
      for (int hp = 0; hp < 4; hp++)
        if ((badmask >> hp) & 1) attn_slow_rows(cta, j, hp, 16 * wr, tid & ~31);
      __syncwarp();
      mbar_arrive_if(bar + 8 * B_SO1, l0 & !early_o);
      mbar_arrive_if(bar + 8 * B_SO2, l0);
    }
    STAMP(8);
    const uint32_t odesc = (((sb + wg * 1024) & 0x3FFFF) >> 4) | LO_O;
    mbar_wait(bar + 8 * (B_GF + 0), 0);
    wg_fence();
#pragma unroll
    for (int k = 0; k < 3; k++) { G2_MMA(HI_O, odesc + k * 256, b2desc + k * 128, 1024) }
    wg_commit();
    mbar_wait(bar + 8 * (B_GF + 1), 0);
    wg_fence();
#pragma unroll
    for (int k = 1; k < 4; k++) { G2_MMA(HI_O, odesc + 3584 + k * 256, b2desc + 3584 + k * 128, 1024) }
    wg_commit();
    STAMP(13);
    const uint32_t tag = (*(volatile uint32_t*)FLAG_EPOCH + 1) & 1;
    mbar_wait(bar + 8 * B_OL, 0);
    STAMP(14);
    wg_fence();
    G2_MMA(HI_O, odesc + 768, b2desc + 384, 1024)
    G2_MMA(HI_O, odesc + 3584, b2desc + 3584, 1024)
    G2_MMA(HI_O, odesc + (SM_OL >> 4), (((sb + SM_W16) & 0x3FFFF) >> 4) | LO_B16, 256)
    wg_commit();
    int tid2, bid2;
    asm volatile("mov.u32 %0, %%tid.x;" : "=r"(tid2));
    asm volatile("mov.u32 %0, %%ctaid.x;" : "=r"(bid2));
    const int m2 = bid2 & 15, j2 = bid2 >> 4;
    wg_wait<0>();
    pin<144>(acc2);
    STAMP(9);
    final_exchange(acc2, prm, m2, j2 & 1, j2 >> 1, tid2, tag);
    STAMP(10);
    __syncwarp();
    if (lane == 0) {
      if (atomicInc(FLAG_DONE, NCTA * 8 - 1) == NCTA * 8 - 1) {
        for (int i = 0; i < 8; i++) *FLAG_KV(i) = 0;
        for (int i = 0; i < NCTA; i++) { *FLAG_H(i) = 0; *FLAG_O(i) = 0; }
        *FLAG_EPOCH = tag;
      }
    }
  }
}

typedef CUresult (*EncodeFn)(CUtensorMap*, CUtensorMapDataType, cuuint32_t, void*, const cuuint64_t*, const cuuint64_t*, const cuuint32_t*, const cuuint32_t*,
                             CUtensorMapInterleave, CUtensorMapSwizzle, CUtensorMapL2promotion, CUtensorMapFloatOOBfill);

void enc2d(EncodeFn enc, CUtensorMap* tm, const void* base, uint64_t w, uint64_t h, uint64_t pitch_elems, uint32_t bw, uint32_t bh, CUtensorMapSwizzle sw) {
  cuuint64_t dims[2] = {w, h}, str[1] = {pitch_elems * 2};
  cuuint32_t box[2] = {bw, bh}, es[2] = {1, 1};
  enc(tm, CU_TENSOR_MAP_DATA_TYPE_BFLOAT16, 2, const_cast<void*>(base), dims, str, box, es, CU_TENSOR_MAP_INTERLEAVE_NONE, sw,
      CU_TENSOR_MAP_L2_PROMOTION_L2_128B, CU_TENSOR_MAP_FLOAT_OOB_FILL_NONE);
}

}

extern "C" void kernel_launch(void* const* d_in, const int* in_sizes, int n_in, void* d_out, int out_size) {
  (void)in_sizes; (void)n_in; (void)out_size;
  const __nv_bfloat16* x = (const __nv_bfloat16*)d_in[0];
  const __nv_bfloat16* wqkv = (const __nv_bfloat16*)d_in[1];
  const __nv_bfloat16* wo = (const __nv_bfloat16*)d_in[2];
  const __nv_bfloat16* wg = (const __nv_bfloat16*)d_in[4];
  const __nv_bfloat16* wu = (const __nv_bfloat16*)d_in[5];
  const __nv_bfloat16* wd = (const __nv_bfloat16*)d_in[6];
  void* fn = nullptr;
  cudaDriverEntryPointQueryResult qr;
  cudaGetDriverEntryPoint("cuTensorMapEncodeTiled", &fn, cudaEnableDefault, &qr);
  EncodeFn enc = (EncodeFn)fn;
  void *hp = nullptr, *kvp = nullptr;
  cudaGetSymbolAddress(&kvp, g_KV);
  cudaGetSymbolAddress(&hp, g_H);
  Params p;
  enc2d(enc, &p.xm, x, DM, SEQ, DM, 64, 128, CU_TENSOR_MAP_SWIZZLE_128B);
  enc2d(enc, &p.kv, kvp, 320, 32 * 256, 320, 192, 8, CU_TENSOR_MAP_SWIZZLE_NONE);
  enc2d(enc, &p.wqkv64, wqkv, 3 * DM, DM, 3 * DM, 64, 64, CU_TENSOR_MAP_SWIZZLE_128B);
  enc2d(enc, &p.wqkv8, wqkv, 3 * DM, DM, 3 * DM, 8, 64, CU_TENSOR_MAP_SWIZZLE_NONE);
  enc2d(enc, &p.wg, wg, FF, DM, FF, 64, 48, CU_TENSOR_MAP_SWIZZLE_128B);
  enc2d(enc, &p.wu, wu, FF, DM, FF, 64, 48, CU_TENSOR_MAP_SWIZZLE_128B);
  enc2d(enc, &p.h, hp, FF, SEQ, FF, 64, 128, CU_TENSOR_MAP_SWIZZLE_128B);
  for (int hh = 0; hh < 2; hh++) {
    for (int e = 0; e < 2; e++) {
      cuuint64_t d3[3] = {288, e ? 2u : 16u, 32}, s3[2] = {DM * 2, 18 * DM * 2};
      cuuint32_t b3[3] = {64, e ? 2u : 16u, e ? 8u : 4u}, e3[3] = {1, 1, 1};
      enc(e ? &p.wo16[hh] : &p.wo[hh], CU_TENSOR_MAP_DATA_TYPE_BFLOAT16, 3, (void*)(wo + 288 * hh + (e ? 16 * DM : 0)), d3, s3, b3, e3,
          CU_TENSOR_MAP_INTERLEAVE_NONE, CU_TENSOR_MAP_SWIZZLE_128B, CU_TENSOR_MAP_L2_PROMOTION_L2_128B, CU_TENSOR_MAP_FLOAT_OOB_FILL_NONE);
    }
    cuuint64_t dims[5] = {288, 2, 4, 4, FF / 32}, str[4] = {DM * 2, 8 * DM * 2, 2 * DM * 2, 32 * DM * 2};
    cuuint32_t box[5] = {64, 2, 4, 4, 2}, es[5] = {1, 1, 1, 1, 1};
    enc(&p.wd[hh], CU_TENSOR_MAP_DATA_TYPE_BFLOAT16, 5, (void*)(wd + 288 * hh), dims, str, box, es, CU_TENSOR_MAP_INTERLEAVE_NONE,
        CU_TENSOR_MAP_SWIZZLE_128B, CU_TENSOR_MAP_L2_PROMOTION_L2_128B, CU_TENSOR_MAP_FLOAT_OOB_FILL_NONE);
  }
  p.x = x;
  p.out = (__nv_bfloat16*)d_out;
  cudaFuncSetAttribute(fused_kernel, cudaFuncAttributeMaxDynamicSharedMemorySize, SM_TOTAL);
  fused_kernel<<<NCTA, 384, SM_TOTAL, cudaStreamPerThread>>>(p);
}
```

```cpp
#include <cuda_runtime.h>
#include <cuda.h>
#include <cuda_bf16.h>
#include <stdint.h>

namespace {

constexpr int SEQ = 2048, DM = 576, FF = 4608;
constexpr int NCTA = 128;

constexpr uint32_t SM_XN = 0;
constexpr uint32_t SM_RING = 147456;
constexpr uint32_t SM_KV = 212992;
constexpr uint32_t QST = 27648, BST = 16384, KVST = 6144;
constexpr uint32_t G2ST = 43008;
constexpr uint32_t SM_LB = 0, SM_LA = 49152, SM_LX0 = 81920, SM_SEND = 86016, SM_RECV = 143360, SM_LX1 = 198656;
constexpr uint32_t SM_BAR = 231936;
constexpr uint32_t SM_BAD = 232432;
constexpr uint32_t SM_TOTAL = 232448;
enum { B_QF = 0, B_QE = 3, B_BF = 6, B_BE = 10, B_GF = 14, B_GE = 18, B_KF = 22, B_KE = 25, B_SK1 = 28, B_SK2 = 29, B_SH = 30, B_SO1 = 31,
       B_SO2 = 32, B_OL = 33, B_SP = 34, B_RX = 35, B_X = 36, B_NR = 45, B_N = 47 };
constexpr int PF_WD = 5;
constexpr int NG0 = 5;

constexpr uint32_t HI_SW128 = 0x40000040u;
constexpr uint32_t LO_A = 1u << 16;
constexpr uint32_t LO_B = 512u << 16;
constexpr uint32_t HI_R = 64u, LO_R = 8u << 16;
constexpr uint32_t HI_K = 24u, LO_K = 8u << 16;
constexpr uint32_t HI_V = 8u, LO_V = 24u << 16;
constexpr uint32_t LO_B48 = 384u << 16;
constexpr uint32_t HI_O = 8u, LO_O = 128u << 16;
constexpr uint32_t LO_BL = 1536u << 16;

constexpr float QSCALE = 0.23570226039551584f * 1.4426950408889634f;
constexpr float MOFF = 90.f;

struct __align__(64) Params {
  CUtensorMap xm, wqkv64, wqkv8, wg, wu, kv, wd[3], wo3[3], wo2[3], wo16[3];
  const __nv_bfloat16* x;
  __nv_bfloat16* out;
};

__device__ __align__(1024) uint32_t g_H[16 * 576 * 512];
__device__ __align__(1024) uint32_t g_O[NCTA * 9 * 512];
__device__ __align__(1024) uint32_t g_KV[32 * SEQ * 20];
__device__ __align__(1024) uint32_t g_Q[NCTA * 4 * 256 * 8];
__device__ __align__(1024) uint4 g_P[NCTA * 3 * 1152];
__device__ float g_S[NCTA * 8 * SEQ];
__device__ uint32_t g_flags[16 * 32 + NCTA * 32 * 4];
#define FLAG_KV(l, j) (&g_flags[((l) * 8 + (j)) * 32])
#define FLAG_H(c) (&g_flags[16 * 32 + (c) * 32])
#define FLAG_O(c) (&g_flags[16 * 32 + NCTA * 32 + (c) * 32])
#define FLAG_P(c) (&g_flags[16 * 32 + NCTA * 64 + (c) * 32])
#define FLAG_EPOCH(c) (&g_flags[16 * 32 + NCTA * 96 + (c) * 32])
#define STAMP(i)
#define STAMPW(i)
#define TRACE()

template<uint32_t AHI, uint32_t BHI> __device__ __forceinline__ void wg_ss_n192(float* d, uint32_t a, uint32_t b) {
  asm volatile("{\n.reg .pred p;\n.reg .b64 da, db;\nsetp.ne.b32 p, 1, 0;\nmov.b64 da, {%96, %98};\nmov.b64 db, {%97, %99};\n"
    "wgmma.mma_async.sync.aligned.m64n192k16.f32.bf16.bf16 {%0, %1, %2, %3, %4, %5, %6, %7, %8, %9, %10, %11, %12, %13, %14, %15, %16, %17, %18, %19, %20, %21, %22, %23, %24, %25, %26, %27, %28, %29, %30, %31, %32, %33, %34, %35, %36, %37, %38, %39, %40, %41, %42, %43, %44, %45, %46, %47, %48, %49, %50, %51, %52, %53, %54, %55, %56, %57, %58, %59, %60, %61, %62, %63, %64, %65, %66, %67, %68, %69, %70, %71, %72, %73, %74, %75, %76, %77, %78, %79, %80, %81, %82, %83, %84, %85, %86, %87, %88, %89, %90, %91, %92, %93, %94, %95}, da, db, p, 1, 1, 0, 1;\n}\n"
    : "+f"(d[0]), "+f"(d[1]), "+f"(d[2]), "+f"(d[3]), "+f"(d[4]), "+f"(d[5]), "+f"(d[6]), "+f"(d[7]), "+f"(d[8]), "+f"(d[9]), "+f"(d[10]), "+f"(d[11]), "+f"(d[12]), "+f"(d[13]), "+f"(d[14]), "+f"(d[15]), "+f"(d[16]), "+f"(d[17]), "+f"(d[18]), "+f"(d[19]), "+f"(d[20]), "+f"(d[21]), "+f"(d[22]), "+f"(d[23]), "+f"(d[24]), "+f"(d[25]), "+f"(d[26]), "+f"(d[27]), "+f"(d[28]), "+f"(d[29]), "+f"(d[30]), "+f"(d[31]), "+f"(d[32]), "+f"(d[33]), "+f"(d[34]), "+f"(d[35]), "+f"(d[36]), "+f"(d[37]), "+f"(d[38]), "+f"(d[39]), "+f"(d[40]), "+f"(d[41]), "+f"(d[42]), "+f"(d[43]), "+f"(d[44]), "+f"(d[45]), "+f"(d[46]), "+f"(d[47]), "+f"(d[48]), "+f"(d[49]), "+f"(d[50]), "+f"(d[51]), "+f"(d[52]), "+f"(d[53]), "+f"(d[54]), "+f"(d[55]), "+f"(d[56]), "+f"(d[57]), "+f"(d[58]), "+f"(d[59]), "+f"(d[60]), "+f"(d[61]), "+f"(d[62]), "+f"(d[63]), "+f"(d[64]), "+f"(d[65]), "+f"(d[66]), "+f"(d[67]), "+f"(d[68]), "+f"(d[69]), "+f"(d[70]), "+f"(d[71]), "+f"(d[72]), "+f"(d[73]), "+f"(d[74]), "+f"(d[75]), "+f"(d[76]), "+f"(d[77]), "+f"(d[78]), "+f"(d[79]), "+f"(d[80]), "+f"(d[81]), "+f"(d[82]), "+f"(d[83]), "+f"(d[84]), "+f"(d[85]), "+f"(d[86]), "+f"(d[87]), "+f"(d[88]), "+f"(d[89]), "+f"(d[90]), "+f"(d[91]), "+f"(d[92]), "+f"(d[93]), "+f"(d[94]), "+f"(d[95])
    : "r"(a), "r"(b), "n"(AHI), "n"(BHI));
}
template<uint32_t AHI, uint32_t BHI> __device__ __forceinline__ void wg_ss_z_n192(float* d, uint32_t a, uint32_t b) {
  asm volatile("{\n.reg .pred p;\n.reg .b64 da, db;\nsetp.ne.b32 p, 0, 0;\nmov.b64 da, {%96, %98};\nmov.b64 db, {%97, %99};\n"
    "wgmma.mma_async.sync.aligned.m64n192k16.f32.bf16.bf16 {%0, %1, %2, %3, %4, %5, %6, %7, %8, %9, %10, %11, %12, %13, %14, %15, %16, %17, %18, %19, %20, %21, %22, %23, %24, %25, %26, %27, %28, %29, %30, %31, %32, %33, %34, %35, %36, %37, %38, %39, %40, %41, %42, %43, %44, %45, %46, %47, %48, %49, %50, %51, %52, %53, %54, %55, %56, %57, %58, %59, %60, %61, %62, %63, %64, %65, %66, %67, %68, %69, %70, %71, %72, %73, %74, %75, %76, %77, %78, %79, %80, %81, %82, %83, %84, %85, %86, %87, %88, %89, %90, %91, %92, %93, %94, %95}, da, db, p, 1, 1, 0, 1;\n}\n"
    : "=f"(d[0]), "=f"(d[1]), "=f"(d[2]), "=f"(d[3]), "=f"(d[4]), "=f"(d[5]), "=f"(d[6]), "=f"(d[7]), "=f"(d[8]), "=f"(d[9]), "=f"(d[10]), "=f"(d[11]), "=f"(d[12]), "=f"(d[13]), "=f"(d[14]), "=f"(d[15]), "=f"(d[16]), "=f"(d[17]), "=f"(d[18]), "=f"(d[19]), "=f"(d[20]), "=f"(d[21]), "=f"(d[22]), "=f"(d[23]), "=f"(d[24]), "=f"(d[25]), "=f"(d[26]), "=f"(d[27]), "=f"(d[28]), "=f"(d[29]), "=f"(d[30]), "=f"(d[31]), "=f"(d[32]), "=f"(d[33]), "=f"(d[34]), "=f"(d[35]), "=f"(d[36]), "=f"(d[37]), "=f"(d[38]), "=f"(d[39]), "=f"(d[40]), "=f"(d[41]), "=f"(d[42]), "=f"(d[43]), "=f"(d[44]), "=f"(d[45]), "=f"(d[46]), "=f"(d[47]), "=f"(d[48]), "=f"(d[49]), "=f"(d[50]), "=f"(d[51]), "=f"(d[52]), "=f"(d[53]), "=f"(d[54]), "=f"(d[55]), "=f"(d[56]), "=f"(d[57]), "=f"(d[58]), "=f"(d[59]), "=f"(d[60]), "=f"(d[61]), "=f"(d[62]), "=f"(d[63]), "=f"(d[64]), "=f"(d[65]), "=f"(d[66]), "=f"(d[67]), "=f"(d[68]), "=f"(d[69]), "=f"(d[70]), "=f"(d[71]), "=f"(d[72]), "=f"(d[73]), "=f"(d[74]), "=f"(d[75]), "=f"(d[76]), "=f"(d[77]), "=f"(d[78]), "=f"(d[79]), "=f"(d[80]), "=f"(d[81]), "=f"(d[82]), "=f"(d[83]), "=f"(d[84]), "=f"(d[85]), "=f"(d[86]), "=f"(d[87]), "=f"(d[88]), "=f"(d[89]), "=f"(d[90]), "=f"(d[91]), "=f"(d[92]), "=f"(d[93]), "=f"(d[94]), "=f"(d[95])
    : "r"(a), "r"(b), "n"(AHI), "n"(BHI));
}
template<uint32_t AHI, uint32_t BHI> __device__ __forceinline__ void wg_ss_n24(float* d, uint32_t a, uint32_t b) {
  asm volatile("{\n.reg .pred p;\n.reg .b64 da, db;\nsetp.ne.b32 p, 1, 0;\nmov.b64 da, {%12, %14};\nmov.b64 db, {%13, %15};\n"
    "wgmma.mma_async.sync.aligned.m64n24k16.f32.bf16.bf16 {%0, %1, %2, %3, %4, %5, %6, %7, %8, %9, %10, %11}, da, db, p, 1, 1, 0, 1;\n}\n"
    : "+f"(d[0]), "+f"(d[1]), "+f"(d[2]), "+f"(d[3]), "+f"(d[4]), "+f"(d[5]), "+f"(d[6]), "+f"(d[7]), "+f"(d[8]), "+f"(d[9]), "+f"(d[10]), "+f"(d[11])
    : "r"(a), "r"(b), "n"(AHI), "n"(BHI));
}
template<uint32_t AHI, uint32_t BHI> __device__ __forceinline__ void wg_ss_z_n24(float* d, uint32_t a, uint32_t b) {
  asm volatile("{\n.reg .pred p;\n.reg .b64 da, db;\nsetp.ne.b32 p, 0, 0;\nmov.b64 da, {%12, %14};\nmov.b64 db, {%13, %15};\n"
    "wgmma.mma_async.sync.aligned.m64n24k16.f32.bf16.bf16 {%0, %1, %2, %3, %4, %5, %6, %7, %8, %9, %10, %11}, da, db, p, 1, 1, 0, 1;\n}\n"
    : "=f"(d[0]), "=f"(d[1]), "=f"(d[2]), "=f"(d[3]), "=f"(d[4]), "=f"(d[5]), "=f"(d[6]), "=f"(d[7]), "=f"(d[8]), "=f"(d[9]), "=f"(d[10]), "=f"(d[11])
    : "r"(a), "r"(b), "n"(AHI), "n"(BHI));
}
template<uint32_t AHI, uint32_t BHI> __device__ __forceinline__ void wg_ss_n128(float* d, uint32_t a, uint32_t b) {
  asm volatile("{\n.reg .pred p;\n.reg .b64 da, db;\nsetp.ne.b32 p, 1, 0;\nmov.b64 da, {%64, %66};\nmov.b64 db, {%65, %67};\n"
    "wgmma.mma_async.sync.aligned.m64n128k16.f32.bf16.bf16 {%0, %1, %2, %3, %4, %5, %6, %7, %8, %9, %10, %11, %12, %13, %14, %15, %16, %17, %18, %19, %20, %21, %22, %23, %24, %25, %26, %27, %28, %29, %30, %31, %32, %33, %34, %35, %36, %37, %38, %39, %40, %41, %42, %43, %44, %45, %46, %47, %48, %49, %50, %51, %52, %53, %54, %55, %56, %57, %58, %59, %60, %61, %62, %63}, da, db, p, 1, 1, 0, 1;\n}\n"
    : "+f"(d[0]), "+f"(d[1]), "+f"(d[2]), "+f"(d[3]), "+f"(d[4]), "+f"(d[5]), "+f"(d[6]), "+f"(d[7]), "+f"(d[8]), "+f"(d[9]), "+f"(d[10]), "+f"(d[11]), "+f"(d[12]), "+f"(d[13]), "+f"(d[14]), "+f"(d[15]), "+f"(d[16]), "+f"(d[17]), "+f"(d[18]), "+f"(d[19]), "+f"(d[20]), "+f"(d[21]), "+f"(d[22]), "+f"(d[23]), "+f"(d[24]), "+f"(d[25]), "+f"(d[26]), "+f"(d[27]), "+f"(d[28]), "+f"(d[29]), "+f"(d[30]), "+f"(d[31]), "+f"(d[32]), "+f"(d[33]), "+f"(d[34]), "+f"(d[35]), "+f"(d[36]), "+f"(d[37]), "+f"(d[38]), "+f"(d[39]), "+f"(d[40]), "+f"(d[41]), "+f"(d[42]), "+f"(d[43]), "+f"(d[44]), "+f"(d[45]), "+f"(d[46]), "+f"(d[47]), "+f"(d[48]), "+f"(d[49]), "+f"(d[50]), "+f"(d[51]), "+f"(d[52]), "+f"(d[53]), "+f"(d[54]), "+f"(d[55]), "+f"(d[56]), "+f"(d[57]), "+f"(d[58]), "+f"(d[59]), "+f"(d[60]), "+f"(d[61]), "+f"(d[62]), "+f"(d[63])
    : "r"(a), "r"(b), "n"(AHI), "n"(BHI));
}
template<uint32_t AHI, uint32_t BHI> __device__ __forceinline__ void wg_ss_z_n128(float* d, uint32_t a, uint32_t b) {
  asm volatile("{\n.reg .pred p;\n.reg .b64 da, db;\nsetp.ne.b32 p, 0, 0;\nmov.b64 da, {%64, %66};\nmov.b64 db, {%65, %67};\n"
    "wgmma.mma_async.sync.aligned.m64n128k16.f32.bf16.bf16 {%0, %1, %2, %3, %4, %5, %6, %7, %8, %9, %10, %11, %12, %13, %14, %15, %16, %17, %18, %19, %20, %21, %22, %23, %24, %25, %26, %27, %28, %29, %30, %31, %32, %33, %34, %35, %36, %37, %38, %39, %40, %41, %42, %43, %44, %45, %46, %47, %48, %49, %50, %51, %52, %53, %54, %55, %56, %57, %58, %59, %60, %61, %62, %63}, da, db, p, 1, 1, 0, 1;\n}\n"
    : "=f"(d[0]), "=f"(d[1]), "=f"(d[2]), "=f"(d[3]), "=f"(d[4]), "=f"(d[5]), "=f"(d[6]), "=f"(d[7]), "=f"(d[8]), "=f"(d[9]), "=f"(d[10]), "=f"(d[11]), "=f"(d[12]), "=f"(d[13]), "=f"(d[14]), "=f"(d[15]), "=f"(d[16]), "=f"(d[17]), "=f"(d[18]), "=f"(d[19]), "=f"(d[20]), "=f"(d[21]), "=f"(d[22]), "=f"(d[23]), "=f"(d[24]), "=f"(d[25]), "=f"(d[26]), "=f"(d[27]), "=f"(d[28]), "=f"(d[29]), "=f"(d[30]), "=f"(d[31]), "=f"(d[32]), "=f"(d[33]), "=f"(d[34]), "=f"(d[35]), "=f"(d[36]), "=f"(d[37]), "=f"(d[38]), "=f"(d[39]), "=f"(d[40]), "=f"(d[41]), "=f"(d[42]), "=f"(d[43]), "=f"(d[44]), "=f"(d[45]), "=f"(d[46]), "=f"(d[47]), "=f"(d[48]), "=f"(d[49]), "=f"(d[50]), "=f"(d[51]), "=f"(d[52]), "=f"(d[53]), "=f"(d[54]), "=f"(d[55]), "=f"(d[56]), "=f"(d[57]), "=f"(d[58]), "=f"(d[59]), "=f"(d[60]), "=f"(d[61]), "=f"(d[62]), "=f"(d[63])
    : "r"(a), "r"(b), "n"(AHI), "n"(BHI));
}
template<uint32_t AHI, uint32_t BHI> __device__ __forceinline__ void wg_ss_n160(float* d, uint32_t a, uint32_t b) {
  asm volatile("{\n.reg .pred p;\n.reg .b64 da, db;\nsetp.ne.b32 p, 1, 0;\nmov.b64 da, {%80, %82};\nmov.b64 db, {%81, %83};\n"
    "wgmma.mma_async.sync.aligned.m64n160k16.f32.bf16.bf16 {%0, %1, %2, %3, %4, %5, %6, %7, %8, %9, %10, %11, %12, %13, %14, %15, %16, %17, %18, %19, %20, %21, %22, %23, %24, %25, %26, %27, %28, %29, %30, %31, %32, %33, %34, %35, %36, %37, %38, %39, %40, %41, %42, %43, %44, %45, %46, %47, %48, %49, %50, %51, %52, %53, %54, %55, %56, %57, %58, %59, %60, %61, %62, %63, %64, %65, %66, %67, %68, %69, %70, %71, %72, %73, %74, %75, %76, %77, %78, %79}, da, db, p, 1, 1, 0, 1;\n}\n"
    : "+f"(d[0]), "+f"(d[1]), "+f"(d[2]), "+f"(d[3]), "+f"(d[4]), "+f"(d[5]), "+f"(d[6]), "+f"(d[7]), "+f"(d[8]), "+f"(d[9]), "+f"(d[10]), "+f"(d[11]), "+f"(d[12]), "+f"(d[13]), "+f"(d[14]), "+f"(d[15]), "+f"(d[16]), "+f"(d[17]), "+f"(d[18]), "+f"(d[19]), "+f"(d[20]), "+f"(d[21]), "+f"(d[22]), "+f"(d[23]), "+f"(d[24]), "+f"(d[25]), "+f"(d[26]), "+f"(d[27]), "+f"(d[28]), "+f"(d[29]), "+f"(d[30]), "+f"(d[31]), "+f"(d[32]), "+f"(d[33]), "+f"(d[34]), "+f"(d[35]), "+f"(d[36]), "+f"(d[37]), "+f"(d[38]), "+f"(d[39]), "+f"(d[40]), "+f"(d[41]), "+f"(d[42]), "+f"(d[43]), "+f"(d[44]), "+f"(d[45]), "+f"(d[46]), "+f"(d[47]), "+f"(d[48]), "+f"(d[49]), "+f"(d[50]), "+f"(d[51]), "+f"(d[52]), "+f"(d[53]), "+f"(d[54]), "+f"(d[55]), "+f"(d[56]), "+f"(d[57]), "+f"(d[58]), "+f"(d[59]), "+f"(d[60]), "+f"(d[61]), "+f"(d[62]), "+f"(d[63]), "+f"(d[64]), "+f"(d[65]), "+f"(d[66]), "+f"(d[67]), "+f"(d[68]), "+f"(d[69]), "+f"(d[70]), "+f"(d[71]), "+f"(d[72]), "+f"(d[73]), "+f"(d[74]), "+f"(d[75]), "+f"(d[76]), "+f"(d[77]), "+f"(d[78]), "+f"(d[79])
    : "r"(a), "r"(b), "n"(AHI), "n"(BHI));
}
template<uint32_t AHI, uint32_t BHI> __device__ __forceinline__ void wg_ss_z_n160(float* d, uint32_t a, uint32_t b) {
  asm volatile("{\n.reg .pred p;\n.reg .b64 da, db;\nsetp.ne.b32 p, 0, 0;\nmov.b64 da, {%80, %82};\nmov.b64 db, {%81, %83};\n"
    "wgmma.mma_async.sync.aligned.m64n160k16.f32.bf16.bf16 {%0, %1, %2, %3, %4, %5, %6, %7, %8, %9, %10, %11, %12, %13, %14, %15, %16, %17, %18, %19, %20, %21, %22, %23, %24, %25, %26, %27, %28, %29, %30, %31, %32, %33, %34, %35, %36, %37, %38, %39, %40, %41, %42, %43, %44, %45, %46, %47, %48, %49, %50, %51, %52, %53, %54, %55, %56, %57, %58, %59, %60, %61, %62, %63, %64, %65, %66, %67, %68, %69, %70, %71, %72, %73, %74, %75, %76, %77, %78, %79}, da, db, p, 1, 1, 0, 1;\n}\n"
    : "=f"(d[0]), "=f"(d[1]), "=f"(d[2]), "=f"(d[3]), "=f"(d[4]), "=f"(d[5]), "=f"(d[6]), "=f"(d[7]), "=f"(d[8]), "=f"(d[9]), "=f"(d[10]), "=f"(d[11]), "=f"(d[12]), "=f"(d[13]), "=f"(d[14]), "=f"(d[15]), "=f"(d[16]), "=f"(d[17]), "=f"(d[18]), "=f"(d[19]), "=f"(d[20]), "=f"(d[21]), "=f"(d[22]), "=f"(d[23]), "=f"(d[24]), "=f"(d[25]), "=f"(d[26]), "=f"(d[27]), "=f"(d[28]), "=f"(d[29]), "=f"(d[30]), "=f"(d[31]), "=f"(d[32]), "=f"(d[33]), "=f"(d[34]), "=f"(d[35]), "=f"(d[36]), "=f"(d[37]), "=f"(d[38]), "=f"(d[39]), "=f"(d[40]), "=f"(d[41]), "=f"(d[42]), "=f"(d[43]), "=f"(d[44]), "=f"(d[45]), "=f"(d[46]), "=f"(d[47]), "=f"(d[48]), "=f"(d[49]), "=f"(d[50]), "=f"(d[51]), "=f"(d[52]), "=f"(d[53]), "=f"(d[54]), "=f"(d[55]), "=f"(d[56]), "=f"(d[57]), "=f"(d[58]), "=f"(d[59]), "=f"(d[60]), "=f"(d[61]), "=f"(d[62]), "=f"(d[63]), "=f"(d[64]), "=f"(d[65]), "=f"(d[66]), "=f"(d[67]), "=f"(d[68]), "=f"(d[69]), "=f"(d[70]), "=f"(d[71]), "=f"(d[72]), "=f"(d[73]), "=f"(d[74]), "=f"(d[75]), "=f"(d[76]), "=f"(d[77]), "=f"(d[78]), "=f"(d[79])
    : "r"(a), "r"(b), "n"(AHI), "n"(BHI));
}
template<uint32_t AHI, uint32_t BHI> __device__ __forceinline__ void wg_ss_n96(float* d, uint32_t a, uint32_t b) {
  asm volatile("{\n.reg .pred p;\n.reg .b64 da, db;\nsetp.ne.b32 p, 1, 0;\nmov.b64 da, {%48, %50};\nmov.b64 db, {%49, %51};\n"
    "wgmma.mma_async.sync.aligned.m64n96k16.f32.bf16.bf16 {%0, %1, %2, %3, %4, %5, %6, %7, %8, %9, %10, %11, %12, %13, %14, %15, %16, %17, %18, %19, %20, %21, %22, %23, %24, %25, %26, %27, %28, %29, %30, %31, %32, %33, %34, %35, %36, %37, %38, %39, %40, %41, %42, %43, %44, %45, %46, %47}, da, db, p, 1, 1, 0, 1;\n}\n"
    : "+f"(d[0]), "+f"(d[1]), "+f"(d[2]), "+f"(d[3]), "+f"(d[4]), "+f"(d[5]), "+f"(d[6]), "+f"(d[7]), "+f"(d[8]), "+f"(d[9]), "+f"(d[10]), "+f"(d[11]), "+f"(d[12]), "+f"(d[13]), "+f"(d[14]), "+f"(d[15]), "+f"(d[16]), "+f"(d[17]), "+f"(d[18]), "+f"(d[19]), "+f"(d[20]), "+f"(d[21]), "+f"(d[22]), "+f"(d[23]), "+f"(d[24]), "+f"(d[25]), "+f"(d[26]), "+f"(d[27]), "+f"(d[28]), "+f"(d[29]), "+f"(d[30]), "+f"(d[31]), "+f"(d[32]), "+f"(d[33]), "+f"(d[34]), "+f"(d[35]), "+f"(d[36]), "+f"(d[37]), "+f"(d[38]), "+f"(d[39]), "+f"(d[40]), "+f"(d[41]), "+f"(d[42]), "+f"(d[43]), "+f"(d[44]), "+f"(d[45]), "+f"(d[46]), "+f"(d[47])
    : "r"(a), "r"(b), "n"(AHI), "n"(BHI));
}
template<uint32_t AHI, uint32_t BHI> __device__ __forceinline__ void wg_ss_z_n96(float* d, uint32_t a, uint32_t b) {
  asm volatile("{\n.reg .pred p;\n.reg .b64 da, db;\nsetp.ne.b32 p, 0, 0;\nmov.b64 da, {%48, %50};\nmov.b64 db, {%49, %51};\n"
    "wgmma.mma_async.sync.aligned.m64n96k16.f32.bf16.bf16 {%0, %1, %2, %3, %4, %5, %6, %7, %8, %9, %10, %11, %12, %13, %14, %15, %16, %17, %18, %19, %20, %21, %22, %23, %24, %25, %26, %27, %28, %29, %30, %31, %32, %33, %34, %35, %36, %37, %38, %39, %40, %41, %42, %43, %44, %45, %46, %47}, da, db, p, 1, 1, 0, 1;\n}\n"
    : "=f"(d[0]), "=f"(d[1]), "=f"(d[2]), "=f"(d[3]), "=f"(d[4]), "=f"(d[5]), "=f"(d[6]), "=f"(d[7]), "=f"(d[8]), "=f"(d[9]), "=f"(d[10]), "=f"(d[11]), "=f"(d[12]), "=f"(d[13]), "=f"(d[14]), "=f"(d[15]), "=f"(d[16]), "=f"(d[17]), "=f"(d[18]), "=f"(d[19]), "=f"(d[20]), "=f"(d[21]), "=f"(d[22]), "=f"(d[23]), "=f"(d[24]), "=f"(d[25]), "=f"(d[26]), "=f"(d[27]), "=f"(d[28]), "=f"(d[29]), "=f"(d[30]), "=f"(d[31]), "=f"(d[32]), "=f"(d[33]), "=f"(d[34]), "=f"(d[35]), "=f"(d[36]), "=f"(d[37]), "=f"(d[38]), "=f"(d[39]), "=f"(d[40]), "=f"(d[41]), "=f"(d[42]), "=f"(d[43]), "=f"(d[44]), "=f"(d[45]), "=f"(d[46]), "=f"(d[47])
    : "r"(a), "r"(b), "n"(AHI), "n"(BHI));
}
template<uint32_t BHI> __device__ __forceinline__ void wg_rs_n64(float* d, uint32_t a0, uint32_t a1, uint32_t a2, uint32_t a3, uint32_t b) {
  asm volatile("{\n.reg .pred p;\n.reg .b64 db;\nsetp.ne.b32 p, 1, 0;\nmov.b64 db, {%36, %37};\n"
    "wgmma.mma_async.sync.aligned.m64n64k16.f32.bf16.bf16 {%0, %1, %2, %3, %4, %5, %6, %7, %8, %9, %10, %11, %12, %13, %14, %15, %16, %17, %18, %19, %20, %21, %22, %23, %24, %25, %26, %27, %28, %29, %30, %31}, {%32, %33, %34, %35}, db, p, 1, 1, 0;\n}\n"
    : "+f"(d[0]), "+f"(d[1]), "+f"(d[2]), "+f"(d[3]), "+f"(d[4]), "+f"(d[5]), "+f"(d[6]), "+f"(d[7]), "+f"(d[8]), "+f"(d[9]), "+f"(d[10]), "+f"(d[11]), "+f"(d[12]), "+f"(d[13]), "+f"(d[14]), "+f"(d[15]), "+f"(d[16]), "+f"(d[17]), "+f"(d[18]), "+f"(d[19]), "+f"(d[20]), "+f"(d[21]), "+f"(d[22]), "+f"(d[23]), "+f"(d[24]), "+f"(d[25]), "+f"(d[26]), "+f"(d[27]), "+f"(d[28]), "+f"(d[29]), "+f"(d[30]), "+f"(d[31])
    : "r"(a0), "r"(a1), "r"(a2), "r"(a3), "r"(b), "n"(BHI));
}
template<uint32_t BHI> __device__ __forceinline__ void wg_rs_z_n64(float* d, uint32_t a0, uint32_t a1, uint32_t a2, uint32_t a3, uint32_t b) {
  asm volatile("{\n.reg .pred p;\n.reg .b64 db;\nsetp.ne.b32 p, 0, 0;\nmov.b64 db, {%36, %37};\n"
    "wgmma.mma_async.sync.aligned.m64n64k16.f32.bf16.bf16 {%0, %1, %2, %3, %4, %5, %6, %7, %8, %9, %10, %11, %12, %13, %14, %15, %16, %17, %18, %19, %20, %21, %22, %23, %24, %25, %26, %27, %28, %29, %30, %31}, {%32, %33, %34, %35}, db, p, 1, 1, 0;\n}\n"
    : "=f"(d[0]), "=f"(d[1]), "=f"(d[2]), "=f"(d[3]), "=f"(d[4]), "=f"(d[5]), "=f"(d[6]), "=f"(d[7]), "=f"(d[8]), "=f"(d[9]), "=f"(d[10]), "=f"(d[11]), "=f"(d[12]), "=f"(d[13]), "=f"(d[14]), "=f"(d[15]), "=f"(d[16]), "=f"(d[17]), "=f"(d[18]), "=f"(d[19]), "=f"(d[20]), "=f"(d[21]), "=f"(d[22]), "=f"(d[23]), "=f"(d[24]), "=f"(d[25]), "=f"(d[26]), "=f"(d[27]), "=f"(d[28]), "=f"(d[29]), "=f"(d[30]), "=f"(d[31])
    : "r"(a0), "r"(a1), "r"(a2), "r"(a3), "r"(b), "n"(BHI));
}
template<uint32_t BHI> __device__ __forceinline__ void wg_rs_n24(float* d, uint32_t a0, uint32_t a1, uint32_t a2, uint32_t a3, uint32_t b) {
  asm volatile("{\n.reg .pred p;\n.reg .b64 db;\nsetp.ne.b32 p, 1, 0;\nmov.b64 db, {%16, %17};\n"
    "wgmma.mma_async.sync.aligned.m64n24k16.f32.bf16.bf16 {%0, %1, %2, %3, %4, %5, %6, %7, %8, %9, %10, %11}, {%12, %13, %14, %15}, db, p, 1, 1, 1;\n}\n"
    : "+f"(d[0]), "+f"(d[1]), "+f"(d[2]), "+f"(d[3]), "+f"(d[4]), "+f"(d[5]), "+f"(d[6]), "+f"(d[7]), "+f"(d[8]), "+f"(d[9]), "+f"(d[10]), "+f"(d[11])
    : "r"(a0), "r"(a1), "r"(a2), "r"(a3), "r"(b), "n"(BHI));
}
template<uint32_t BHI> __device__ __forceinline__ void wg_rs_z_n24(float* d, uint32_t a0, uint32_t a1, uint32_t a2, uint32_t a3, uint32_t b) {
  asm volatile("{\n.reg .pred p;\n.reg .b64 db;\nsetp.ne.b32 p, 0, 0;\nmov.b64 db, {%16, %17};\n"
    "wgmma.mma_async.sync.aligned.m64n24k16.f32.bf16.bf16 {%0, %1, %2, %3, %4, %5, %6, %7, %8, %9, %10, %11}, {%12, %13, %14, %15}, db, p, 1, 1, 1;\n}\n"
    : "=f"(d[0]), "=f"(d[1]), "=f"(d[2]), "=f"(d[3]), "=f"(d[4]), "=f"(d[5]), "=f"(d[6]), "=f"(d[7]), "=f"(d[8]), "=f"(d[9]), "=f"(d[10]), "=f"(d[11])
    : "r"(a0), "r"(a1), "r"(a2), "r"(a3), "r"(b), "n"(BHI));
}

__device__ __forceinline__ void wg_fence() { asm volatile("wgmma.fence.sync.aligned;" ::: "memory"); }
__device__ __forceinline__ void wg_commit() { asm volatile("wgmma.commit_group.sync.aligned;" ::: "memory"); }
template <int N> __device__ __forceinline__ void wg_wait() { asm volatile("wgmma.wait_group.sync.aligned %0;" ::"n"(N) : "memory"); }
template <int R> __device__ __forceinline__ void pin(float* d) {
#pragma unroll
  for (int i = 0; i < R; i++) asm volatile("" : "+f"(d[i])::"memory");
}
template <int R> __device__ __forceinline__ void pin(uint32_t* d) {
#pragma unroll
  for (int i = 0; i < R; i++) asm volatile("" : "+r"(d[i])::"memory");
}
__device__ __forceinline__ float ex2(float x) { float y; asm("ex2.approx.ftz.f32 %0, %1;" : "=f"(y) : "f"(x)); return y; }
__device__ __forceinline__ float tanh_fast(float x) { float y; asm("tanh.approx.f32 %0, %1;" : "=f"(y) : "f"(x)); return y; }
__device__ __forceinline__ uint32_t pack(float lo, float hi) { uint32_t r; asm("cvt.rn.bf16x2.f32 %0, %1, %2;" : "=r"(r) : "f"(hi), "f"(lo)); return r; }
__device__ __forceinline__ float bf_lo(uint32_t v) { return __uint_as_float(v << 16); }
__device__ __forceinline__ float bf_hi(uint32_t v) { return __uint_as_float(v & 0xffff0000u); }
__device__ __forceinline__ float bf_round(float x) { return bf_lo(pack(x, 0.f)); }

__device__ __forceinline__ void mbar_init(uint32_t bar, uint32_t cnt) { asm volatile("mbarrier.init.shared::cta.b64 [%0], %1;" ::"r"(bar), "r"(cnt) : "memory"); }
__device__ __forceinline__ void mbar_expect(uint32_t bar, uint32_t bytes) { asm volatile("mbarrier.arrive.expect_tx.shared::cta.b64 _, [%0], %1;" ::"r"(bar), "r"(bytes) : "memory"); }
__device__ __forceinline__ void mbar_arrive(uint32_t bar) { asm volatile("mbarrier.arrive.shared::cta.b64 _, [%0];" ::"r"(bar) : "memory"); }
__device__ __forceinline__ void mbar_wait(uint32_t bar, uint32_t parity) {
  asm volatile(
      "{\n.reg .pred p;\n.reg .u32 c;\n"
      "mbarrier.try_wait.parity.shared::cta.b64 p, [%0], %1;\n"
      "@p bra.uni DONE;\n"
      "mov.u32 c, 0;\n"
      "LOOP:\n"
      "mbarrier.try_wait.parity.shared::cta.b64 p, [%0], %1;\n"
      "@p bra.uni DONE;\n"
      "add.u32 c, c, 1;\n"
      "setp.lt.u32 p, c, 0x4000000;\n"
      "@p bra.uni LOOP;\n"
      "trap;\n"
      "DONE:\n}\n" ::"r"(bar), "r"(parity) : "memory");
}
__device__ __forceinline__ uint32_t mbar_test(uint32_t bar, uint32_t parity) {
  uint32_t ok;
  asm volatile("{\n.reg .pred p;\nmbarrier.test_wait.parity.shared::cta.b64 p, [%1], %2;\nselp.u32 %0, 1, 0, p;\n}\n" : "=r"(ok) : "r"(bar), "r"(parity) : "memory");
  return ok;
}
__device__ __forceinline__ void mbar_arrive_if(uint32_t bar, uint32_t cond) {
  asm volatile("{\n.reg .pred p;\nsetp.ne.u32 p, %1, 0;\n@p mbarrier.arrive.shared::cta.b64 _, [%0];\n}\n" ::"r"(bar), "r"(cond) : "memory");
}
__device__ __forceinline__ uint32_t bsub2(uint32_t a, uint32_t b) { uint32_t d; asm("sub.rn.bf16x2 %0, %1, %2;" : "=r"(d) : "r"(a), "r"(b)); return d; }
__device__ __forceinline__ uint32_t bscale2(uint32_t d, uint32_t hi, uint32_t lo) {
  uint32_t t, r;
  asm("mul.rn.bf16x2 %0, %1, %2;" : "=r"(t) : "r"(d), "r"(lo));
  asm("fma.rn.bf16x2 %0, %1, %2, %3;" : "=r"(r) : "r"(d), "r"(hi), "r"(t));
  return r;
}
__device__ __forceinline__ void flag_wait(const uint32_t* f, uint32_t target) {
  asm volatile(
      "{\n.reg .pred p;\n.reg .u32 c, v;\n"
      "mov.u32 c, 0;\n"
      "LOOP:\n"
      "ld.acquire.gpu.global.u32 v, [%0];\n"
      "sub.u32 v, v, %1;\n"
      "setp.ge.s32 p, v, 0;\n"
      "@p bra DONE;\n"
      "add.u32 c, c, 1;\n"
      "setp.lt.u32 p, c, 0x1000000;\n"
      "@p bra LOOP;\n"
      "trap;\n"
      "DONE:\n}\n" ::"l"(f), "r"(target) : "memory");
}
__device__ __forceinline__ uint32_t flag_wait_v(const uint32_t* f, uint32_t target) {
  uint32_t v;
  asm volatile(
      "{\n.reg .pred p;\n.reg .u32 c, d;\n"
      "mov.u32 c, 0;\n"
      "LOOP:\n"
      "ld.acquire.gpu.global.u32 %0, [%1];\n"
      "sub.u32 d, %0, %2;\n"
      "setp.ge.s32 p, d, 0;\n"
      "@p bra DONE;\n"
      "add.u32 c, c, 1;\n"
      "setp.lt.u32 p, c, 0x1000000;\n"
      "@p bra LOOP;\n"
      "trap;\n"
      "DONE:\n}\n" : "=&r"(v) : "l"(f), "r"(target) : "memory");
  return v;
}
__device__ __forceinline__ float sqrt_fast(float x) { float y; asm("sqrt.approx.f32 %0, %1;" : "=f"(y) : "f"(x)); return y; }
__device__ __forceinline__ float rcp_fast(float x) { float y; asm("rcp.approx.ftz.f32 %0, %1;" : "=f"(y) : "f"(x)); return y; }
__device__ __forceinline__ void ldsm4(uint32_t* v, uint32_t addr) {
  asm volatile("ldmatrix.sync.aligned.m8n8.x4.shared.b16 {%0,%1,%2,%3}, [%4];" : "=r"(v[0]), "=r"(v[1]), "=r"(v[2]), "=r"(v[3]) : "r"(addr) : "memory");
}
__device__ __forceinline__ void stsm4(uint32_t addr, uint32_t a, uint32_t b, uint32_t c, uint32_t d) {
  asm volatile("stmatrix.sync.aligned.m8n8.x4.shared.b16 [%0], {%1,%2,%3,%4};" ::"r"(addr), "r"(a), "r"(b), "r"(c), "r"(d) : "memory");
}
__device__ __forceinline__ void flag_add(uint32_t* f) { asm volatile("red.relaxed.gpu.global.add.u32 [%0], 1;" ::"l"(f) : "memory"); }
__device__ __forceinline__ void fence_gpu() { asm volatile("fence.acq_rel.gpu;" ::: "memory"); }
__device__ __forceinline__ void fence_async() { asm volatile("fence.proxy.async;" ::: "memory"); }
__device__ __forceinline__ void tma2d(uint32_t dst, const CUtensorMap* tm, uint32_t bar, int c0, int c1) {
  asm volatile("cp.async.bulk.tensor.2d.shared::cluster.global.mbarrier::complete_tx::bytes [%0], [%1, {%3, %4}], [%2];" ::"r"(dst), "l"(tm), "r"(bar), "r"(c0), "r"(c1) : "memory");
}
__device__ __forceinline__ void tma2d_h(uint32_t dst, const CUtensorMap* tm, uint32_t bar, int c0, int c1, uint64_t pol) {
  asm volatile("cp.async.bulk.tensor.2d.shared::cluster.global.mbarrier::complete_tx::bytes.L2::cache_hint [%0], [%1, {%3, %4}], [%2], %5;" ::"r"(dst), "l"(tm), "r"(bar), "r"(c0), "r"(c1), "l"(pol) : "memory");
}
__device__ __forceinline__ void bulk_s2g(void* dst, uint32_t src, uint32_t bytes) {
  asm volatile("cp.async.bulk.global.shared::cta.bulk_group [%0], [%1], %2;" ::"l"(dst), "r"(src), "r"(bytes) : "memory");
}
__device__ __forceinline__ void mma_ones(float* c, const uint32_t* a) {
  asm("mma.sync.aligned.m16n8k16.row.col.f32.bf16.bf16.f32 {%0,%1,%2,%3}, {%4,%5,%6,%7}, {%8,%8}, {%0,%1,%2,%3};"
      : "+f"(c[0]), "+f"(c[1]), "+f"(c[2]), "+f"(c[3]) : "r"(a[0]), "r"(a[1]), "r"(a[2]), "r"(a[3]), "r"(0x3f803f80u));
}
__device__ __forceinline__ void tma5d(uint32_t dst, const CUtensorMap* tm, uint32_t bar, int c0, int c4) {
  asm volatile("cp.async.bulk.tensor.5d.shared::cluster.global.mbarrier::complete_tx::bytes [%0], [%1, {%3, %5, %5, %5, %4}], [%2];" ::"r"(dst), "l"(tm), "r"(bar), "r"(c0), "r"(c4), "r"(0) : "memory");
}
__device__ __forceinline__ void tma3d(uint32_t dst, const CUtensorMap* tm, uint32_t bar, int c0, int c2) {
  asm volatile("cp.async.bulk.tensor.3d.shared::cluster.global.mbarrier::complete_tx::bytes [%0], [%1, {%3, %5, %4}], [%2];" ::"r"(dst), "l"(tm), "r"(bar), "r"(c0), "r"(c2), "r"(0) : "memory");
}
__device__ __forceinline__ void bulk_g2s(uint32_t dst, const void* src, uint32_t bytes, uint32_t bar) {
  asm volatile("cp.async.bulk.shared::cluster.global.mbarrier::complete_tx::bytes [%0], [%1], %2, [%3];" ::"r"(dst), "l"(src), "r"(bytes), "r"(bar) : "memory");
}
__device__ __forceinline__ void pf3d(const CUtensorMap* tm, int c0, int c2) {
  asm volatile("cp.async.bulk.prefetch.tensor.3d.L2.global [%0, {%1, %3, %2}];" ::"l"(tm), "r"(c0), "r"(c2), "r"(0) : "memory");
}
__device__ __forceinline__ void pf2d(const CUtensorMap* tm, int c0, int c1) {
  asm volatile("cp.async.bulk.prefetch.tensor.2d.L2.global [%0, {%1, %2}];" ::"l"(tm), "r"(c0), "r"(c1) : "memory");
}
__device__ __forceinline__ void pf5d(const CUtensorMap* tm, int c0, int c4) {
  asm volatile("cp.async.bulk.prefetch.tensor.5d.L2.global [%0, {%1, %3, %3, %3, %2}];" ::"l"(tm), "r"(c0), "r"(c4), "r"(0) : "memory");
}

__device__ __forceinline__ int fresh_tid() { int v; asm volatile("mov.u32 %0, %%tid.x;" : "=r"(v)); return v; }
struct Att {
  float s[32];
  float o[12];
  uint32_t p[16];
  uint32_t q[8];
};

__device__ __forceinline__ float warp_sum(float v) {
#pragma unroll 1
  for (int d = 16; d; d >>= 1) v += __shfl_xor_sync(0xffffffffu, v, d);
  return v;
}
#define OPAQUE(x) asm volatile("" : "+r"(x))
__device__ __forceinline__ void attn_slow_row(int cta, uint32_t& w) {
  float mx = -INFINITY;
#pragma unroll 1
  for (uint32_t key = threadIdx.x & 31; key < SEQ; key += 32) {
    float s = 0.f;
#pragma unroll 1
    for (uint32_t v = 0; v < 9; v++) {
      OPAQUE(w); OPAQUE(key);
      const uint32_t hp = (w >> 4) & 3, pos = (v + hp) & 3;
      const uint32_t q = g_Q[(((cta * 4 + hp) * 2 + (v >> 3)) * 256 + ((w >> 6) & 7) * 32 + (w & 7) * 4 + pos) * 4 + 2 * ((v >> 2) & 1) + ((w >> 3) & 1)];
      const uint32_t u = g_KV[(4 * (cta & 7) + hp) * SEQ * 20 + (key >> 3) * 160 + (key & 7) * 4 + (v >> 2) * 32 + pos];
      s = fmaf(bf_lo(q), bf_lo(u), fmaf(bf_hi(q), bf_hi(u), s));
    }
    g_S[(cta * 8 + ((w >> 6) & 7)) * SEQ + key] = s;
    mx = fmaxf(mx, s);
  }
#pragma unroll 1
  for (int d = 16; d; d >>= 1) mx = fmaxf(mx, __shfl_xor_sync(0xffffffffu, mx, d));
  float l = 0.f;
#pragma unroll 1
  for (uint32_t key = threadIdx.x & 31; key < SEQ; key += 32) l += ex2(g_S[(cta * 8 + ((w >> 6) & 7)) * SEQ + key] - mx);
  l = 2.f * rcp_fast(warp_sum(l));
#pragma unroll 1
  for (uint32_t v = w >> 9; v < 9; v++) {
    float a = 0.f, b = 0.f;
#pragma unroll 1
    for (uint32_t key = threadIdx.x & 31; key < SEQ; key += 32) {
      OPAQUE(w); OPAQUE(v);
      const uint32_t hp = (w >> 4) & 3;
      const uint32_t u = g_KV[(4 * (cta & 7) + hp) * SEQ * 20 + (key >> 3) * 160 + (key & 7) * 4 + (v < 8 ? (3 + (v >> 2)) * 32 + (v & 3) : 64 + ((hp + 2) & 3))];
      const float p = ex2(g_S[(cta * 8 + ((w >> 6) & 7)) * SEQ + key] - mx);
      a = fmaf(p, bf_lo(u), a); b = fmaf(p, bf_hi(u), b);
    }
    a = warp_sum(a); b = warp_sum(b);
    OPAQUE(w);
    const uint32_t hp = (w >> 4) & 3;
    if ((threadIdx.x & 31) == 0) g_O[cta * 9 * 512 + (((w >> 6) & 7) * 16 + (w & 15)) * 4 + (v < 8 ? (2 * hp + (v >> 2)) * 512 + (v & 3) : 8 * 512 + hp)] = pack(a * l, b * l);
  }
}

__device__ __forceinline__ uint32_t bad_heads(uint32_t bad_addr, int wr) {
  uint32_t bad;
  __syncwarp();
  asm volatile("ld.volatile.shared.u32 %0, [%1];" : "=r"(bad) : "r"(bad_addr) : "memory");
  return __shfl_sync(0xffffffffu, (bad >> (4 * wr)) & 15, 0);
}
__device__ __forceinline__ void repair_rows(int cta, int wr, uint32_t bad, int last_head, bool final) {
#pragma unroll 1
  for (uint32_t w = wr * 64; w < wr * 64 + 64; w++) {
    if (!((bad >> ((w >> 4) & 3)) & 1)) continue;
    if (final && ((w >> 4) & 3) != last_head) w |= 8u << 9;
    attn_slow_row(cta, w);
    w &= 511;
  }
  __syncwarp();
}
__device__ __forceinline__ void o_epilogue(float* o, uint32_t& x0, uint32_t& x1, int hp, uint32_t* odst, int lane, uint32_t bad_addr, int wr) {
  const int src = (lane & ~3) | ((hp + 1) & 3);
  float l0 = __shfl_sync(0xffffffffu, o[0], src), l1 = __shfl_sync(0xffffffffu, o[2], src);
  float sa = 0.f;
#pragma unroll
  for (int i = 0; i < 12; i++) sa += fabsf(o[i]);
  bool ok = (l0 <= 1.329228e36f) && (l1 <= 1.329228e36f) && (l0 > 0.f) && (l1 > 0.f) && (sa <= 3.0e38f);
  float i0 = 2.f * rcp_fast(l0), i1 = 2.f * rcp_fast(l1);
  uint32_t* d = odst + hp * 1024;
  d[0] = pack(o[4] * i0, o[5] * i0);
  d[32] = pack(o[6] * i1, o[7] * i1);
  d[512] = pack(o[8] * i0, o[9] * i0);
  d[544] = pack(o[10] * i1, o[11] * i1);
  if ((lane & 3) == ((hp + 2) & 3)) { x0 = pack(o[0] * i0, o[1] * i0); x1 = pack(o[2] * i1, o[3] * i1); }
  if (!ok) asm volatile("red.shared.or.b32 [%0], %1;" ::"r"(bad_addr), "r"(1u << (4 * wr + hp)) : "memory");
}

__device__ __forceinline__ void issue_pv(Att& a, uint32_t kdesc) {
  const uint32_t vdesc = kdesc + 192 + (LO_V - LO_K);
#pragma unroll
  for (int k = 0; k < 4; k++) wg_rs_n24<HI_V>(a.o, a.p[4 * k], a.p[4 * k + 1], a.p[4 * k + 2], a.p[4 * k + 3], vdesc + k * 48);
}
__device__ __forceinline__ void issue_att(Att& a, uint32_t kdesc) {
  issue_pv(a, kdesc);
  wg_rs_z_n64<HI_K>(a.s, a.q[0], a.q[1], a.q[2], a.q[3], kdesc);
  wg_rs_n64<HI_K>(a.s, a.q[4], a.q[5], a.q[6], a.q[7], kdesc + 16);
}
__device__ __forceinline__ void softmax_a(Att& a) {
#pragma unroll
  for (int i = 0; i < 9; i++) a.p[i] = pack(ex2(a.s[2 * i]), ex2(a.s[2 * i + 1]));
  a.s[18] = ex2(a.s[18]); a.s[19] = ex2(a.s[19]);
  pin<9>(a.p); pin<2>(a.s + 18);
}
__device__ __forceinline__ void softmax_b(Att& a) {
  a.p[9] = pack(a.s[18], a.s[19]);
#pragma unroll
  for (int i = 10; i < 16; i++) a.p[i] = pack(ex2(a.s[2 * i]), ex2(a.s[2 * i + 1]));
  pin<7>(a.p + 9);
}
__device__ __forceinline__ void first_tile(Att& a, int hp, int lane) {
  float m0 = fmaxf(a.s[0], a.s[1]), m1 = fmaxf(a.s[2], a.s[3]);
#pragma unroll
  for (int i = 4; i < 32; i += 4) { m0 = fmaxf(m0, fmaxf(a.s[i], a.s[i + 1])); m1 = fmaxf(m1, fmaxf(a.s[i + 2], a.s[i + 3])); }
  m0 = fmaxf(m0, __shfl_xor_sync(0xffffffffu, m0, 1)); m1 = fmaxf(m1, __shfl_xor_sync(0xffffffffu, m1, 1));
  m0 = fmaxf(m0, __shfl_xor_sync(0xffffffffu, m0, 2)); m1 = fmaxf(m1, __shfl_xor_sync(0xffffffffu, m1, 2));
  float n0 = -(m0 + MOFF), n1 = -(m1 + MOFF);
  float h0 = bf_round(n0), h1 = bf_round(n1);
  uint32_t e0 = pack(h0, n0 - h0), e1 = pack(h1, n1 - h1);
  n0 = h0 + bf_hi(e0); n1 = h1 + bf_hi(e1);
  if ((lane & 3) == ((hp + 1) & 3)) { a.q[4] = e0; a.q[5] = e1; }
#pragma unroll
  for (int i = 0; i < 32; i += 4) { a.s[i] += n0; a.s[i + 1] += n0; a.s[i + 2] += n1; a.s[i + 3] += n1; }
#pragma unroll
  for (int i = 0; i < 12; i++) a.o[i] = 0.f;
  pin<12>(a.o); pin<8>(a.q);
}
__device__ __forceinline__ void prefetch_q(int cta, int hp, int tid) {
  const uint4* src = reinterpret_cast<const uint4*>(g_Q) + (cta * 4 + hp) * 512 + tid;
  asm volatile("prefetch.global.L1 [%0];\nprefetch.global.L1 [%0 + 4096];" ::"l"(src) : "memory");
}
__device__ __forceinline__ void load_q(Att& a, int cta, int hp, int tid) {
  const uint4* src = reinterpret_cast<const uint4*>(g_Q) + (cta * 4 + hp) * 512 + tid;
  const uint4 u = __ldca(src), v = __ldca(src + 256);
  a.q[0] = u.x; a.q[1] = u.y; a.q[2] = u.z; a.q[3] = u.w; a.q[4] = v.x; a.q[5] = v.y; a.q[6] = v.z; a.q[7] = v.w;
}
__device__ __forceinline__ void h_epilogue(const float* acc, uint32_t* dst) {
#pragma unroll
  for (int b = 0; b < 4; b++) {
    uint32_t w[2][2];
#pragma unroll
    for (int i = 0; i < 2; i++) {
      float h[4];
#pragma unroll
      for (int e = 0; e < 4; e++) {
        const float g = acc[(2 * b + i) * 4 + e], u = acc[32 + (2 * b + i) * 4 + e];
        h[e] = fmaf(tanh_fast(0.5f * g), u, u);
      }
      w[0][i] = pack(h[0], h[1]); w[1][i] = pack(h[2], h[3]);
    }
    *reinterpret_cast<uint2*>(dst + 1024 * b) = make_uint2(w[0][0], w[0][1]);
    *reinterpret_cast<uint2*>(dst + 1024 * b + 32) = make_uint2(w[1][0], w[1][1]);
  }
}
template <int HP> __device__ __forceinline__ void store_kv_head(uint32_t (&pk)[2][9][2], uint32_t* kvp, int lane) {
  const int t = lane & 3;
  const bool up = t < HP;
#pragma unroll
  for (int rh = 0; rh < 2; rh++) {
    uint32_t* d = kvp + HP * SEQ * 20 + rh * 160;
    d[0] = up ? pk[0][2 * HP + 1][rh] : pk[0][2 * HP][rh];
    d[32] = up ? pk[0][2 * HP + 2][rh] : pk[0][2 * HP + 1][rh];
    d[96 + ((t - HP) & 3) - t] = up ? pk[1][2 * HP + 1][rh] : pk[1][2 * HP][rh];
    d[128 + ((t - HP) & 3) - t] = up ? pk[1][2 * HP + 2][rh] : pk[1][2 * HP + 1][rh];
    const uint32_t v9 = __shfl_sync(0xffffffffu, pk[1][2 * HP + 2][rh], (lane & ~3) | HP);
    d[64] = t == HP ? pk[0][2 * HP + 2][rh] : t == ((HP + 1) & 3) ? 0x3f803f80u : t == ((HP + 2) & 3) ? v9 : 0u;
  }
}

__device__ __forceinline__ void stage_partials(const float* acc, uint32_t dst, int tid) {
#pragma unroll
  for (int i = 0; i < 12; i++) {
    const float* v = acc + 8 * i;
    asm volatile("st.shared.v4.b32 [%0], {%1,%2,%3,%4};" ::"r"(dst + i * 4096 + tid * 16), "r"(pack(v[0], v[1])), "r"(pack(v[2], v[3])), "r"(pack(v[4], v[5])), "r"(pack(v[6], v[7])) : "memory");
  }
#pragma unroll
  for (int d = 0; d < 4; d++) {
    const float* v = acc + 128 + 8 * (d & 1) + 2 * (d >> 1);
    asm volatile("st.shared.v2.b32 [%0], {%1,%2};" ::"r"(dst + 49152 + d * 2048 + tid * 8), "r"(pack(v[0], v[1])), "r"(pack(v[4], v[5])) : "memory");
  }
}
__device__ __forceinline__ void load_residual(uint32_t* xv, const Params& prm, int m, int hh, int q, int tid) {
  const size_t off = (size_t)(128 * m + (tid >> 5) * 16 + ((tid & 31) >> 2)) * DM + 2 * (tid & 3);
  const uint32_t* xr = reinterpret_cast<const uint32_t*>(prm.x + off + 320 * hh + 64 * q);
  const uint32_t* xr2 = reinterpret_cast<const uint32_t*>(prm.x + off + 256 + 32 * hh + 16 * (q & 1) + (q >> 1) * 8 * DM);
#pragma unroll
  for (int i = 0; i < 16; i++) xv[i] = __ldg(xr + 4 * (i >> 1) + (i & 1) * 8 * (DM / 2));
  xv[16] = __ldg(xr2); xv[17] = __ldg(xr2 + 4);
}
__device__ __forceinline__ void final_epilogue(const float* acc, const uint32_t* xv, uint32_t recv, const Params& prm, int m, int hh, int q, int tid) {
  float own[4];
#pragma unroll
  for (int e = 0; e < 4; e++) {
    const int o = 32 + (e & 1) + 4 * (e >> 1);
    const float s0 = (q & 2) ? acc[o + 2] : acc[o], s1 = (q & 2) ? acc[o + 10] : acc[o + 8];
    own[e] = (q & 1) ? s1 : s0;
  }
  uint32_t v[3][18];
#pragma unroll
  for (int d = 0; d < 3; d++) {
#pragma unroll
    for (int i = 0; i < 4; i++)
      asm volatile("ld.shared.v4.b32 {%0,%1,%2,%3}, [%4];" : "=r"(v[d][4 * i]), "=r"(v[d][4 * i + 1]), "=r"(v[d][4 * i + 2]), "=r"(v[d][4 * i + 3])
                   : "r"(recv + d * 18432 + i * 4096 + tid * 16) : "memory");
    asm volatile("ld.shared.v2.b32 {%0,%1}, [%2];" : "=r"(v[d][16]), "=r"(v[d][17]) : "r"(recv + d * 18432 + 16384 + tid * 8) : "memory");
  }
  const size_t off = (size_t)(128 * m + (tid >> 5) * 16 + ((tid & 31) >> 2)) * DM + 2 * (tid & 3);
  const bool odd = tid & 1;
  uint32_t* o1 = reinterpret_cast<uint32_t*>(prm.out + off + 320 * hh + 64 * q) + (odd ? 3 : 0);
  uint32_t* o2 = reinterpret_cast<uint32_t*>(prm.out + off + 256 + 32 * hh + 16 * (q & 1) + (q >> 1) * 8 * DM) + (odd ? 3 : 0);
  uint32_t r[18];
#pragma unroll
  for (int i = 0; i < 18; i++) {
    const float lo = (i < 16 ? acc[2 * i] : own[2 * (i - 16)]) + ((bf_lo(v[0][i]) + bf_lo(v[1][i])) + bf_lo(v[2][i]));
    const float hi = (i < 16 ? acc[2 * i + 1] : own[2 * (i - 16) + 1]) + ((bf_hi(v[0][i]) + bf_hi(v[1][i])) + bf_hi(v[2][i]));
    r[i] = pack(fmaf(lo, 0.5f, bf_lo(xv[i])), fmaf(hi, 0.5f, bf_hi(xv[i])));
  }
#pragma unroll
  for (int i = 0; i < 9; i++) {
    const uint32_t A = i < 8 ? r[4 * (i >> 1) + (i & 1)] : r[16], B = i < 8 ? r[4 * (i >> 1) + 2 + (i & 1)] : r[17];
    const uint32_t y = __shfl_xor_sync(0xffffffffu, odd ? A : B, 1);
    *reinterpret_cast<uint2*>(i < 8 ? o1 + 8 * (i >> 1) + (i & 1) * 8 * (DM / 2) : o2) = odd ? make_uint2(y, B) : make_uint2(A, y);
  }
}

__global__ void __launch_bounds__(384, 1) fused_kernel(const __grid_constant__ Params prm) {
  extern __shared__ __align__(1024) uint8_t smem[];
  const uint32_t sb = (uint32_t)__cvta_generic_to_shared(smem);
  const uint32_t bar = sb + SM_BAR;
  const int m = blockIdx.x & 15, j = blockIdx.x >> 4;
  const int cta = m * 8 + j;
  const int wr = __shfl_sync(0xffffffffu, (int)(threadIdx.x >> 5), 0);
  const int wg = wr >> 2;
  const int lane = threadIdx.x & 31;
  STAMP(0);
  if (wr == 8) {
    if (lane < 9) {
      mbar_init(bar + 8 * (B_X + lane), 1);
      asm volatile("fence.proxy.async.shared::cta;" ::: "memory");
      mbar_expect(bar + 8 * (B_X + lane), 16384);
      tma2d(sb + SM_XN + lane * 16384, &prm.xm, bar + 8 * (B_X + lane), 64 * lane, 128 * m);
    }
  } else if (wr == 9) {
    for (int i = lane; i < B_N; i += 32) {
      if (i >= B_X && i < B_NR) continue;
      const bool full = i < B_QE || (i >= B_BF && i < B_BE) || (i >= B_GF && i < B_GE) || (i >= B_KF && i < B_KE) || i == B_OL || i == B_RX;
      mbar_init(bar + 8 * i, full ? 1 : i >= B_NR ? 4 : 8);
    }
    asm volatile("fence.proxy.async.shared::cta;" ::: "memory");
    asm volatile("st.shared.u32 [%0], 0;" ::"r"(sb + SM_BAD) : "memory");
    if (sb & 1023) asm volatile("trap;");
  } else if (wr == 10) {
    if (lane >= 1 && lane < 18) asm volatile("prefetch.tensormap [%0];" ::"l"(&prm.xm + lane) : "memory");
  } else if (wr == 11) {
    if (lane < 6 && m < 9) pf2d((lane & 1) ? &prm.wqkv8 : &prm.wqkv64, 576 * (lane >> 1) + 72 * j + 64 * (lane & 1), 64 * m);
  }
  __syncthreads();

  if (wg == 2) {
    asm volatile("setmaxnreg.dec.sync.aligned.u32 24;");
    const int pw = wr & 3;
    const uint32_t epoch = *(volatile uint32_t*)FLAG_EPOCH(cta);
    const int hh = j & 1;
#define ACOL(A) (320 * hh + 64 * (((j >> 1) + 1 + (A)) & 3))
    if (pw == 0) {
      if (lane == 0) {
        uint64_t pol;
        asm volatile("createpolicy.fractional.L2::evict_first.b64 %0, 1.0;" : "=l"(pol));
#pragma unroll 1
        for (int kb = 0; kb < 9; kb++) {
          const int s = kb % 3;
          if (kb >= 3) mbar_wait(bar + 8 * (B_QE + s), (kb / 3 - 1) & 1);
          const uint32_t fb = bar + 8 * (B_QF + s), dst = sb + SM_RING + s * QST;
          mbar_expect(fb, QST);
#pragma unroll
          for (int p = 0; p < 3; p++) {
            tma2d(dst + p * 8192, &prm.wqkv64, fb, 576 * p + 72 * j, 64 * kb);
            tma2d(dst + 24576 + p * 1024, &prm.wqkv8, fb, 576 * p + 72 * j + 64, 64 * kb);
          }
        }
        int col = 576 * j, kr = 0;
#pragma unroll 1
        for (int s = 0; s < 81; s++) {
          const int slot = s & 3;
          if (s >= 4) mbar_wait(bar + 8 * (B_BE + slot), ((s >> 2) - 1) & 1);
          else if (s != 2) mbar_wait(bar + 8 * (B_QE + (s == 3 ? 2 : s)), 0);
          const uint32_t fb = bar + 8 * (B_BF + slot), dst = sb + SM_RING + slot * BST;
          mbar_expect(fb, BST);
          tma2d_h(dst, &prm.wg, fb, col, kr, pol);
          tma2d_h(dst + 8192, &prm.wu, fb, col, kr, pol);
          if ((kr += 64) == 576) { kr = 0; col += 64; }
        }
        mbar_arrive(bar + 8 * (B_BF + 1));
        uint32_t seen = flag_wait_v(FLAG_H(cta), 9 * epoch + 1) - 9 * epoch;
        fence_async();
#pragma unroll 1
        for (int b = 0; b < 26; b++) {
          const int st = b & 3;
          if (b >= 4) mbar_wait(bar + 8 * (B_GE + st), ((b >> 2) - 1) & 1);
          else if (b) mbar_wait(bar + 8 * (B_BE + (b == 1 ? 1 : b == 2 ? 3 : 0)), b != 3);
          const uint32_t fb = bar + 8 * (B_GF + st), dst = sb + st * G2ST;
          if (b == 0) STAMPW(16);
          mbar_expect(fb, G2ST);
          if (b < 24) {
            const int jj = (b < 10 || b == 20 || b == 21) ? j : (j ^ 1), lb = b < 10 ? b : b < 20 ? b - 10 : 10 + (b & 1);
            bulk_g2s(dst, g_H + (m * 576 + 72 * jj + 6 * lb) * 512, 12288, fb);
#pragma unroll
            for (int a = 0; a < 4; a++) tma5d(dst + 12288 + a * 6144, &prm.wd[0], fb, ACOL(a), 36 * jj + 3 * lb);
            tma5d(dst + 36864, &prm.wd[1 + hh], fb, 0, 36 * jj + 3 * lb);
          } else {
            const int r = b - 24;
            bulk_g2s(dst, g_O + ((cta & ~1) + r) * 9 * 512 + r * 1024, 12288, fb);
#pragma unroll
            for (int a = 0; a < 4; a++) tma3d(dst + 12288 + a * 6144, &prm.wo3[0], fb, ACOL(a), 4 * (j & 6) + 5 * r);
            tma3d(dst + 36864, &prm.wo3[1 + hh], fb, 0, 4 * (j & 6) + 5 * r);
          }
          if (b == 0) STAMPW(17);
          if (b < 23) {
            const int n = b + 1, lb = n < 10 ? n : n < 20 ? n - 10 : 10 + (n & 1), need = (3 * lb + 6) >> 2;
            if (n == 10 || n == 20 || n == 22) seen = 0;
            if (seen < need) { seen = flag_wait_v(FLAG_H((n < 10 || n == 20 || n == 21) ? cta : (cta ^ 1)), 9 * epoch + need) - 9 * epoch; fence_async(); }
          } else if (b == 23) { flag_wait(FLAG_O(cta), 2 * epoch + 1); flag_wait(FLAG_O(cta ^ 1), 2 * epoch + 1); fence_async(); }
        }
        mbar_wait(bar + 8 * (B_GE + 1), 0);
        mbar_expect(bar + 8 * B_OL, 98304);
#pragma unroll 1
        for (int i = 0; i < 4; i++) {
          tma3d(sb + SM_LB + i * 4096, &prm.wo2[0], bar + 8 * B_OL, ACOL(3), 8 * i + 3);
          tma3d(sb + SM_LB + 24576 + i * 4096, &prm.wo2[1 + hh], bar + 8 * B_OL, 0, 8 * i + 3);
          tma3d(sb + SM_LB + 16384 + i * 2048, &prm.wo16[0], bar + 8 * B_OL, ACOL(3), 8 * i);
          tma3d(sb + SM_LB + 40960 + i * 2048, &prm.wo16[1 + hh], bar + 8 * B_OL, 0, 8 * i);
        }
      }
    } else if (pw == 1) {
      if (lane == 0) {
        flag_wait(FLAG_KV(0, j), 16 * epoch + 16);
        fence_async();
        STAMPW(18);
        int slot = 0, ph = 1, vrow = 0;
        const int hx = (j & 1) * 3;
#pragma unroll 1
        for (int u = 0; u <= 128; u++) {
          if (u >= 3) mbar_wait(bar + 8 * (B_KE + slot), ph);
          const uint32_t fb = bar + 8 * (B_KF + slot), dst = sb + SM_KV + slot * KVST;
          const int krow = (4 * j + ((u >> 5) ^ hx)) * 256 + ((u + 2 * m) & 31) * 8;
          if (u == 0) vrow = krow;
          mbar_expect(fb, u < 128 ? KVST : KVST / 2);
          if (u < 128) tma2d(dst, &prm.kv, fb, 0, krow);
          tma2d(dst + 3072, &prm.kv, fb, 128, vrow);
          vrow = krow;
          if (++slot == 3) { slot = 0; ph ^= 1; }
          if (u == 16) { flag_wait(FLAG_KV(1, j), 16 * epoch + 16); fence_async(); }
        }
        mbar_wait(bar + 8 * (B_GE + 1), 0);
      }
      __syncwarp();
      bool pending = lane < 8;
      for (uint32_t tries = 0; __any_sync(0xffffffffu, pending); tries++) {
        if (pending) {
          uint32_t v;
          asm volatile("ld.acquire.gpu.global.u32 %0, [%1];" : "=r"(v) : "l"(FLAG_O(m * 8 + lane)) : "memory");
          if ((int)(v - (2 * epoch + 2)) >= 0) {
            fence_async();
            const uint32_t* src = g_O + (m * 8 + lane) * 9 * 512;
            bulk_g2s(sb + SM_LA + lane * 4096, src + ((lane & 1) ? 0 : 3072), 4096, bar + 8 * B_OL);
            bulk_g2s(sb + (lane < 2 ? SM_LX0 : SM_LX1 - 4096) + lane * 2048, src + 4096, 2048, bar + 8 * B_OL);
            pending = false;
          }
        }
        if (tries > 0x1000000u) asm volatile("trap;");
      }
      if (lane == 0) STAMPW(19);
    } else if (pw == 2) {
      if (lane == 0) {
        mbar_wait(bar + 8 * B_SK1, 0);
        STAMPW(22);
        fence_gpu(); flag_add(FLAG_KV(0, j));
        STAMPW(20);
        mbar_wait(bar + 8 * B_SK2, 0);
        fence_gpu(); flag_add(FLAG_KV(1, j));
#pragma unroll 1
        for (int t = 0; t < 9; t++) { mbar_wait(bar + 8 * B_SH, t & 1); fence_gpu(); flag_add(FLAG_H(cta)); }
        mbar_wait(bar + 8 * B_SO1, 0);
        fence_gpu(); flag_add(FLAG_O(cta));
        mbar_wait(bar + 8 * B_SO2, 0);
        fence_gpu(); flag_add(FLAG_O(cta));
        STAMPW(21);
      }
    } else if (lane == 0) {
      mbar_wait(bar + 8 * (B_X + 8), 0);
#pragma unroll 1
      for (int b = m; b < 162; b += 16) {
        const int s = b >> 1;
        pf2d((b & 1) ? &prm.wu : &prm.wg, 576 * j + 64 * (s / 9), 64 * (s % 9));
      }
      flag_wait(FLAG_H(cta), 9 * epoch + PF_WD);
#pragma unroll 1
      for (int b = m + 16 * hh; b < 216; b += 32) pf5d(&prm.wd[0], 64 * (b % 9), 72 * (j >> 1) + 3 * (b / 9));
      if (m < 9) { pf3d(&prm.wo3[0], 64 * m, 4 * j); pf3d(&prm.wo3[0], 64 * m, 4 * j + 1); if (!hh) pf3d(&prm.wo16[0], 64 * m, 4 * j); }
      mbar_wait(bar + 8 * B_SP, 0);
      const int q = j >> 1;
#pragma unroll 1
      for (int a = 0; a < 3; a++) {
        const int d = (q + 1 + a) & 3;
        uint4* dst = g_P + ((m * 8 + 2 * d + hh) * 3 + a) * 1152;
        bulk_s2g(dst, sb + SM_SEND + a * 16384, 16384);
        bulk_s2g(dst + 1024, sb + SM_SEND + 49152 + d * 2048, 2048);
      }
      asm volatile("cp.async.bulk.commit_group;\ncp.async.bulk.wait_group 0;" ::: "memory");
      fence_gpu();
#pragma unroll 1
      for (int a = 0; a < 3; a++) flag_add(FLAG_P(m * 8 + 2 * ((q + 1 + a) & 3) + hh));
      STAMPW(15);
      flag_wait(FLAG_P(cta), 3 * epoch + 3);
      fence_async();
      STAMPW(25);
      mbar_expect(bar + 8 * B_RX, 55296);
      bulk_g2s(sb + SM_RECV, g_P + cta * 3 * 1152, 55296, bar + 8 * B_RX);
      *FLAG_EPOCH(cta) = epoch + 1;
    }
  } else {
    const int tid = threadIdx.x;
    const int t = lane & 3;
    const uint32_t l0 = lane == 0;
    const uint32_t adesc = (((sb + SM_XN + wg * 8192) & 0x3FFFF) >> 4) | LO_A;
    const uint32_t bdesc = (((sb + SM_RING) & 0x3FFFF) >> 4) | LO_B;
    const uint32_t kdesc0 = (((sb + SM_KV) & 0x3FFFF) >> 4) | LO_K;
    const int hx = (j & 1) * 3;
    float accA[64], accB[64];
    Att a;
    uint32_t gs = 0;
#define G1_ISSUE(ACC, AD, BD) _Pragma("unroll") for (int k = 0; k < 4; k++) wg_ss_n128<HI_SW128, HI_SW128>(ACC, (AD) + k * 2, (BD) + k * 128);
#define G1_ISSUE_Z(ACC, BD)                                                                                    \
  wg_ss_z_n128<HI_SW128, HI_SW128>(ACC, adesc, BD);                                                            \
  _Pragma("unroll") for (int k = 1; k < 4; k++) wg_ss_n128<HI_SW128, HI_SW128>(ACC, adesc + k * 2, (BD) + k * 128);
#define BF_BAR (bar + 8 * B_BF + 8 * (gs & 3))
#define BF_PH ((gs >> 2) & 1)
#define G1_ONLY() { mbar_wait(BF_BAR, BF_PH); wg_fence(); G1_ISSUE(accA, adesc + gs * 1024, bdesc + (gs & 3) * 1024) wg_commit(); wg_wait<1>(); \
                    mbar_arrive_if(bar + 8 * B_BE + 8 * ((gs - 1) & 3), l0); gs++; }
    {
      const int lr = wr * 16 + (lane & 15);
      uint32_t ra[4];
#pragma unroll
      for (int k = 0; k < 4; k++) ra[k] = sb + SM_XN + lr * 128 + (((2 * k + (lane >> 4)) ^ (lr & 7)) << 4);
      STAMP(26);
      float cs[2][4] = {}, q0 = 0.f, q1 = 0.f, q2 = 0.f, q3 = 0.f;
#pragma unroll 1
      for (int c = 0; c < 9; c++) {
        mbar_wait(bar + 8 * (B_X + c), 0);
        if (c == 0) STAMP(27);
        if (c == 8) STAMP(28);
        uint32_t v[4][4];
#pragma unroll
        for (int k = 0; k < 4; k++) ldsm4(v[k], ra[k] + c * 16384);
#pragma unroll
        for (int k = 0; k < 4; k++) {
          mma_ones(cs[k & 1], v[k]);
#pragma unroll
          for (int e = 0; e < 4; e += 2) {
            const float x0 = bf_lo(v[k][e]), x1 = bf_hi(v[k][e]), y0 = bf_lo(v[k][e + 1]), y1 = bf_hi(v[k][e + 1]);
            q0 = fmaf(x0, x0, q0); q1 = fmaf(x1, x1, q1); q2 = fmaf(y0, y0, q2); q3 = fmaf(y1, y1, q3);
          }
        }
      }
      STAMP(11);
      asm volatile("setmaxnreg.inc.sync.aligned.u32 240;");
      const float mean0 = (cs[0][0] + cs[1][0]) * (1.f / 576.f), mean1 = (cs[0][2] + cs[1][2]) * (1.f / 576.f);
      q0 += q1; q2 += q3;
      q0 += __shfl_xor_sync(0xffffffffu, q0, 1); q2 += __shfl_xor_sync(0xffffffffu, q2, 1);
      q0 += __shfl_xor_sync(0xffffffffu, q0, 2); q2 += __shfl_xor_sync(0xffffffffu, q2, 2);
      float var0 = fmaf(q0, 1.f / 576.f, -mean0 * mean0), var1 = fmaf(q2, 1.f / 576.f, -mean1 * mean1);
      if (__any_sync(0xffffffffu, !(mean0 * mean0 <= 8.f * var0) || !(mean1 * mean1 <= 8.f * var1))) {
        q0 = q2 = 0.f;
#pragma unroll 1
        for (int i = 0; i < 36; i++) {
          uint32_t v[4];
          ldsm4(v, ((ra[0] + (i >> 2) * 16384) ^ ((i & 3) << 5)));
#pragma unroll
          for (int e = 0; e < 4; e += 2) {
            const float x0 = bf_lo(v[e]) - mean0, x1 = bf_hi(v[e]) - mean0, y0 = bf_lo(v[e + 1]) - mean1, y1 = bf_hi(v[e + 1]) - mean1;
            q0 = fmaf(x0, x0, fmaf(x1, x1, q0)); q2 = fmaf(y0, y0, fmaf(y1, y1, q2));
          }
        }
        q0 += __shfl_xor_sync(0xffffffffu, q0, 1); q2 += __shfl_xor_sync(0xffffffffu, q2, 1);
        q0 += __shfl_xor_sync(0xffffffffu, q0, 2); q2 += __shfl_xor_sync(0xffffffffu, q2, 2);
        var0 = q0 * (1.f / 576.f); var1 = q2 * (1.f / 576.f);
      }
      const float inv0 = rcp_fast(bf_round(sqrt_fast(bf_round(bf_round(var0) + 1e-5f)))), inv1 = rcp_fast(bf_round(sqrt_fast(bf_round(bf_round(var1) + 1e-5f))));
      const uint32_t mb0 = pack(mean0, mean0), mb1 = pack(mean1, mean1);
      const uint32_t h0 = pack(inv0, inv0), h1 = pack(inv1, inv1);
      const uint32_t e0 = pack(inv0 - bf_lo(h0), inv0 - bf_lo(h0)), e1 = pack(inv1 - bf_lo(h1), inv1 - bf_lo(h1));
#define NORM_STORE(C)                                                                                          \
  {                                                                                                            \
    _Pragma("unroll") for (int k = 0; k < 4; k++)                                                              \
      stsm4(ra[k] + (C) * 16384, bscale2(bsub2(v[k][0], mb0), h0, e0), bscale2(bsub2(v[k][1], mb1), h1, e1),   \
            bscale2(bsub2(v[k][2], mb0), h0, e0), bscale2(bsub2(v[k][3], mb1), h1, e1));                       \
    asm volatile("fence.proxy.async.shared::cta;" ::: "memory");                                               \
    __syncwarp();                                                                                              \
    mbar_arrive_if(bar + 8 * B_NR + 8 * wg, l0);                                                               \
  }
      float aq[96], ar[12];
      {
        uint32_t v[4][4];
#pragma unroll
        for (int k = 0; k < 4; k++) ldsm4(v[k], ra[k]);
        NORM_STORE(0)
      }
#pragma unroll
      for (int i = 0; i < 96; i++) aq[i] = 0.f;
#pragma unroll
      for (int i = 0; i < 12; i++) ar[i] = 0.f;
      pin<96>(aq); pin<12>(ar);
      STAMP(1);
      const uint32_t rdesc = (((sb + SM_RING + 24576) & 0x3FFFF) >> 4) | LO_R;
      uint32_t s = 0, ph = 0;
#pragma unroll 1
      for (int kb = 0; kb < 9; kb++) {
        uint32_t v[4][4];
        const int cn = kb < 8 ? kb + 1 : 8;
#pragma unroll
        for (int k = 0; k < 4; k++) ldsm4(v[k], ra[k] + cn * 16384);
        mbar_wait(bar + 8 * B_QF + 8 * s, ph);
        mbar_wait(bar + 8 * B_NR + 8 * wg, kb & 1);
        wg_fence();
#pragma unroll
        for (int k = 0; k < 4; k++) {
          wg_ss_n192<HI_SW128, HI_SW128>(aq, adesc + kb * 1024 + k * 2, bdesc + s * (QST >> 4) + k * 128);
          wg_ss_n24<HI_SW128, HI_R>(ar, adesc + kb * 1024 + k * 2, rdesc + s * (QST >> 4) + k * 16);
        }
        wg_commit();
        if (kb < 8) NORM_STORE(cn)
        wg_wait<1>();
        mbar_arrive_if(bar + 8 * B_QE + (s == 0 ? 16 : 8 * s - 8), l0 & (kb > 0));
        if (++s == 3) { s = 0; ph ^= 1; }
      }
      wg_wait<0>();
      pin<96>(aq); pin<12>(ar);
      mbar_arrive_if(bar + 8 * (B_QE + 2), l0);
      STAMP(2);
      uint32_t* kvp = g_KV + (size_t)(4 * j) * SEQ * 20 + (16 * m + 2 * wr) * 160 + lane;
      uint32_t pk[2][9][2];
#pragma unroll
      for (int p = 0; p < 2; p++)
#pragma unroll
        for (int i = 0; i < 9; i++) {
          const float* src = i < 8 ? &aq[(8 * (p + 1) + i) * 4] : &ar[4 * (p + 1)];
          pk[p][i][0] = pack(src[0], src[1]); pk[p][i][1] = pack(src[2], src[3]);
        }
      if (hx) store_kv_head<3>(pk, kvp, lane); else store_kv_head<0>(pk, kvp, lane);
      __syncwarp();
      mbar_arrive_if(bar + 8 * B_SK1, l0);
      STAMP(3);
      mbar_wait(bar + 8 * B_BF, 0);
      wg_fence();
      G1_ISSUE_Z(accA, bdesc)
      wg_commit();
      gs = 1;
      uint32_t pq[9][2];
#pragma unroll
      for (int i = 0; i < 9; i++) {
        const float* src = i < 8 ? &aq[i * 4] : &ar[0];
        pq[i][0] = pack(bf_round(src[0]) * QSCALE, bf_round(src[1]) * QSCALE); pq[i][1] = pack(bf_round(src[2]) * QSCALE, bf_round(src[3]) * QSCALE);
      }
      pin<18>(&pq[0][0]);
#pragma unroll 1
      while (gs < 3) G1_ONLY()
      if (hx) store_kv_head<0>(pk, kvp, lane); else store_kv_head<3>(pk, kvp, lane);
      store_kv_head<1>(pk, kvp, lane);
      store_kv_head<2>(pk, kvp, lane);
      __syncwarp();
      mbar_arrive_if(bar + 8 * B_SK2, l0);
      G1_ONLY()
      uint4* qp = reinterpret_cast<uint4*>(g_Q) + cta * 4 * 512 + tid;
#pragma unroll
      for (int hp = 0; hp < 4; hp++) {
        const bool up = t < hp;
        const uint4 u = make_uint4(up ? pq[2 * hp + 1][0] : pq[2 * hp][0], up ? pq[2 * hp + 1][1] : pq[2 * hp][1],
                                   up ? pq[2 * hp + 2][0] : pq[2 * hp + 1][0], up ? pq[2 * hp + 2][1] : pq[2 * hp + 1][1]);
        const uint4 v = make_uint4(t == hp ? pq[2 * hp + 2][0] : 0u, t == hp ? pq[2 * hp + 2][1] : 0u, 0u, 0u);
        qp[hp * 512] = u; qp[hp * 512 + 256] = v;
        if (hp == 0 || (hp == 3 && hx)) { a.q[0] = u.x; a.q[1] = u.y; a.q[2] = u.z; a.q[3] = u.w; a.q[4] = v.x; a.q[5] = v.y; }
      }
      a.q[6] = __shfl_sync(0xffffffffu, lane, 0); a.q[7] = __shfl_sync(0xffffffffu, lane >> 1, 1);
#pragma unroll
      for (int i = 0; i < 16; i++) a.p[i] = 0;
#pragma unroll
      for (int i = 0; i < 12; i++) a.o[i] = 0.f;
      pin<16>(a.p); pin<12>(a.o); pin<8>(a.q);
    }
    static_assert(NG0 == 5, "slot / item alignment below assumes NG0 == 5");
    G1_ONLY()
    STAMP(4);
    mbar_wait(BF_BAR, BF_PH);
    mbar_wait(bar + 8 * B_KF, 0);
    STAMP(23);
    uint32_t k8 = 0, kph = 0, kd = kdesc0;
    uint32_t it = 0;
    uint32_t ox0 = 0, ox1 = 0;
    bool special = true;
    uint32_t* hdst = g_H + ((m * 576 + 72 * j + (t >> 1)) * 128 + 16 * wr + (lane >> 2)) * 4 + 2 * (t & 1);
    uint32_t ad = adesc + NG0 * 1024, bd = bdesc + (gs & 3) * 1024;

#define ITEM_FIRST()                                                                                           \
  {                                                                                                            \
    pin<12>(a.o);                                                                                              \
    if (it != 0) o_epilogue(a.o, ox0, ox1, ((it >> 5) - 1) ^ hx, g_O + cta * 9 * 512 + wr * 64 + lane, lane, sb + SM_BAD, wr); \
    if (it == 96) mbar_arrive_if(bar + 8 * B_SO1, l0 & (bad_heads(sb + SM_BAD, wr) == 0));                     \
    first_tile(a, (it >> 5) ^ hx, lane);                                                                       \
  }
#define ITEM_NEXTQ() { if (it & 2) load_q(a, cta, ((it >> 5) + 1) ^ hx, tid); else prefetch_q(cta, ((it >> 5) + 1) ^ hx, tid); }
#define KV_ADVANCE() { kd += 384; k8 += 8; if (k8 == 24) { k8 = 0; kd = kdesc0; kph ^= 1; } it++; special = ((it + 3) & 31) < 4; }
#define WAIT_UNLESS(OK, BA, PA, BB, PB) if (__builtin_expect(!__all_sync(0xffffffffu, OK), 0)) { mbar_wait(BA, PA); mbar_wait(BB, PB); }
#define EPI_STEP(ACCN, ACCO)                                                                                   \
  {                                                                                                            \
    wg_fence();                                                                                                \
    G1_ISSUE_Z(ACCN, bd)                                                                                       \
    wg_commit();                                                                                               \
    wg_wait<1>();                                                                                              \
    pin<64>(ACCO);                                                                                             \
    mbar_arrive_if(bar + 8 * B_BE + 8 * ((gs - 1) & 3), l0);                                                   \
    gs++;                                                                                                      \
    ad = adesc + 1024; bd = bdesc + (gs & 3) * 1024;                                                           \
    const uint32_t ok = mbar_test(BF_BAR, BF_PH);                                                              \
    h_epilogue(ACCO, hdst);                                                                                    \
    hdst += 4096;                                                                                              \
    __syncwarp();                                                                                              \
    mbar_arrive_if(bar + 8 * B_SH, l0);                                                                        \
    WAIT_UNLESS(ok, BF_BAR, BF_PH, BF_BAR, BF_PH)                                                              \
  }
#define ATT_LOOP1(ACC, ITEMS)                                                                                  \
  do {                                                                                                         \
    wg_fence();                                                                                                \
    issue_att(a, kd);                                                                                          \
    wg_commit();                                                                                               \
    G1_ISSUE(ACC, ad, bd)                                                                                      \
    wg_commit();                                                                                               \
    wg_wait<1>();                                                                                              \
    pin<32>(a.s);                                                                                              \
    mbar_arrive_if(bar + 8 * B_BE + 8 * ((gs - 1) & 3), l0);                                                   \
    mbar_arrive_if(bar + 8 * B_KE + k8, l0);                                                                   \
    TRACE()                                                                                                    \
    if (ITEMS) { if (__builtin_expect(special, 0)) { if (it & 1) ITEM_NEXTQ() else if (!(it & 2)) ITEM_FIRST() } } \
    else __syncwarp();                                                                                         \
    gs++;                                                                                                      \
    KV_ADVANCE()                                                                                               \
    ad += 1024; bd = bdesc + (gs & 3) * 1024;                                                                  \
    const uint32_t ok = mbar_test(BF_BAR, BF_PH) & mbar_test(bar + 8 * B_KF + k8, kph);                        \
    softmax_a(a);                                                                                              \
    WAIT_UNLESS(ok, BF_BAR, BF_PH, bar + 8 * B_KF + k8, kph)                                                   \
    softmax_b(a);                                                                                              \
    pin<8>(a.q);                                                                                               \
  } while (ad != adesc + 9 * 1024);
#pragma unroll 1
    for (int pr = 0;; pr++) {
      ATT_LOOP1(accA, true)
      if (pr == 4) break;
      EPI_STEP(accB, accA)
      ATT_LOOP1(accB, false)
      EPI_STEP(accA, accB)
    }
    STAMP(5);
    wg_wait<0>();
    pin<64>(accA);
    mbar_arrive_if(bar + 8 * B_BE, l0);
    h_epilogue(accA, hdst);
    __syncwarp();
    mbar_arrive_if(bar + 8 * B_SH, l0);
    STAMP(6);
    mbar_wait(bar + 8 * B_GF, 0);
    STAMP(12);

    float acc2[144];
    const uint32_t a2desc = (((sb + wg * 1024) & 0x3FFFF) >> 4) | LO_O;
    const uint32_t b2desc = (((sb + 12288) & 0x3FFFF) >> 4) | LO_B48;
    uint32_t gb = 0;
    ad = a2desc; bd = b2desc;
#define G2_LO(K) wg_ss_n128<HI_O, HI_SW128>(acc2, ad + (K) * 256, bd + (K) * 128);
#define G2_HI(K) wg_ss_n160<HI_O, HI_SW128>(acc2 + 64, ad + (K) * 256, bd + (K) * 128 + 768);
#define ATT_PAIR(ZERO)                                                                                         \
  {                                                                                                            \
    wg_fence();                                                                                                \
    issue_att(a, kd);                                                                                          \
    wg_commit();                                                                                               \
    if (ZERO) { wg_ss_z_n128<HI_O, HI_SW128>(acc2, ad, bd); wg_ss_z_n160<HI_O, HI_SW128>(acc2 + 64, ad, bd + 768); } \
    else { G2_LO(0) G2_HI(0) }                                                                                 \
    G2_LO(1)                                                                                                   \
    wg_commit();                                                                                               \
    wg_wait<1>();                                                                                              \
    pin<32>(a.s);                                                                                              \
    mbar_arrive_if(bar + 8 * B_KE + k8, l0);                                                                   \
    if (!(ZERO)) mbar_arrive_if(bar + 8 * B_GE + 8 * ((gb - 1) & 3), l0);                                      \
    TRACE()                                                                                                    \
    if (!(ZERO)) { if (__builtin_expect(it == 96, 0)) ITEM_FIRST() }                                           \
    KV_ADVANCE()                                                                                               \
    uint32_t ok = mbar_test(bar + 8 * B_KF + k8, kph);                                                         \
    softmax_a(a);                                                                                              \
    WAIT_UNLESS(ok, bar + 8 * B_KF + k8, kph, bar + 8 * B_KF + k8, kph)                                        \
    softmax_b(a);                                                                                              \
    pin<8>(a.q);                                                                                               \
    wg_fence();                                                                                                \
    issue_att(a, kd);                                                                                          \
    wg_commit();                                                                                               \
    G2_HI(1) G2_LO(2) G2_HI(2)                                                                                 \
    wg_commit();                                                                                               \
    wg_wait<1>();                                                                                              \
    pin<32>(a.s);                                                                                              \
    mbar_arrive_if(bar + 8 * B_KE + k8, l0);                                                                   \
    TRACE()                                                                                                    \
    if (!(ZERO)) { if (__builtin_expect(it - 93 < 3, 0)) ITEM_NEXTQ() }                                        \
    KV_ADVANCE()                                                                                               \
    gb++;                                                                                                      \
    ad = a2desc + (gb & 3) * 2688; bd = b2desc + (gb & 3) * 2688;                                              \
         \
    const uint32_t nb = gb == 26 ? bar + 8 * (B_GE + 3) : bar + 8 * B_GF + 8 * (gb & 3), np = gb == 26 ? 1 : (gb >> 2) & 1; \
    ok = mbar_test(nb, np) & mbar_test(bar + 8 * B_KF + k8, kph);                                              \
    softmax_a(a);                                                                                              \
    WAIT_UNLESS(ok, nb, np, bar + 8 * B_KF + k8, kph)                                                          \
    softmax_b(a);                                                                                              \
    pin<8>(a.q);                                                                                               \
    if (!(ZERO) && __builtin_expect(gb == 23, 0)) {      \
      const uint32_t bad = bad_heads(sb + SM_BAD, wr);                                                         \
      if (bad) { repair_rows(cta, wr, bad, 3 ^ hx, false); mbar_arrive_if(bar + 8 * B_SO1, l0); }              \
    }                                                                                                          \
  }
    ATT_PAIR(true)
    do ATT_PAIR(false) while (gb != 26);
    STAMP(13);
#define ATT_ONLY()                                                                                             \
  {                                                                                                            \
    wg_fence();                                                                                                \
    issue_att(a, kd);                                                                                          \
    wg_commit();                                                                                               \
    wg_wait<0>();                                                                                              \
    pin<32>(a.s);                                                                                              \
    mbar_arrive_if(bar + 8 * B_KE + k8, l0);                                                                   \
    TRACE()                                                                                                    \
    KV_ADVANCE()                                                                                               \
    const uint32_t ok = mbar_test(bar + 8 * B_KF + k8, kph);                                                   \
    softmax_a(a);                                                                                              \
    WAIT_UNLESS(ok, bar + 8 * B_KF + k8, kph, bar + 8 * B_KF + k8, kph)                                        \
    softmax_b(a);                                                                                              \
  }
    float fin[48];
    wg_wait<0>(); pin<144>(acc2); mbar_arrive_if(bar + 8 * (B_GE + 1), l0);
    stage_partials(acc2, sb + SM_SEND, fresh_tid());
    asm volatile("fence.proxy.async.shared::cta;" ::: "memory");
    __syncwarp();
    mbar_arrive_if(bar + 8 * B_SP, l0);
    do ATT_ONLY() while (it != 128);
    STAMP(7);
    wg_fence();
    issue_pv(a, kd);
    wg_commit();
    int tid2, bid2;
    asm volatile("mov.u32 %0, %%tid.x;" : "=r"(tid2));
    asm volatile("mov.u32 %0, %%ctaid.x;" : "=r"(bid2));
    const int m2 = bid2 & 15, j2 = bid2 >> 4;
    wg_wait<0>();
    pin<12>(a.o);
    {
      uint32_t* od = g_O + cta * 9 * 512 + wr * 64 + lane;
      o_epilogue(a.o, ox0, ox1, 3 ^ hx, od, lane, sb + SM_BAD, wr);
      od += 4096 + ((t + 2) & 3) - t;
      od[0] = ox0; od[32] = ox1;
      const uint32_t bad = bad_heads(sb + SM_BAD, wr);
      if (bad) repair_rows(cta, wr, bad, 3 ^ hx, true);
    }
    __syncwarp();
    mbar_arrive_if(bar + 8 * B_SO2, l0);
    STAMP(8);
    uint32_t xv[18];
    load_residual(xv, prm, m2, j2 & 1, j2 >> 1, tid2);
    pin<18>(xv);
    const uint32_t ldesc = (((sb + SM_LB) & 0x3FFFF) >> 4) | LO_BL;
    mbar_wait(bar + 8 * B_OL, 0);
    STAMP(14);
    wg_fence();
    wg_ss_z_n96<HI_O, HI_SW128>(fin, a2desc + (SM_LA >> 4), ldesc);
#pragma unroll
    for (int k = 1; k < 12; k++)
      wg_ss_n96<HI_O, HI_SW128>(fin, a2desc + ((k < 8 ? SM_LA + k * 4096 : k == 8 ? SM_LX0 : SM_LX1 + (k - 9) * 4096) >> 4), ldesc + k * 128);
    wg_commit();
    mbar_wait(bar + 8 * B_RX, 0);
    STAMP(24);
    wg_wait<0>();
    pin<48>(fin);
#pragma unroll
    for (int i = 0; i < 48; i++) fin[i] += acc2[96 + i];
    STAMP(9);
    final_epilogue(fin, xv, sb + SM_RECV, prm, m2, j2 & 1, j2 >> 1, tid2);
    STAMP(10);
  }
}

typedef CUresult (*EncodeFn)(CUtensorMap*, CUtensorMapDataType, cuuint32_t, void*, const cuuint64_t*, const cuuint64_t*, const cuuint32_t*, const cuuint32_t*,
                             CUtensorMapInterleave, CUtensorMapSwizzle, CUtensorMapL2promotion, CUtensorMapFloatOOBfill);

void enc2d(EncodeFn enc, CUtensorMap* tm, const void* base, uint64_t w, uint64_t h, uint64_t pitch_elems, uint32_t bw, uint32_t bh, CUtensorMapSwizzle sw) {
  cuuint64_t dims[2] = {w, h}, str[1] = {pitch_elems * 2};
  cuuint32_t box[2] = {bw, bh}, es[2] = {1, 1};
  enc(tm, CU_TENSOR_MAP_DATA_TYPE_BFLOAT16, 2, const_cast<void*>(base), dims, str, box, es, CU_TENSOR_MAP_INTERLEAVE_NONE, sw,
      CU_TENSOR_MAP_L2_PROMOTION_L2_128B, CU_TENSOR_MAP_FLOAT_OOB_FILL_NONE);
}

}

extern "C" void kernel_launch(void* const* d_in, const int* in_sizes, int n_in, void* d_out, int out_size) {
  (void)in_sizes; (void)n_in; (void)out_size;
  const __nv_bfloat16* x = (const __nv_bfloat16*)d_in[0];
  const __nv_bfloat16* wqkv = (const __nv_bfloat16*)d_in[1];
  const __nv_bfloat16* wo = (const __nv_bfloat16*)d_in[2];
  const __nv_bfloat16* wg = (const __nv_bfloat16*)d_in[4];
  const __nv_bfloat16* wu = (const __nv_bfloat16*)d_in[5];
  const __nv_bfloat16* wd = (const __nv_bfloat16*)d_in[6];
  void* fn = nullptr;
  cudaDriverEntryPointQueryResult qr;
  cudaGetDriverEntryPoint("cuTensorMapEncodeTiled", &fn, cudaEnableDefault, &qr);
  EncodeFn enc = (EncodeFn)fn;
  void* kvp = nullptr;
  cudaGetSymbolAddress(&kvp, g_KV);
  Params p;
  enc2d(enc, &p.xm, x, DM, SEQ, DM, 64, 128, CU_TENSOR_MAP_SWIZZLE_128B);
  enc2d(enc, &p.kv, kvp, 320, 32 * 256, 320, 192, 8, CU_TENSOR_MAP_SWIZZLE_NONE);
  enc2d(enc, &p.wqkv64, wqkv, 3 * DM, DM, 3 * DM, 64, 64, CU_TENSOR_MAP_SWIZZLE_128B);
  enc2d(enc, &p.wqkv8, wqkv, 3 * DM, DM, 3 * DM, 8, 64, CU_TENSOR_MAP_SWIZZLE_NONE);
  enc2d(enc, &p.wg, wg, FF, DM, FF, 64, 64, CU_TENSOR_MAP_SWIZZLE_128B);
  enc2d(enc, &p.wu, wu, FF, DM, FF, 64, 64, CU_TENSOR_MAP_SWIZZLE_128B);
  for (int v = 0; v < 3; v++) {
    const cuuint64_t wdt = v ? 32 : DM;
    const int c0 = v ? 256 + 32 * (v - 1) : 0;
    for (int e = 0; e < 3; e++) {
      cuuint64_t d3[3] = {wdt, e == 2 ? 2u : 16u, 32}, s3[2] = {DM * 2, 18 * DM * 2};
      cuuint32_t b3[3] = {64, e == 2 ? 2u : 16u, e == 0 ? 3u : e == 1 ? 2u : 8u}, e3[3] = {1, 1, 1};
      enc(e == 0 ? &p.wo3[v] : e == 1 ? &p.wo2[v] : &p.wo16[v], CU_TENSOR_MAP_DATA_TYPE_BFLOAT16, 3, (void*)(wo + c0 + (e == 2 ? 16 * DM : 0)), d3, s3, b3, e3,
          CU_TENSOR_MAP_INTERLEAVE_NONE, CU_TENSOR_MAP_SWIZZLE_128B, CU_TENSOR_MAP_L2_PROMOTION_L2_128B, CU_TENSOR_MAP_FLOAT_OOB_FILL_NONE);
    }
    cuuint64_t dims[5] = {wdt, 2, 2, 4, FF / 16}, str[4] = {DM * 2, 8 * DM * 2, 2 * DM * 2, 16 * DM * 2};
    cuuint32_t box[5] = {64, 2, 2, 4, 3}, es[5] = {1, 1, 1, 1, 1};
    enc(&p.wd[v], CU_TENSOR_MAP_DATA_TYPE_BFLOAT16, 5, (void*)(wd + c0), dims, str, box, es, CU_TENSOR_MAP_INTERLEAVE_NONE,
        CU_TENSOR_MAP_SWIZZLE_128B, CU_TENSOR_MAP_L2_PROMOTION_L2_128B, CU_TENSOR_MAP_FLOAT_OOB_FILL_NONE);
  }
  p.x = x;
  p.out = (__nv_bfloat16*)d_out;
  cudaFuncSetAttribute(fused_kernel, cudaFuncAttributeMaxDynamicSharedMemorySize, SM_TOTAL);
  fused_kernel<<<NCTA, 384, SM_TOTAL, cudaStreamPerThread>>>(p);
}
```

```cpp
#include <cuda_runtime.h>
#include <cuda.h>
#include <cuda_bf16.h>
#include <stdint.h>

namespace {

constexpr int SEQ = 2048, DM = 576, FF = 4608;
constexpr int NCTA = 128;

constexpr uint32_t SM_XN = 0;
constexpr uint32_t SM_RING = 147456;
constexpr uint32_t SM_KV = 212992;
constexpr uint32_t QST = 27648, BST = 16384, KVST = 6144;
constexpr uint32_t G2ST = 43008;
constexpr uint32_t SM_LB = 0, SM_SEND = 86016, SM_RECV = 143360;
constexpr uint32_t SM_BAR = 231936;
constexpr uint32_t SM_TAG = 232436;
constexpr uint32_t SM_BAD = 232432;
constexpr uint32_t SM_TOTAL = 232448;
enum { B_QF = 0, B_QE = 3, B_BF = 6, B_BE = 10, B_GF = 14, B_GE = 18, B_KF = 22, B_KE = 25, B_SK1 = 28, B_SK2 = 29, B_SH = 30, B_SO1 = 31,
       B_SO2 = 32, B_OL = 33, B_SP = 34, B_RX = 35, B_X = 36, B_NR = 45, B_N = 47 };
constexpr int PF_G1 = 1;
constexpr int NG0 = 5;

constexpr uint32_t HI_SW128 = 0x40000040u;
constexpr uint32_t LO_A = 1u << 16;
constexpr uint32_t LO_B = 512u << 16;
constexpr uint32_t HI_R = 64u, LO_R = 8u << 16;
constexpr uint32_t HI_K = 24u, LO_K = 8u << 16;
constexpr uint32_t HI_V = 8u, LO_V = 24u << 16;
constexpr uint32_t LO_B48 = 384u << 16;
constexpr uint32_t HI_O = 8u, LO_O = 128u << 16;
constexpr uint32_t LO_BL = 1536u << 16;

constexpr float QSCALE = 0.23570226039551584f * 1.4426950408889634f;
constexpr float MOFF = 90.f;

struct __align__(64) Params {
  CUtensorMap xm, wqkv64, wqkv8, wg, wu, kv, wd[3], wo3[3], wo2[3], wo16[3];
  const __nv_bfloat16* x;
  __nv_bfloat16* out;
};

__device__ __align__(1024) uint32_t g_H[16 * 576 * 512];
__device__ __align__(1024) uint32_t g_O[NCTA * 9 * 512];
__device__ __align__(1024) uint32_t g_KV[32 * SEQ * 20];
__device__ __align__(1024) uint32_t g_Q[NCTA * 4 * 256 * 8];
__device__ __align__(1024) uint4 g_P[NCTA * 3 * 1152];
__device__ __align__(1024) uint4 g_L[NCTA * 384];
__device__ float g_S[NCTA * 8 * SEQ];
__device__ uint32_t g_flags[16 * 32 + NCTA * 32 * 4];
#define FLAG_KV(l, j) (&g_flags[((l) * 8 + (j)) * 32])
#define FLAG_H(c) (&g_flags[16 * 32 + (c) * 32])
#define FLAG_O(c) (&g_flags[16 * 32 + NCTA * 32 + (c) * 32])
#define FLAG_P(c) (&g_flags[16 * 32 + NCTA * 64 + (c) * 32])
#define FLAG_EPOCH(c) (&g_flags[16 * 32 + NCTA * 96 + (c) * 32])
#define STAMP(i)
#define STAMPW(i)
#define TRACE()

template<uint32_t AHI, uint32_t BHI> __device__ __forceinline__ void wg_ss_n192(float* d, uint32_t a, uint32_t b) {
  asm volatile("{\n.reg .pred p;\n.reg .b64 da, db;\nsetp.ne.b32 p, 1, 0;\nmov.b64 da, {%96, %98};\nmov.b64 db, {%97, %99};\n"
    "wgmma.mma_async.sync.aligned.m64n192k16.f32.bf16.bf16 {%0, %1, %2, %3, %4, %5, %6, %7, %8, %9, %10, %11, %12, %13, %14, %15, %16, %17, %18, %19, %20, %21, %22, %23, %24, %25, %26, %27, %28, %29, %30, %31, %32, %33, %34, %35, %36, %37, %38, %39, %40, %41, %42, %43, %44, %45, %46, %47, %48, %49, %50, %51, %52, %53, %54, %55, %56, %57, %58, %59, %60, %61, %62, %63, %64, %65, %66, %67, %68, %69, %70, %71, %72, %73, %74, %75, %76, %77, %78, %79, %80, %81, %82, %83, %84, %85, %86, %87, %88, %89, %90, %91, %92, %93, %94, %95}, da, db, p, 1, 1, 0, 1;\n}\n"
    : "+f"(d[0]), "+f"(d[1]), "+f"(d[2]), "+f"(d[3]), "+f"(d[4]), "+f"(d[5]), "+f"(d[6]), "+f"(d[7]), "+f"(d[8]), "+f"(d[9]), "+f"(d[10]), "+f"(d[11]), "+f"(d[12]), "+f"(d[13]), "+f"(d[14]), "+f"(d[15]), "+f"(d[16]), "+f"(d[17]), "+f"(d[18]), "+f"(d[19]), "+f"(d[20]), "+f"(d[21]), "+f"(d[22]), "+f"(d[23]), "+f"(d[24]), "+f"(d[25]), "+f"(d[26]), "+f"(d[27]), "+f"(d[28]), "+f"(d[29]), "+f"(d[30]), "+f"(d[31]), "+f"(d[32]), "+f"(d[33]), "+f"(d[34]), "+f"(d[35]), "+f"(d[36]), "+f"(d[37]), "+f"(d[38]), "+f"(d[39]), "+f"(d[40]), "+f"(d[41]), "+f"(d[42]), "+f"(d[43]), "+f"(d[44]), "+f"(d[45]), "+f"(d[46]), "+f"(d[47]), "+f"(d[48]), "+f"(d[49]), "+f"(d[50]), "+f"(d[51]), "+f"(d[52]), "+f"(d[53]), "+f"(d[54]), "+f"(d[55]), "+f"(d[56]), "+f"(d[57]), "+f"(d[58]), "+f"(d[59]), "+f"(d[60]), "+f"(d[61]), "+f"(d[62]), "+f"(d[63]), "+f"(d[64]), "+f"(d[65]), "+f"(d[66]), "+f"(d[67]), "+f"(d[68]), "+f"(d[69]), "+f"(d[70]), "+f"(d[71]), "+f"(d[72]), "+f"(d[73]), "+f"(d[74]), "+f"(d[75]), "+f"(d[76]), "+f"(d[77]), "+f"(d[78]), "+f"(d[79]), "+f"(d[80]), "+f"(d[81]), "+f"(d[82]), "+f"(d[83]), "+f"(d[84]), "+f"(d[85]), "+f"(d[86]), "+f"(d[87]), "+f"(d[88]), "+f"(d[89]), "+f"(d[90]), "+f"(d[91]), "+f"(d[92]), "+f"(d[93]), "+f"(d[94]), "+f"(d[95])
    : "r"(a), "r"(b), "n"(AHI), "n"(BHI));
}
template<uint32_t AHI, uint32_t BHI> __device__ __forceinline__ void wg_ss_z_n192(float* d, uint32_t a, uint32_t b) {
  asm volatile("{\n.reg .pred p;\n.reg .b64 da, db;\nsetp.ne.b32 p, 0, 0;\nmov.b64 da, {%96, %98};\nmov.b64 db, {%97, %99};\n"
    "wgmma.mma_async.sync.aligned.m64n192k16.f32.bf16.bf16 {%0, %1, %2, %3, %4, %5, %6, %7, %8, %9, %10, %11, %12, %13, %14, %15, %16, %17, %18, %19, %20, %21, %22, %23, %24, %25, %26, %27, %28, %29, %30, %31, %32, %33, %34, %35, %36, %37, %38, %39, %40, %41, %42, %43, %44, %45, %46, %47, %48, %49, %50, %51, %52, %53, %54, %55, %56, %57, %58, %59, %60, %61, %62, %63, %64, %65, %66, %67, %68, %69, %70, %71, %72, %73, %74, %75, %76, %77, %78, %79, %80, %81, %82, %83, %84, %85, %86, %87, %88, %89, %90, %91, %92, %93, %94, %95}, da, db, p, 1, 1, 0, 1;\n}\n"
    : "=f"(d[0]), "=f"(d[1]), "=f"(d[2]), "=f"(d[3]), "=f"(d[4]), "=f"(d[5]), "=f"(d[6]), "=f"(d[7]), "=f"(d[8]), "=f"(d[9]), "=f"(d[10]), "=f"(d[11]), "=f"(d[12]), "=f"(d[13]), "=f"(d[14]), "=f"(d[15]), "=f"(d[16]), "=f"(d[17]), "=f"(d[18]), "=f"(d[19]), "=f"(d[20]), "=f"(d[21]), "=f"(d[22]), "=f"(d[23]), "=f"(d[24]), "=f"(d[25]), "=f"(d[26]), "=f"(d[27]), "=f"(d[28]), "=f"(d[29]), "=f"(d[30]), "=f"(d[31]), "=f"(d[32]), "=f"(d[33]), "=f"(d[34]), "=f"(d[35]), "=f"(d[36]), "=f"(d[37]), "=f"(d[38]), "=f"(d[39]), "=f"(d[40]), "=f"(d[41]), "=f"(d[42]), "=f"(d[43]), "=f"(d[44]), "=f"(d[45]), "=f"(d[46]), "=f"(d[47]), "=f"(d[48]), "=f"(d[49]), "=f"(d[50]), "=f"(d[51]), "=f"(d[52]), "=f"(d[53]), "=f"(d[54]), "=f"(d[55]), "=f"(d[56]), "=f"(d[57]), "=f"(d[58]), "=f"(d[59]), "=f"(d[60]), "=f"(d[61]), "=f"(d[62]), "=f"(d[63]), "=f"(d[64]), "=f"(d[65]), "=f"(d[66]), "=f"(d[67]), "=f"(d[68]), "=f"(d[69]), "=f"(d[70]), "=f"(d[71]), "=f"(d[72]), "=f"(d[73]), "=f"(d[74]), "=f"(d[75]), "=f"(d[76]), "=f"(d[77]), "=f"(d[78]), "=f"(d[79]), "=f"(d[80]), "=f"(d[81]), "=f"(d[82]), "=f"(d[83]), "=f"(d[84]), "=f"(d[85]), "=f"(d[86]), "=f"(d[87]), "=f"(d[88]), "=f"(d[89]), "=f"(d[90]), "=f"(d[91]), "=f"(d[92]), "=f"(d[93]), "=f"(d[94]), "=f"(d[95])
    : "r"(a), "r"(b), "n"(AHI), "n"(BHI));
}
template<uint32_t AHI, uint32_t BHI> __device__ __forceinline__ void wg_ss_n24(float* d, uint32_t a, uint32_t b) {
  asm volatile("{\n.reg .pred p;\n.reg .b64 da, db;\nsetp.ne.b32 p, 1, 0;\nmov.b64 da, {%12, %14};\nmov.b64 db, {%13, %15};\n"
    "wgmma.mma_async.sync.aligned.m64n24k16.f32.bf16.bf16 {%0, %1, %2, %3, %4, %5, %6, %7, %8, %9, %10, %11}, da, db, p, 1, 1, 0, 1;\n}\n"
    : "+f"(d[0]), "+f"(d[1]), "+f"(d[2]), "+f"(d[3]), "+f"(d[4]), "+f"(d[5]), "+f"(d[6]), "+f"(d[7]), "+f"(d[8]), "+f"(d[9]), "+f"(d[10]), "+f"(d[11])
    : "r"(a), "r"(b), "n"(AHI), "n"(BHI));
}
template<uint32_t AHI, uint32_t BHI> __device__ __forceinline__ void wg_ss_z_n24(float* d, uint32_t a, uint32_t b) {
  asm volatile("{\n.reg .pred p;\n.reg .b64 da, db;\nsetp.ne.b32 p, 0, 0;\nmov.b64 da, {%12, %14};\nmov.b64 db, {%13, %15};\n"
    "wgmma.mma_async.sync.aligned.m64n24k16.f32.bf16.bf16 {%0, %1, %2, %3, %4, %5, %6, %7, %8, %9, %10, %11}, da, db, p, 1, 1, 0, 1;\n}\n"
    : "=f"(d[0]), "=f"(d[1]), "=f"(d[2]), "=f"(d[3]), "=f"(d[4]), "=f"(d[5]), "=f"(d[6]), "=f"(d[7]), "=f"(d[8]), "=f"(d[9]), "=f"(d[10]), "=f"(d[11])
    : "r"(a), "r"(b), "n"(AHI), "n"(BHI));
}
template<uint32_t AHI, uint32_t BHI> __device__ __forceinline__ void wg_ss_n128(float* d, uint32_t a, uint32_t b) {
  asm volatile("{\n.reg .pred p;\n.reg .b64 da, db;\nsetp.ne.b32 p, 1, 0;\nmov.b64 da, {%64, %66};\nmov.b64 db, {%65, %67};\n"
    "wgmma.mma_async.sync.aligned.m64n128k16.f32.bf16.bf16 {%0, %1, %2, %3, %4, %5, %6, %7, %8, %9, %10, %11, %12, %13, %14, %15, %16, %17, %18, %19, %20, %21, %22, %23, %24, %25, %26, %27, %28, %29, %30, %31, %32, %33, %34, %35, %36, %37, %38, %39, %40, %41, %42, %43, %44, %45, %46, %47, %48, %49, %50, %51, %52, %53, %54, %55, %56, %57, %58, %59, %60, %61, %62, %63}, da, db, p, 1, 1, 0, 1;\n}\n"
    : "+f"(d[0]), "+f"(d[1]), "+f"(d[2]), "+f"(d[3]), "+f"(d[4]), "+f"(d[5]), "+f"(d[6]), "+f"(d[7]), "+f"(d[8]), "+f"(d[9]), "+f"(d[10]), "+f"(d[11]), "+f"(d[12]), "+f"(d[13]), "+f"(d[14]), "+f"(d[15]), "+f"(d[16]), "+f"(d[17]), "+f"(d[18]), "+f"(d[19]), "+f"(d[20]), "+f"(d[21]), "+f"(d[22]), "+f"(d[23]), "+f"(d[24]), "+f"(d[25]), "+f"(d[26]), "+f"(d[27]), "+f"(d[28]), "+f"(d[29]), "+f"(d[30]), "+f"(d[31]), "+f"(d[32]), "+f"(d[33]), "+f"(d[34]), "+f"(d[35]), "+f"(d[36]), "+f"(d[37]), "+f"(d[38]), "+f"(d[39]), "+f"(d[40]), "+f"(d[41]), "+f"(d[42]), "+f"(d[43]), "+f"(d[44]), "+f"(d[45]), "+f"(d[46]), "+f"(d[47]), "+f"(d[48]), "+f"(d[49]), "+f"(d[50]), "+f"(d[51]), "+f"(d[52]), "+f"(d[53]), "+f"(d[54]), "+f"(d[55]), "+f"(d[56]), "+f"(d[57]), "+f"(d[58]), "+f"(d[59]), "+f"(d[60]), "+f"(d[61]), "+f"(d[62]), "+f"(d[63])
    : "r"(a), "r"(b), "n"(AHI), "n"(BHI));
}
template<uint32_t AHI, uint32_t BHI> __device__ __forceinline__ void wg_ss_z_n128(float* d, uint32_t a, uint32_t b) {
  asm volatile("{\n.reg .pred p;\n.reg .b64 da, db;\nsetp.ne.b32 p, 0, 0;\nmov.b64 da, {%64, %66};\nmov.b64 db, {%65, %67};\n"
    "wgmma.mma_async.sync.aligned.m64n128k16.f32.bf16.bf16 {%0, %1, %2, %3, %4, %5, %6, %7, %8, %9, %10, %11, %12, %13, %14, %15, %16, %17, %18, %19, %20, %21, %22, %23, %24, %25, %26, %27, %28, %29, %30, %31, %32, %33, %34, %35, %36, %37, %38, %39, %40, %41, %42, %43, %44, %45, %46, %47, %48, %49, %50, %51, %52, %53, %54, %55, %56, %57, %58, %59, %60, %61, %62, %63}, da, db, p, 1, 1, 0, 1;\n}\n"
    : "=f"(d[0]), "=f"(d[1]), "=f"(d[2]), "=f"(d[3]), "=f"(d[4]), "=f"(d[5]), "=f"(d[6]), "=f"(d[7]), "=f"(d[8]), "=f"(d[9]), "=f"(d[10]), "=f"(d[11]), "=f"(d[12]), "=f"(d[13]), "=f"(d[14]), "=f"(d[15]), "=f"(d[16]), "=f"(d[17]), "=f"(d[18]), "=f"(d[19]), "=f"(d[20]), "=f"(d[21]), "=f"(d[22]), "=f"(d[23]), "=f"(d[24]), "=f"(d[25]), "=f"(d[26]), "=f"(d[27]), "=f"(d[28]), "=f"(d[29]), "=f"(d[30]), "=f"(d[31]), "=f"(d[32]), "=f"(d[33]), "=f"(d[34]), "=f"(d[35]), "=f"(d[36]), "=f"(d[37]), "=f"(d[38]), "=f"(d[39]), "=f"(d[40]), "=f"(d[41]), "=f"(d[42]), "=f"(d[43]), "=f"(d[44]), "=f"(d[45]), "=f"(d[46]), "=f"(d[47]), "=f"(d[48]), "=f"(d[49]), "=f"(d[50]), "=f"(d[51]), "=f"(d[52]), "=f"(d[53]), "=f"(d[54]), "=f"(d[55]), "=f"(d[56]), "=f"(d[57]), "=f"(d[58]), "=f"(d[59]), "=f"(d[60]), "=f"(d[61]), "=f"(d[62]), "=f"(d[63])
    : "r"(a), "r"(b), "n"(AHI), "n"(BHI));
}
template<uint32_t AHI, uint32_t BHI> __device__ __forceinline__ void wg_ss_n160(float* d, uint32_t a, uint32_t b) {
  asm volatile("{\n.reg .pred p;\n.reg .b64 da, db;\nsetp.ne.b32 p, 1, 0;\nmov.b64 da, {%80, %82};\nmov.b64 db, {%81, %83};\n"
    "wgmma.mma_async.sync.aligned.m64n160k16.f32.bf16.bf16 {%0, %1, %2, %3, %4, %5, %6, %7, %8, %9, %10, %11, %12, %13, %14, %15, %16, %17, %18, %19, %20, %21, %22, %23, %24, %25, %26, %27, %28, %29, %30, %31, %32, %33, %34, %35, %36, %37, %38, %39, %40, %41, %42, %43, %44, %45, %46, %47, %48, %49, %50, %51, %52, %53, %54, %55, %56, %57, %58, %59, %60, %61, %62, %63, %64, %65, %66, %67, %68, %69, %70, %71, %72, %73, %74, %75, %76, %77, %78, %79}, da, db, p, 1, 1, 0, 1;\n}\n"
    : "+f"(d[0]), "+f"(d[1]), "+f"(d[2]), "+f"(d[3]), "+f"(d[4]), "+f"(d[5]), "+f"(d[6]), "+f"(d[7]), "+f"(d[8]), "+f"(d[9]), "+f"(d[10]), "+f"(d[11]), "+f"(d[12]), "+f"(d[13]), "+f"(d[14]), "+f"(d[15]), "+f"(d[16]), "+f"(d[17]), "+f"(d[18]), "+f"(d[19]), "+f"(d[20]), "+f"(d[21]), "+f"(d[22]), "+f"(d[23]), "+f"(d[24]), "+f"(d[25]), "+f"(d[26]), "+f"(d[27]), "+f"(d[28]), "+f"(d[29]), "+f"(d[30]), "+f"(d[31]), "+f"(d[32]), "+f"(d[33]), "+f"(d[34]), "+f"(d[35]), "+f"(d[36]), "+f"(d[37]), "+f"(d[38]), "+f"(d[39]), "+f"(d[40]), "+f"(d[41]), "+f"(d[42]), "+f"(d[43]), "+f"(d[44]), "+f"(d[45]), "+f"(d[46]), "+f"(d[47]), "+f"(d[48]), "+f"(d[49]), "+f"(d[50]), "+f"(d[51]), "+f"(d[52]), "+f"(d[53]), "+f"(d[54]), "+f"(d[55]), "+f"(d[56]), "+f"(d[57]), "+f"(d[58]), "+f"(d[59]), "+f"(d[60]), "+f"(d[61]), "+f"(d[62]), "+f"(d[63]), "+f"(d[64]), "+f"(d[65]), "+f"(d[66]), "+f"(d[67]), "+f"(d[68]), "+f"(d[69]), "+f"(d[70]), "+f"(d[71]), "+f"(d[72]), "+f"(d[73]), "+f"(d[74]), "+f"(d[75]), "+f"(d[76]), "+f"(d[77]), "+f"(d[78]), "+f"(d[79])
    : "r"(a), "r"(b), "n"(AHI), "n"(BHI));
}
template<uint32_t AHI, uint32_t BHI> __device__ __forceinline__ void wg_ss_z_n160(float* d, uint32_t a, uint32_t b) {
  asm volatile("{\n.reg .pred p;\n.reg .b64 da, db;\nsetp.ne.b32 p, 0, 0;\nmov.b64 da, {%80, %82};\nmov.b64 db, {%81, %83};\n"
    "wgmma.mma_async.sync.aligned.m64n160k16.f32.bf16.bf16 {%0, %1, %2, %3, %4, %5, %6, %7, %8, %9, %10, %11, %12, %13, %14, %15, %16, %17, %18, %19, %20, %21, %22, %23, %24, %25, %26, %27, %28, %29, %30, %31, %32, %33, %34, %35, %36, %37, %38, %39, %40, %41, %42, %43, %44, %45, %46, %47, %48, %49, %50, %51, %52, %53, %54, %55, %56, %57, %58, %59, %60, %61, %62, %63, %64, %65, %66, %67, %68, %69, %70, %71, %72, %73, %74, %75, %76, %77, %78, %79}, da, db, p, 1, 1, 0, 1;\n}\n"
    : "=f"(d[0]), "=f"(d[1]), "=f"(d[2]), "=f"(d[3]), "=f"(d[4]), "=f"(d[5]), "=f"(d[6]), "=f"(d[7]), "=f"(d[8]), "=f"(d[9]), "=f"(d[10]), "=f"(d[11]), "=f"(d[12]), "=f"(d[13]), "=f"(d[14]), "=f"(d[15]), "=f"(d[16]), "=f"(d[17]), "=f"(d[18]), "=f"(d[19]), "=f"(d[20]), "=f"(d[21]), "=f"(d[22]), "=f"(d[23]), "=f"(d[24]), "=f"(d[25]), "=f"(d[26]), "=f"(d[27]), "=f"(d[28]), "=f"(d[29]), "=f"(d[30]), "=f"(d[31]), "=f"(d[32]), "=f"(d[33]), "=f"(d[34]), "=f"(d[35]), "=f"(d[36]), "=f"(d[37]), "=f"(d[38]), "=f"(d[39]), "=f"(d[40]), "=f"(d[41]), "=f"(d[42]), "=f"(d[43]), "=f"(d[44]), "=f"(d[45]), "=f"(d[46]), "=f"(d[47]), "=f"(d[48]), "=f"(d[49]), "=f"(d[50]), "=f"(d[51]), "=f"(d[52]), "=f"(d[53]), "=f"(d[54]), "=f"(d[55]), "=f"(d[56]), "=f"(d[57]), "=f"(d[58]), "=f"(d[59]), "=f"(d[60]), "=f"(d[61]), "=f"(d[62]), "=f"(d[63]), "=f"(d[64]), "=f"(d[65]), "=f"(d[66]), "=f"(d[67]), "=f"(d[68]), "=f"(d[69]), "=f"(d[70]), "=f"(d[71]), "=f"(d[72]), "=f"(d[73]), "=f"(d[74]), "=f"(d[75]), "=f"(d[76]), "=f"(d[77]), "=f"(d[78]), "=f"(d[79])
    : "r"(a), "r"(b), "n"(AHI), "n"(BHI));
}
template<uint32_t BHI> __device__ __forceinline__ void wg_rs_n96(float* d, uint32_t a0, uint32_t a1, uint32_t a2, uint32_t a3, uint32_t b) {
  asm volatile("{\n.reg .pred p;\n.reg .b64 db;\nsetp.ne.b32 p, 1, 0;\nmov.b64 db, {%52, %53};\n"
    "wgmma.mma_async.sync.aligned.m64n96k16.f32.bf16.bf16 {%0, %1, %2, %3, %4, %5, %6, %7, %8, %9, %10, %11, %12, %13, %14, %15, %16, %17, %18, %19, %20, %21, %22, %23, %24, %25, %26, %27, %28, %29, %30, %31, %32, %33, %34, %35, %36, %37, %38, %39, %40, %41, %42, %43, %44, %45, %46, %47}, {%48, %49, %50, %51}, db, p, 1, 1, 1;\n}\n"
    : "+f"(d[0]), "+f"(d[1]), "+f"(d[2]), "+f"(d[3]), "+f"(d[4]), "+f"(d[5]), "+f"(d[6]), "+f"(d[7]), "+f"(d[8]), "+f"(d[9]), "+f"(d[10]), "+f"(d[11]), "+f"(d[12]), "+f"(d[13]), "+f"(d[14]), "+f"(d[15]), "+f"(d[16]), "+f"(d[17]), "+f"(d[18]), "+f"(d[19]), "+f"(d[20]), "+f"(d[21]), "+f"(d[22]), "+f"(d[23]), "+f"(d[24]), "+f"(d[25]), "+f"(d[26]), "+f"(d[27]), "+f"(d[28]), "+f"(d[29]), "+f"(d[30]), "+f"(d[31]), "+f"(d[32]), "+f"(d[33]), "+f"(d[34]), "+f"(d[35]), "+f"(d[36]), "+f"(d[37]), "+f"(d[38]), "+f"(d[39]), "+f"(d[40]), "+f"(d[41]), "+f"(d[42]), "+f"(d[43]), "+f"(d[44]), "+f"(d[45]), "+f"(d[46]), "+f"(d[47])
    : "r"(a0), "r"(a1), "r"(a2), "r"(a3), "r"(b), "n"(BHI));
}
template<uint32_t BHI> __device__ __forceinline__ void wg_rs_z_n96(float* d, uint32_t a0, uint32_t a1, uint32_t a2, uint32_t a3, uint32_t b) {
  asm volatile("{\n.reg .pred p;\n.reg .b64 db;\nsetp.ne.b32 p, 0, 0;\nmov.b64 db, {%52, %53};\n"
    "wgmma.mma_async.sync.aligned.m64n96k16.f32.bf16.bf16 {%0, %1, %2, %3, %4, %5, %6, %7, %8, %9, %10, %11, %12, %13, %14, %15, %16, %17, %18, %19, %20, %21, %22, %23, %24, %25, %26, %27, %28, %29, %30, %31, %32, %33, %34, %35, %36, %37, %38, %39, %40, %41, %42, %43, %44, %45, %46, %47}, {%48, %49, %50, %51}, db, p, 1, 1, 1;\n}\n"
    : "=f"(d[0]), "=f"(d[1]), "=f"(d[2]), "=f"(d[3]), "=f"(d[4]), "=f"(d[5]), "=f"(d[6]), "=f"(d[7]), "=f"(d[8]), "=f"(d[9]), "=f"(d[10]), "=f"(d[11]), "=f"(d[12]), "=f"(d[13]), "=f"(d[14]), "=f"(d[15]), "=f"(d[16]), "=f"(d[17]), "=f"(d[18]), "=f"(d[19]), "=f"(d[20]), "=f"(d[21]), "=f"(d[22]), "=f"(d[23]), "=f"(d[24]), "=f"(d[25]), "=f"(d[26]), "=f"(d[27]), "=f"(d[28]), "=f"(d[29]), "=f"(d[30]), "=f"(d[31]), "=f"(d[32]), "=f"(d[33]), "=f"(d[34]), "=f"(d[35]), "=f"(d[36]), "=f"(d[37]), "=f"(d[38]), "=f"(d[39]), "=f"(d[40]), "=f"(d[41]), "=f"(d[42]), "=f"(d[43]), "=f"(d[44]), "=f"(d[45]), "=f"(d[46]), "=f"(d[47])
    : "r"(a0), "r"(a1), "r"(a2), "r"(a3), "r"(b), "n"(BHI));
}
template<uint32_t BHI> __device__ __forceinline__ void wg_rs_n64(float* d, uint32_t a0, uint32_t a1, uint32_t a2, uint32_t a3, uint32_t b) {
  asm volatile("{\n.reg .pred p;\n.reg .b64 db;\nsetp.ne.b32 p, 1, 0;\nmov.b64 db, {%36, %37};\n"
    "wgmma.mma_async.sync.aligned.m64n64k16.f32.bf16.bf16 {%0, %1, %2, %3, %4, %5, %6, %7, %8, %9, %10, %11, %12, %13, %14, %15, %16, %17, %18, %19, %20, %21, %22, %23, %24, %25, %26, %27, %28, %29, %30, %31}, {%32, %33, %34, %35}, db, p, 1, 1, 0;\n}\n"
    : "+f"(d[0]), "+f"(d[1]), "+f"(d[2]), "+f"(d[3]), "+f"(d[4]), "+f"(d[5]), "+f"(d[6]), "+f"(d[7]), "+f"(d[8]), "+f"(d[9]), "+f"(d[10]), "+f"(d[11]), "+f"(d[12]), "+f"(d[13]), "+f"(d[14]), "+f"(d[15]), "+f"(d[16]), "+f"(d[17]), "+f"(d[18]), "+f"(d[19]), "+f"(d[20]), "+f"(d[21]), "+f"(d[22]), "+f"(d[23]), "+f"(d[24]), "+f"(d[25]), "+f"(d[26]), "+f"(d[27]), "+f"(d[28]), "+f"(d[29]), "+f"(d[30]), "+f"(d[31])
    : "r"(a0), "r"(a1), "r"(a2), "r"(a3), "r"(b), "n"(BHI));
}
template<uint32_t BHI> __device__ __forceinline__ void wg_rs_z_n64(float* d, uint32_t a0, uint32_t a1, uint32_t a2, uint32_t a3, uint32_t b) {
  asm volatile("{\n.reg .pred p;\n.reg .b64 db;\nsetp.ne.b32 p, 0, 0;\nmov.b64 db, {%36, %37};\n"
    "wgmma.mma_async.sync.aligned.m64n64k16.f32.bf16.bf16 {%0, %1, %2, %3, %4, %5, %6, %7, %8, %9, %10, %11, %12, %13, %14, %15, %16, %17, %18, %19, %20, %21, %22, %23, %24, %25, %26, %27, %28, %29, %30, %31}, {%32, %33, %34, %35}, db, p, 1, 1, 0;\n}\n"
    : "=f"(d[0]), "=f"(d[1]), "=f"(d[2]), "=f"(d[3]), "=f"(d[4]), "=f"(d[5]), "=f"(d[6]), "=f"(d[7]), "=f"(d[8]), "=f"(d[9]), "=f"(d[10]), "=f"(d[11]), "=f"(d[12]), "=f"(d[13]), "=f"(d[14]), "=f"(d[15]), "=f"(d[16]), "=f"(d[17]), "=f"(d[18]), "=f"(d[19]), "=f"(d[20]), "=f"(d[21]), "=f"(d[22]), "=f"(d[23]), "=f"(d[24]), "=f"(d[25]), "=f"(d[26]), "=f"(d[27]), "=f"(d[28]), "=f"(d[29]), "=f"(d[30]), "=f"(d[31])
    : "r"(a0), "r"(a1), "r"(a2), "r"(a3), "r"(b), "n"(BHI));
}
template<uint32_t BHI> __device__ __forceinline__ void wg_rs_n24(float* d, uint32_t a0, uint32_t a1, uint32_t a2, uint32_t a3, uint32_t b) {
  asm volatile("{\n.reg .pred p;\n.reg .b64 db;\nsetp.ne.b32 p, 1, 0;\nmov.b64 db, {%16, %17};\n"
    "wgmma.mma_async.sync.aligned.m64n24k16.f32.bf16.bf16 {%0, %1, %2, %3, %4, %5, %6, %7, %8, %9, %10, %11}, {%12, %13, %14, %15}, db, p, 1, 1, 1;\n}\n"
    : "+f"(d[0]), "+f"(d[1]), "+f"(d[2]), "+f"(d[3]), "+f"(d[4]), "+f"(d[5]), "+f"(d[6]), "+f"(d[7]), "+f"(d[8]), "+f"(d[9]), "+f"(d[10]), "+f"(d[11])
    : "r"(a0), "r"(a1), "r"(a2), "r"(a3), "r"(b), "n"(BHI));
}
template<uint32_t BHI> __device__ __forceinline__ void wg_rs_z_n24(float* d, uint32_t a0, uint32_t a1, uint32_t a2, uint32_t a3, uint32_t b) {
  asm volatile("{\n.reg .pred p;\n.reg .b64 db;\nsetp.ne.b32 p, 0, 0;\nmov.b64 db, {%16, %17};\n"
    "wgmma.mma_async.sync.aligned.m64n24k16.f32.bf16.bf16 {%0, %1, %2, %3, %4, %5, %6, %7, %8, %9, %10, %11}, {%12, %13, %14, %15}, db, p, 1, 1, 1;\n}\n"
    : "=f"(d[0]), "=f"(d[1]), "=f"(d[2]), "=f"(d[3]), "=f"(d[4]), "=f"(d[5]), "=f"(d[6]), "=f"(d[7]), "=f"(d[8]), "=f"(d[9]), "=f"(d[10]), "=f"(d[11])
    : "r"(a0), "r"(a1), "r"(a2), "r"(a3), "r"(b), "n"(BHI));
}

__device__ __forceinline__ void wg_fence() { asm volatile("wgmma.fence.sync.aligned;" ::: "memory"); }
__device__ __forceinline__ void wg_commit() { asm volatile("wgmma.commit_group.sync.aligned;" ::: "memory"); }
template <int N> __device__ __forceinline__ void wg_wait() { asm volatile("wgmma.wait_group.sync.aligned %0;" ::"n"(N) : "memory"); }
template <int R> __device__ __forceinline__ void pin(float* d) {
#pragma unroll
  for (int i = 0; i < R; i++) asm volatile("" : "+f"(d[i])::"memory");
}
template <int R> __device__ __forceinline__ void pin(uint32_t* d) {
#pragma unroll
  for (int i = 0; i < R; i++) asm volatile("" : "+r"(d[i])::"memory");
}
__device__ __forceinline__ float ex2(float x) { float y; asm("ex2.approx.ftz.f32 %0, %1;" : "=f"(y) : "f"(x)); return y; }
__device__ __forceinline__ float tanh_fast(float x) { float y; asm("tanh.approx.f32 %0, %1;" : "=f"(y) : "f"(x)); return y; }
__device__ __forceinline__ uint32_t pack(float lo, float hi) { uint32_t r; asm("cvt.rn.bf16x2.f32 %0, %1, %2;" : "=r"(r) : "f"(hi), "f"(lo)); return r; }
__device__ __forceinline__ float bf_lo(uint32_t v) { return __uint_as_float(v << 16); }
__device__ __forceinline__ float bf_hi(uint32_t v) { return __uint_as_float(v & 0xffff0000u); }
__device__ __forceinline__ float bf_round(float x) { return bf_lo(pack(x, 0.f)); }

__device__ __forceinline__ void mbar_init(uint32_t bar, uint32_t cnt) { asm volatile("mbarrier.init.shared::cta.b64 [%0], %1;" ::"r"(bar), "r"(cnt) : "memory"); }
__device__ __forceinline__ void mbar_expect(uint32_t bar, uint32_t bytes) { asm volatile("mbarrier.arrive.expect_tx.shared::cta.b64 _, [%0], %1;" ::"r"(bar), "r"(bytes) : "memory"); }
__device__ __forceinline__ void mbar_arrive(uint32_t bar) { asm volatile("mbarrier.arrive.shared::cta.b64 _, [%0];" ::"r"(bar) : "memory"); }
__device__ __forceinline__ void mbar_wait(uint32_t bar, uint32_t parity) {
  asm volatile(
      "{\n.reg .pred p;\n.reg .u32 c;\n"
      "mbarrier.try_wait.parity.shared::cta.b64 p, [%0], %1;\n"
      "@p bra.uni DONE;\n"
      "mov.u32 c, 0;\n"
      "LOOP:\n"
      "mbarrier.try_wait.parity.shared::cta.b64 p, [%0], %1;\n"
      "@p bra.uni DONE;\n"
      "add.u32 c, c, 1;\n"
      "setp.lt.u32 p, c, 0x4000000;\n"
      "@p bra.uni LOOP;\n"
      "trap;\n"
      "DONE:\n}\n" ::"r"(bar), "r"(parity) : "memory");
}
__device__ __forceinline__ uint32_t mbar_test(uint32_t bar, uint32_t parity) {
  uint32_t ok;
  asm volatile("{\n.reg .pred p;\nmbarrier.test_wait.parity.shared::cta.b64 p, [%1], %2;\nselp.u32 %0, 1, 0, p;\n}\n" : "=r"(ok) : "r"(bar), "r"(parity) : "memory");
  return ok;
}
__device__ __forceinline__ void mbar_arrive_if(uint32_t bar, uint32_t cond) {
  asm volatile("{\n.reg .pred p;\nsetp.ne.u32 p, %1, 0;\n@p mbarrier.arrive.shared::cta.b64 _, [%0];\n}\n" ::"r"(bar), "r"(cond) : "memory");
}
__device__ __forceinline__ uint32_t bsub2(uint32_t a, uint32_t b) { uint32_t d; asm("sub.rn.bf16x2 %0, %1, %2;" : "=r"(d) : "r"(a), "r"(b)); return d; }
__device__ __forceinline__ uint32_t bscale2(uint32_t d, uint32_t hi, uint32_t lo) {
  uint32_t t, r;
  asm("mul.rn.bf16x2 %0, %1, %2;" : "=r"(t) : "r"(d), "r"(lo));
  asm("fma.rn.bf16x2 %0, %1, %2, %3;" : "=r"(r) : "r"(d), "r"(hi), "r"(t));
  return r;
}
__device__ __forceinline__ void flag_wait(const uint32_t* f, uint32_t target) {
  asm volatile(
      "{\n.reg .pred p;\n.reg .u32 c, v;\n"
      "mov.u32 c, 0;\n"
      "LOOP:\n"
      "ld.acquire.gpu.global.u32 v, [%0];\n"
      "sub.u32 v, v, %1;\n"
      "setp.ge.s32 p, v, 0;\n"
      "@p bra DONE;\n"
      "add.u32 c, c, 1;\n"
      "setp.lt.u32 p, c, 0x1000000;\n"
      "@p bra LOOP;\n"
      "trap;\n"
      "DONE:\n}\n" ::"l"(f), "r"(target) : "memory");
}
__device__ __forceinline__ uint32_t flag_wait_v(const uint32_t* f, uint32_t target) {
  uint32_t v;
  asm volatile(
      "{\n.reg .pred p;\n.reg .u32 c, d;\n"
      "mov.u32 c, 0;\n"
      "LOOP:\n"
      "ld.acquire.gpu.global.u32 %0, [%1];\n"
      "sub.u32 d, %0, %2;\n"
      "setp.ge.s32 p, d, 0;\n"
      "@p bra DONE;\n"
      "add.u32 c, c, 1;\n"
      "setp.lt.u32 p, c, 0x1000000;\n"
      "@p bra LOOP;\n"
      "trap;\n"
      "DONE:\n}\n" : "=&r"(v) : "l"(f), "r"(target) : "memory");
  return v;
}
__device__ __forceinline__ float sqrt_fast(float x) { float y; asm("sqrt.approx.f32 %0, %1;" : "=f"(y) : "f"(x)); return y; }
__device__ __forceinline__ float rcp_fast(float x) { float y; asm("rcp.approx.ftz.f32 %0, %1;" : "=f"(y) : "f"(x)); return y; }
__device__ __forceinline__ void ldsm4(uint32_t* v, uint32_t addr) {
  asm volatile("ldmatrix.sync.aligned.m8n8.x4.shared.b16 {%0,%1,%2,%3}, [%4];" : "=r"(v[0]), "=r"(v[1]), "=r"(v[2]), "=r"(v[3]) : "r"(addr) : "memory");
}
__device__ __forceinline__ void stsm4(uint32_t addr, uint32_t a, uint32_t b, uint32_t c, uint32_t d) {
  asm volatile("stmatrix.sync.aligned.m8n8.x4.shared.b16 [%0], {%1,%2,%3,%4};" ::"r"(addr), "r"(a), "r"(b), "r"(c), "r"(d) : "memory");
}
__device__ __forceinline__ void flag_add(uint32_t* f) { asm volatile("red.relaxed.gpu.global.add.u32 [%0], 1;" ::"l"(f) : "memory"); }
__device__ __forceinline__ void fence_gpu() { asm volatile("fence.acq_rel.gpu;" ::: "memory"); }
__device__ __forceinline__ void fence_async() { asm volatile("fence.proxy.async;" ::: "memory"); }
__device__ __forceinline__ void tma2d(uint32_t dst, const CUtensorMap* tm, uint32_t bar, int c0, int c1) {
  asm volatile("cp.async.bulk.tensor.2d.shared::cluster.global.mbarrier::complete_tx::bytes [%0], [%1, {%3, %4}], [%2];" ::"r"(dst), "l"(tm), "r"(bar), "r"(c0), "r"(c1) : "memory");
}
__device__ __forceinline__ void tma2d_h(uint32_t dst, const CUtensorMap* tm, uint32_t bar, int c0, int c1, uint64_t pol) {
  asm volatile("cp.async.bulk.tensor.2d.shared::cluster.global.mbarrier::complete_tx::bytes.L2::cache_hint [%0], [%1, {%3, %4}], [%2], %5;" ::"r"(dst), "l"(tm), "r"(bar), "r"(c0), "r"(c1), "l"(pol) : "memory");
}
__device__ __forceinline__ void bulk_s2g(void* dst, uint32_t src, uint32_t bytes) {
  asm volatile("cp.async.bulk.global.shared::cta.bulk_group [%0], [%1], %2;" ::"l"(dst), "r"(src), "r"(bytes) : "memory");
}
__device__ __forceinline__ void mma_ones(float* c, const uint32_t* a) {
  asm("mma.sync.aligned.m16n8k16.row.col.f32.bf16.bf16.f32 {%0,%1,%2,%3}, {%4,%5,%6,%7}, {%8,%8}, {%0,%1,%2,%3};"
      : "+f"(c[0]), "+f"(c[1]), "+f"(c[2]), "+f"(c[3]) : "r"(a[0]), "r"(a[1]), "r"(a[2]), "r"(a[3]), "r"(0x3f803f80u));
}
__device__ __forceinline__ void tma5d(uint32_t dst, const CUtensorMap* tm, uint32_t bar, int c0, int c4) {
  asm volatile("cp.async.bulk.tensor.5d.shared::cluster.global.mbarrier::complete_tx::bytes [%0], [%1, {%3, %5, %5, %5, %4}], [%2];" ::"r"(dst), "l"(tm), "r"(bar), "r"(c0), "r"(c4), "r"(0) : "memory");
}
__device__ __forceinline__ void tma3d(uint32_t dst, const CUtensorMap* tm, uint32_t bar, int c0, int c2) {
  asm volatile("cp.async.bulk.tensor.3d.shared::cluster.global.mbarrier::complete_tx::bytes [%0], [%1, {%3, %5, %4}], [%2];" ::"r"(dst), "l"(tm), "r"(bar), "r"(c0), "r"(c2), "r"(0) : "memory");
}
__device__ __forceinline__ void bulk_g2s(uint32_t dst, const void* src, uint32_t bytes, uint32_t bar) {
  asm volatile("cp.async.bulk.shared::cluster.global.mbarrier::complete_tx::bytes [%0], [%1], %2, [%3];" ::"r"(dst), "l"(src), "r"(bytes), "r"(bar) : "memory");
}
__device__ __forceinline__ void pf3d(const CUtensorMap* tm, int c0, int c2) {
  asm volatile("cp.async.bulk.prefetch.tensor.3d.L2.global [%0, {%1, %3, %2}];" ::"l"(tm), "r"(c0), "r"(c2), "r"(0) : "memory");
}
__device__ __forceinline__ void pf2d(const CUtensorMap* tm, int c0, int c1) {
  asm volatile("cp.async.bulk.prefetch.tensor.2d.L2.global [%0, {%1, %2}];" ::"l"(tm), "r"(c0), "r"(c1) : "memory");
}
__device__ __forceinline__ void pf5d(const CUtensorMap* tm, int c0, int c4) {
  asm volatile("cp.async.bulk.prefetch.tensor.5d.L2.global [%0, {%1, %3, %3, %3, %2}];" ::"l"(tm), "r"(c0), "r"(c4), "r"(0) : "memory");
}

__device__ __forceinline__ int fresh_tid() { int v; asm volatile("mov.u32 %0, %%tid.x;" : "=r"(v)); return v; }
struct Att {
  float s[32];
  float o[12];
  uint32_t p[16];
  uint32_t q[8];
};

__device__ __forceinline__ float warp_sum(float v) {
#pragma unroll 1
  for (int d = 16; d; d >>= 1) v += __shfl_xor_sync(0xffffffffu, v, d);
  return v;
}
#define OPAQUE(x) asm volatile("" : "+r"(x))
__device__ __forceinline__ void attn_slow_row(int cta, uint32_t& w) {
  float mx = -INFINITY;
#pragma unroll 1
  for (uint32_t key = threadIdx.x & 31; key < SEQ; key += 32) {
    float s = 0.f;
#pragma unroll 1
    for (uint32_t v = 0; v < 9; v++) {
      OPAQUE(w); OPAQUE(key);
      const uint32_t hp = (w >> 4) & 3, pos = (v + hp) & 3;
      const uint32_t q = g_Q[(((cta * 4 + hp) * 2 + (v >> 3)) * 256 + ((w >> 6) & 7) * 32 + (w & 7) * 4 + pos) * 4 + 2 * ((v >> 2) & 1) + ((w >> 3) & 1)];
      const uint32_t u = g_KV[(4 * (cta & 7) + hp) * SEQ * 20 + (key >> 3) * 160 + (key & 7) * 4 + (v >> 2) * 32 + pos];
      s = fmaf(bf_lo(q), bf_lo(u), fmaf(bf_hi(q), bf_hi(u), s));
    }
    g_S[(cta * 8 + ((w >> 6) & 7)) * SEQ + key] = s;
    mx = fmaxf(mx, s);
  }
#pragma unroll 1
  for (int d = 16; d; d >>= 1) mx = fmaxf(mx, __shfl_xor_sync(0xffffffffu, mx, d));
  float l = 0.f;
#pragma unroll 1
  for (uint32_t key = threadIdx.x & 31; key < SEQ; key += 32) l += ex2(g_S[(cta * 8 + ((w >> 6) & 7)) * SEQ + key] - mx);
  l = 2.f * rcp_fast(warp_sum(l));
#pragma unroll 1
  for (uint32_t v = w >> 9; v < 9; v++) {
    float a = 0.f, b = 0.f;
#pragma unroll 1
    for (uint32_t key = threadIdx.x & 31; key < SEQ; key += 32) {
      OPAQUE(w); OPAQUE(v);
      const uint32_t hp = (w >> 4) & 3;
      const uint32_t u = g_KV[(4 * (cta & 7) + hp) * SEQ * 20 + (key >> 3) * 160 + (key & 7) * 4 + (v < 8 ? (3 + (v >> 2)) * 32 + (v & 3) : 64 + ((hp + 2) & 3))];
      const float p = ex2(g_S[(cta * 8 + ((w >> 6) & 7)) * SEQ + key] - mx);
      a = fmaf(p, bf_lo(u), a); b = fmaf(p, bf_hi(u), b);
    }
    a = warp_sum(a); b = warp_sum(b);
    OPAQUE(w);
    const uint32_t hp = (w >> 4) & 3;
    if ((threadIdx.x & 31) == 0) g_O[cta * 9 * 512 + (((w >> 6) & 7) * 16 + (w & 15)) * 4 + (v < 8 ? (2 * hp + (v >> 2)) * 512 + (v & 3) : 8 * 512 + hp)] = pack(a * l, b * l);
  }
}

__device__ __forceinline__ uint32_t bad_heads(uint32_t bad_addr, int wr) {
  uint32_t bad;
  __syncwarp();
  asm volatile("ld.volatile.shared.u32 %0, [%1];" : "=r"(bad) : "r"(bad_addr) : "memory");
  return __shfl_sync(0xffffffffu, (bad >> (4 * wr)) & 15, 0);
}
__device__ __forceinline__ void repair_rows(int cta, int wr, uint32_t bad, int last_head, bool final) {
#pragma unroll 1
  for (uint32_t w = wr * 64; w < wr * 64 + 64; w++) {
    if (!((bad >> ((w >> 4) & 3)) & 1)) continue;
    if (final && ((w >> 4) & 3) != last_head) w |= 8u << 9;
    attn_slow_row(cta, w);
    w &= 511;
  }
  __syncwarp();
}
__device__ __forceinline__ void o_normalise(const float* o, uint32_t* w, uint32_t& x0, uint32_t& x1, int hp, int lane, uint32_t bad_addr, int wr) {
  const int src = (lane & ~3) | ((hp + 1) & 3);
  float l0 = __shfl_sync(0xffffffffu, o[0], src), l1 = __shfl_sync(0xffffffffu, o[2], src);
  float sa = 0.f;
#pragma unroll
  for (int i = 0; i < 12; i++) sa += fabsf(o[i]);
  bool ok = (l0 <= 1.329228e36f) && (l1 <= 1.329228e36f) && (l0 > 0.f) && (l1 > 0.f) && (sa <= 3.0e38f);
  float i0 = 2.f * rcp_fast(l0), i1 = 2.f * rcp_fast(l1);
  w[0] = pack(o[4] * i0, o[5] * i0);
  w[1] = pack(o[6] * i1, o[7] * i1);
  w[2] = pack(o[8] * i0, o[9] * i0);
  w[3] = pack(o[10] * i1, o[11] * i1);
  if ((lane & 3) == ((hp + 2) & 3)) { x0 = pack(o[0] * i0, o[1] * i0); x1 = pack(o[2] * i1, o[3] * i1); }
  if (!ok) asm volatile("red.shared.or.b32 [%0], %1;" ::"r"(bad_addr), "r"(1u << (4 * wr + hp)) : "memory");
}

__device__ __forceinline__ void issue_pv(Att& a, uint32_t kdesc) {
  const uint32_t vdesc = kdesc + 192 + (LO_V - LO_K);
#pragma unroll
  for (int k = 0; k < 4; k++) wg_rs_n24<HI_V>(a.o, a.p[4 * k], a.p[4 * k + 1], a.p[4 * k + 2], a.p[4 * k + 3], vdesc + k * 48);
}
__device__ __forceinline__ void issue_att(Att& a, uint32_t kdesc) {
  issue_pv(a, kdesc);
  wg_rs_z_n64<HI_K>(a.s, a.q[0], a.q[1], a.q[2], a.q[3], kdesc);
  wg_rs_n64<HI_K>(a.s, a.q[4], a.q[5], a.q[6], a.q[7], kdesc + 16);
}
__device__ __forceinline__ void softmax_a(Att& a) {
#pragma unroll
  for (int i = 0; i < 9; i++) a.p[i] = pack(ex2(a.s[2 * i]), ex2(a.s[2 * i + 1]));
  a.s[18] = ex2(a.s[18]); a.s[19] = ex2(a.s[19]);
  pin<9>(a.p); pin<2>(a.s + 18);
}
__device__ __forceinline__ void softmax_b(Att& a) {
  a.p[9] = pack(a.s[18], a.s[19]);
#pragma unroll
  for (int i = 10; i < 16; i++) a.p[i] = pack(ex2(a.s[2 * i]), ex2(a.s[2 * i + 1]));
  pin<7>(a.p + 9);
}
__device__ __forceinline__ void first_tile(Att& a, int hp, int lane) {
  float m0 = fmaxf(a.s[0], a.s[1]), m1 = fmaxf(a.s[2], a.s[3]);
#pragma unroll
  for (int i = 4; i < 32; i += 4) { m0 = fmaxf(m0, fmaxf(a.s[i], a.s[i + 1])); m1 = fmaxf(m1, fmaxf(a.s[i + 2], a.s[i + 3])); }
  m0 = fmaxf(m0, __shfl_xor_sync(0xffffffffu, m0, 1)); m1 = fmaxf(m1, __shfl_xor_sync(0xffffffffu, m1, 1));
  m0 = fmaxf(m0, __shfl_xor_sync(0xffffffffu, m0, 2)); m1 = fmaxf(m1, __shfl_xor_sync(0xffffffffu, m1, 2));
  float n0 = -(m0 + MOFF), n1 = -(m1 + MOFF);
  float h0 = bf_round(n0), h1 = bf_round(n1);
  uint32_t e0 = pack(h0, n0 - h0), e1 = pack(h1, n1 - h1);
  n0 = h0 + bf_hi(e0); n1 = h1 + bf_hi(e1);
  if ((lane & 3) == ((hp + 1) & 3)) { a.q[4] = e0; a.q[5] = e1; }
#pragma unroll
  for (int i = 0; i < 32; i += 4) { a.s[i] += n0; a.s[i + 1] += n0; a.s[i + 2] += n1; a.s[i + 3] += n1; }
#pragma unroll
  for (int i = 0; i < 12; i++) a.o[i] = 0.f;
  pin<12>(a.o); pin<8>(a.q);
}
__device__ __forceinline__ void prefetch_q(int cta, int hp, int tid) {
  const uint4* src = reinterpret_cast<const uint4*>(g_Q) + (cta * 4 + hp) * 512 + tid;
  asm volatile("prefetch.global.L1 [%0];\nprefetch.global.L1 [%0 + 4096];" ::"l"(src) : "memory");
}
__device__ __forceinline__ void load_q(Att& a, int cta, int hp, int tid) {
  const uint4* src = reinterpret_cast<const uint4*>(g_Q) + (cta * 4 + hp) * 512 + tid;
  const uint4 u = __ldca(src), v = __ldca(src + 256);
  a.q[0] = u.x; a.q[1] = u.y; a.q[2] = u.z; a.q[3] = u.w; a.q[4] = v.x; a.q[5] = v.y; a.q[6] = v.z; a.q[7] = v.w;
}
__device__ __forceinline__ void h_epilogue(const float* acc, uint32_t* dst) {
#pragma unroll
  for (int b = 0; b < 4; b++) {
    uint32_t w[2][2];
#pragma unroll
    for (int i = 0; i < 2; i++) {
      float h[4];
#pragma unroll
      for (int e = 0; e < 4; e++) {
        const float g = acc[(2 * b + i) * 4 + e], u = acc[32 + (2 * b + i) * 4 + e];
        h[e] = fmaf(tanh_fast(0.5f * g), u, u);
      }
      w[0][i] = pack(h[0], h[1]); w[1][i] = pack(h[2], h[3]);
    }
    *reinterpret_cast<uint2*>(dst + 1024 * b) = make_uint2(w[0][0], w[0][1]);
    *reinterpret_cast<uint2*>(dst + 1024 * b + 32) = make_uint2(w[1][0], w[1][1]);
  }
}
template <int HP> __device__ __forceinline__ void store_kv_head(uint32_t (&pk)[2][9][2], uint32_t* kvp, int lane) {
  const int t = lane & 3;
  const bool up = t < HP;
#pragma unroll
  for (int rh = 0; rh < 2; rh++) {
    uint32_t* d = kvp + HP * SEQ * 20 + rh * 160;
    d[0] = up ? pk[0][2 * HP + 1][rh] : pk[0][2 * HP][rh];
    d[32] = up ? pk[0][2 * HP + 2][rh] : pk[0][2 * HP + 1][rh];
    d[96 + ((t - HP) & 3) - t] = up ? pk[1][2 * HP + 1][rh] : pk[1][2 * HP][rh];
    d[128 + ((t - HP) & 3) - t] = up ? pk[1][2 * HP + 2][rh] : pk[1][2 * HP + 1][rh];
    const uint32_t v9 = __shfl_sync(0xffffffffu, pk[1][2 * HP + 2][rh], (lane & ~3) | HP);
    d[64] = t == HP ? pk[0][2 * HP + 2][rh] : t == ((HP + 1) & 3) ? 0x3f803f80u : t == ((HP + 2) & 3) ? v9 : 0u;
  }
}

__device__ __forceinline__ void stage_partials(const float* acc, uint32_t dst, int tid) {
#pragma unroll
  for (int i = 0; i < 12; i++) {
    const float* v = acc + 8 * i;
    asm volatile("st.shared.v4.b32 [%0], {%1,%2,%3,%4};" ::"r"(dst + i * 4096 + tid * 16), "r"(pack(v[0], v[1])), "r"(pack(v[2], v[3])), "r"(pack(v[4], v[5])), "r"(pack(v[6], v[7])) : "memory");
  }
#pragma unroll
  for (int d = 0; d < 4; d++) {
    const float* v = acc + 128 + 8 * (d & 1) + 2 * (d >> 1);
    asm volatile("st.shared.v2.b32 [%0], {%1,%2};" ::"r"(dst + 49152 + d * 2048 + tid * 8), "r"(pack(v[0], v[1])), "r"(pack(v[4], v[5])) : "memory");
  }
}
__device__ __forceinline__ void load_residual(uint32_t* xv, const Params& prm, int m, int hh, int q, int tid) {
  const size_t off = (size_t)(128 * m + (tid >> 5) * 16 + ((tid & 31) >> 2)) * DM + 2 * (tid & 3);
  const uint32_t* xr = reinterpret_cast<const uint32_t*>(prm.x + off + 320 * hh + 64 * q);
  const uint32_t* xr2 = reinterpret_cast<const uint32_t*>(prm.x + off + 256 + 32 * hh + 16 * (q & 1) + (q >> 1) * 8 * DM);
#pragma unroll
  for (int i = 0; i < 16; i++) xv[i] = __ldg(xr + 4 * (i >> 1) + (i & 1) * 8 * (DM / 2));
  xv[16] = __ldg(xr2); xv[17] = __ldg(xr2 + 4);
}
__device__ __forceinline__ void final_epilogue(const float* acc, const uint32_t* xv, uint32_t recv, const Params& prm, int m, int hh, int q, int tid) {
  float own[4];
#pragma unroll
  for (int e = 0; e < 4; e++) {
    const int o = 32 + (e & 1) + 4 * (e >> 1);
    const float s0 = (q & 2) ? acc[o + 2] : acc[o], s1 = (q & 2) ? acc[o + 10] : acc[o + 8];
    own[e] = (q & 1) ? s1 : s0;
  }
  uint32_t v[3][18];
#pragma unroll
  for (int d = 0; d < 3; d++) {
#pragma unroll
    for (int i = 0; i < 4; i++)
      asm volatile("ld.shared.v4.b32 {%0,%1,%2,%3}, [%4];" : "=r"(v[d][4 * i]), "=r"(v[d][4 * i + 1]), "=r"(v[d][4 * i + 2]), "=r"(v[d][4 * i + 3])
                   : "r"(recv + d * 18432 + i * 4096 + tid * 16) : "memory");
    asm volatile("ld.shared.v2.b32 {%0,%1}, [%2];" : "=r"(v[d][16]), "=r"(v[d][17]) : "r"(recv + d * 18432 + 16384 + tid * 8) : "memory");
  }
  const size_t off = (size_t)(128 * m + (tid >> 5) * 16 + ((tid & 31) >> 2)) * DM + 2 * (tid & 3);
  const bool odd = tid & 1;
  uint32_t* o1 = reinterpret_cast<uint32_t*>(prm.out + off + 320 * hh + 64 * q) + (odd ? 3 : 0);
  uint32_t* o2 = reinterpret_cast<uint32_t*>(prm.out + off + 256 + 32 * hh + 16 * (q & 1) + (q >> 1) * 8 * DM) + (odd ? 3 : 0);
  uint32_t r[18];
#pragma unroll
  for (int i = 0; i < 18; i++) {
    const float lo = (i < 16 ? acc[2 * i] : own[2 * (i - 16)]) + ((bf_lo(v[0][i]) + bf_lo(v[1][i])) + bf_lo(v[2][i]));
    const float hi = (i < 16 ? acc[2 * i + 1] : own[2 * (i - 16) + 1]) + ((bf_hi(v[0][i]) + bf_hi(v[1][i])) + bf_hi(v[2][i]));
    r[i] = pack(fmaf(lo, 0.5f, bf_lo(xv[i])), fmaf(hi, 0.5f, bf_hi(xv[i])));
  }
#pragma unroll
  for (int i = 0; i < 9; i++) {
    const uint32_t A = i < 8 ? r[4 * (i >> 1) + (i & 1)] : r[16], B = i < 8 ? r[4 * (i >> 1) + 2 + (i & 1)] : r[17];
    const uint32_t y = __shfl_xor_sync(0xffffffffu, odd ? A : B, 1);
    *reinterpret_cast<uint2*>(i < 8 ? o1 + 8 * (i >> 1) + (i & 1) * 8 * (DM / 2) : o2) = odd ? make_uint2(y, B) : make_uint2(A, y);
  }
}

__global__ void __launch_bounds__(384, 1) fused_kernel(const __grid_constant__ Params prm) {
  extern __shared__ __align__(1024) uint8_t smem[];
  const uint32_t sb = (uint32_t)__cvta_generic_to_shared(smem);
  const uint32_t bar = sb + SM_BAR;
  const int m = blockIdx.x & 15, j = blockIdx.x >> 4;
  const int cta = m * 8 + j;
  const int wr = __shfl_sync(0xffffffffu, (int)(threadIdx.x >> 5), 0);
  const int wg = wr >> 2;
  const int lane = threadIdx.x & 31;
  STAMP(0);
  if (wg == 2 && lane == 0) {
    if (wr == 8) {
      asm volatile("prefetch.tensormap [%0];" ::"l"(&prm.xm) : "memory");
#pragma unroll
      for (int c = 0; c < 9; c++) mbar_init(bar + 8 * (B_X + c), 1);
#pragma unroll
      for (int c = 0; c < 9; c++) mbar_expect(bar + 8 * (B_X + c), 16384);
      asm volatile("fence.proxy.async.shared::cta;" ::: "memory");
#pragma unroll
      for (int c = 0; c < 3; c++) tma2d(sb + SM_XN + c * 16384, &prm.xm, bar + 8 * (B_X + c), 64 * c, 128 * m);
    } else {
      const uint32_t b0 = bar + 112 * (wr - 9);
#pragma unroll
      for (int i = 0; i < 14; i++) {
        const uint32_t c0 = (i < 3 || (i >= 6 && i < 10)) ? 1 : 8, c1 = (i < 4 || (i >= 8 && i < 11)) ? 1 : 8, c2 = (i == 5 || i == 7) ? 1 : 8;
        if (i < 8 || wr != 11) mbar_init(b0 + 8 * i, wr == 9 ? c0 : wr == 10 ? c1 : c2);
      }
      if (wr == 11) {
        mbar_init(bar + 8 * B_NR, 4); mbar_init(bar + 8 * (B_NR + 1), 4);
        asm volatile("st.shared.u32 [%0], 0;" ::"r"(sb + SM_BAD) : "memory");
        if (sb & 1023) asm volatile("trap;");
      }
      asm volatile("fence.proxy.async.shared::cta;" ::: "memory");
    }
  }
  static_assert(B_QE == 3 && B_BF == 6 && B_BE == 10 && B_GF == 14 && B_GE == 18 && B_KF == 22 && B_KE == 25 && B_SK1 == 28 && B_OL == 33 && B_RX == 35, "");
  __syncthreads();

  if (wg == 2) {
    asm volatile("setmaxnreg.dec.sync.aligned.u32 24;");
    const int pw = wr & 3;
    const uint32_t epoch = *(volatile uint32_t*)FLAG_EPOCH(cta);
    const int hh = j & 1;
#define ACOL(A) (320 * hh + 64 * (((j >> 1) + 1 + (A)) & 3))
    if (pw == 0) {
      if (lane == 0) {
#pragma unroll
        for (int c = 3; c < 9; c++) tma2d(sb + SM_XN + c * 16384, &prm.xm, bar + 8 * (B_X + c), 64 * c, 128 * m);
        STAMPW(21);
        uint64_t pol;
        asm volatile("createpolicy.fractional.L2::evict_first.b64 %0, 1.0;" : "=l"(pol));
#pragma unroll 1
        for (int kb = 0; kb < 9; kb++) {
          const int s = kb % 3;
          if (kb >= 3) mbar_wait(bar + 8 * (B_QE + s), (kb / 3 - 1) & 1);
          const uint32_t fb = bar + 8 * (B_QF + s), dst = sb + SM_RING + s * QST;
          mbar_expect(fb, QST);
#pragma unroll
          for (int p = 0; p < 3; p++) {
            tma2d(dst + p * 8192, &prm.wqkv64, fb, 576 * p + 72 * j, 64 * kb);
            tma2d(dst + 24576 + p * 1024, &prm.wqkv8, fb, 576 * p + 72 * j + 64, 64 * kb);
          }
        }
        asm volatile("st.shared.u32 [%0], %1;" ::"r"(sb + SM_TAG), "r"((epoch + 1) & 1) : "memory");
        int col = 576 * j, kr = 0;
#pragma unroll 1
        for (int s = 0; s < 81; s++) {
          const int slot = s & 3;
          if (s >= 4) mbar_wait(bar + 8 * (B_BE + slot), ((s >> 2) - 1) & 1);
          else if (s != 2) mbar_wait(bar + 8 * (B_QE + (s == 3 ? 2 : s)), 0);
          const uint32_t fb = bar + 8 * (B_BF + slot), dst = sb + SM_RING + slot * BST;
          mbar_expect(fb, BST);
          tma2d_h(dst, &prm.wg, fb, col, kr, pol);
          tma2d_h(dst + 8192, &prm.wu, fb, col, kr, pol);
          if ((kr += 64) == 576) { kr = 0; col += 64; }
        }
        mbar_arrive(bar + 8 * (B_BF + 1));
        uint32_t seen = flag_wait_v(FLAG_H(cta), 9 * epoch + 1) - 9 * epoch;
        fence_async();
#pragma unroll 1
        for (int b = 0; b < 26; b++) {
          const int st = b & 3;
          if (b >= 4) mbar_wait(bar + 8 * (B_GE + st), ((b >> 2) - 1) & 1);
          else if (b) mbar_wait(bar + 8 * (B_BE + (b == 1 ? 1 : b == 2 ? 3 : 0)), b != 3);
          const uint32_t fb = bar + 8 * (B_GF + st), dst = sb + st * G2ST;
          if (b == 0) STAMPW(16);
          mbar_expect(fb, G2ST);
          if (b < 24) {
            const int jj = (b < 10 || b == 20 || b == 21) ? j : (j ^ 1), lb = b < 10 ? b : b < 20 ? b - 10 : 10 + (b & 1);
            bulk_g2s(dst, g_H + (m * 576 + 72 * jj + 6 * lb) * 512, 12288, fb);
#pragma unroll
            for (int a = 0; a < 4; a++) tma5d(dst + 12288 + a * 6144, &prm.wd[0], fb, ACOL(a), 36 * jj + 3 * lb);
            tma5d(dst + 36864, &prm.wd[1 + hh], fb, 0, 36 * jj + 3 * lb);
          } else {
            const int r = b - 24;
            bulk_g2s(dst, g_O + ((cta & ~1) + r) * 9 * 512 + r * 1024, 12288, fb);
#pragma unroll
            for (int a = 0; a < 4; a++) tma3d(dst + 12288 + a * 6144, &prm.wo3[0], fb, ACOL(a), 4 * (j & 6) + 5 * r);
            tma3d(dst + 36864, &prm.wo3[1 + hh], fb, 0, 4 * (j & 6) + 5 * r);
          }
          if (b == 0) STAMPW(17);
          if (b < 23) {
            const int n = b + 1, lb = n < 10 ? n : n < 20 ? n - 10 : 10 + (n & 1), need = (3 * lb + 6) >> 2;
            if (n == 10 || n == 20 || n == 22) seen = 0;
            if (seen < need) { seen = flag_wait_v(FLAG_H((n < 10 || n == 20 || n == 21) ? cta : (cta ^ 1)), 9 * epoch + need) - 9 * epoch; fence_async(); }
          } else if (b == 23) { flag_wait(FLAG_O(cta), epoch + 1); flag_wait(FLAG_O(cta ^ 1), epoch + 1); fence_async(); }
        }
        mbar_wait(bar + 8 * (B_GE + 1), 0);
        mbar_expect(bar + 8 * B_OL, 49152);
#pragma unroll 1
        for (int i = 0; i < 4; i++) {
          tma3d(sb + SM_LB + i * 4096, &prm.wo2[0], bar + 8 * B_OL, ACOL(3), 8 * i + 3);
          tma3d(sb + SM_LB + 24576 + i * 4096, &prm.wo2[1 + hh], bar + 8 * B_OL, 0, 8 * i + 3);
          tma3d(sb + SM_LB + 16384 + i * 2048, &prm.wo16[0], bar + 8 * B_OL, ACOL(3), 8 * i);
          tma3d(sb + SM_LB + 40960 + i * 2048, &prm.wo16[1 + hh], bar + 8 * B_OL, 0, 8 * i);
          __nanosleep(200);
        }
      }
    } else if (pw == 1) {
      if (lane == 0) {
        flag_wait(FLAG_KV(0, j), 16 * epoch + 16);
        fence_async();
        STAMPW(18);
        int slot = 0, ph = 1, vrow = 0;
        const int hx = (j & 1) * 3;
#pragma unroll 1
        for (int u = 0; u <= 128; u++) {
          if (u >= 3) mbar_wait(bar + 8 * (B_KE + slot), ph);
          const uint32_t fb = bar + 8 * (B_KF + slot), dst = sb + SM_KV + slot * KVST;
          const int krow = (4 * j + ((u >> 5) ^ hx)) * 256 + ((u + 2 * m) & 31) * 8;
          if (u == 0) vrow = krow;
          mbar_expect(fb, u < 128 ? KVST : KVST / 2);
          if (u < 128) tma2d(dst, &prm.kv, fb, 0, krow);
          tma2d(dst + 3072, &prm.kv, fb, 128, vrow);
          vrow = krow;
          if (++slot == 3) { slot = 0; ph ^= 1; }
          if (u == 16) { flag_wait(FLAG_KV(1, j), 16 * epoch + 16); fence_async(); }
        }
      }
    } else if (pw == 2) {
      if (lane == 0) {
#pragma unroll 1
        for (int i = 1; i < 18; i++) asm volatile("prefetch.tensormap [%0];" ::"l"(&prm.xm + i) : "memory");
        mbar_wait(bar + 8 * B_SK1, 0);
        STAMPW(22);
        fence_gpu(); flag_add(FLAG_KV(0, j));
        STAMPW(20);
        mbar_wait(bar + 8 * B_SK2, 0);
        fence_gpu(); flag_add(FLAG_KV(1, j));
#pragma unroll 1
        for (int t = 0; t < 9; t++) { mbar_wait(bar + 8 * B_SH, t & 1); fence_gpu(); flag_add(FLAG_H(cta)); }
        mbar_wait(bar + 8 * B_SO1, 0);
        fence_gpu(); flag_add(FLAG_O(cta));
      }
    } else if (lane == 0) {
      if (m < 9) {
#pragma unroll 1
        for (int p = 0; p < 6; p++) pf2d((p & 1) ? &prm.wqkv8 : &prm.wqkv64, 576 * (p >> 1) + 72 * j + 64 * (p & 1), 64 * m);
      }
      mbar_wait(bar + 8 * (B_QE + PF_G1), 0);
#pragma unroll 1
      for (int b = m; b < 54; b += 16) pf2d((b & 1) ? &prm.wu : &prm.wg, 576 * j + 64 * (b / 18), 64 * ((b >> 1) % 9));
#pragma unroll 1
      for (int t = 0; t < 9; t++) {
        mbar_wait(bar + 8 * B_SH, t & 1);
        if (t < 6) {
          pf2d((m & 1) ? &prm.wu : &prm.wg, 576 * j + 64 * (t + 3), 64 * (m >> 1));
          if (m < 2) pf2d(m ? &prm.wu : &prm.wg, 576 * j + 64 * (t + 3), 512);
        }
        if (t >= 5) {
#pragma unroll 1
          for (int b = m + 16 * hh + 54 * (t - 5); b < 54 * (t - 4); b += 32) pf5d(&prm.wd[0], 64 * (b % 9), 72 * (j >> 1) + 36 * ((b / 9) & 1) + 3 * (b / 18));
        }
      }
      if (m < 9) { pf3d(&prm.wo3[0], 64 * m, 4 * j); pf3d(&prm.wo3[0], 64 * m, 4 * j + 1); if (!hh) pf3d(&prm.wo16[0], 64 * m, 4 * j); }
      mbar_wait(bar + 8 * B_SP, 0);
      const int q = j >> 1;
#pragma unroll 1
      for (int i = 0; i < 15; i++) {
        const int a = i / 5, p = i % 5, d = (q + 1 + a) & 3;
        bulk_s2g(g_P + ((m * 8 + 2 * d + hh) * 3 + a) * 1152 + p * 256, p < 4 ? sb + SM_SEND + a * 16384 + p * 4096 : sb + SM_SEND + 49152 + d * 2048, p < 4 ? 4096 : 2048);
        asm volatile("cp.async.bulk.commit_group;\ncp.async.bulk.wait_group.read 1;" ::: "memory");
      }
      asm volatile("cp.async.bulk.wait_group 0;" ::: "memory");
      fence_gpu();
#pragma unroll 1
      for (int a = 0; a < 3; a++) flag_add(FLAG_P(m * 8 + 2 * ((q + 1 + a) & 3) + hh));
      STAMPW(15);
      flag_wait(FLAG_P(cta), 3 * epoch + 3);
      fence_async();
      STAMPW(25);
      mbar_expect(bar + 8 * B_RX, 55296);
#pragma unroll 1
      for (int i = 0; i < 9; i++) { bulk_g2s(sb + SM_RECV + i * 6144, g_P + cta * 3 * 1152 + i * 384, 6144, bar + 8 * B_RX); __nanosleep(64); }
      *FLAG_EPOCH(cta) = epoch + 1;
    }
  } else {
    const int tid = threadIdx.x;
    const int t = lane & 3;
    const uint32_t l0 = lane == 0;
    const uint32_t adesc = (((sb + SM_XN + wg * 8192) & 0x3FFFF) >> 4) | LO_A;
    const uint32_t bdesc = (((sb + SM_RING) & 0x3FFFF) >> 4) | LO_B;
    const uint32_t kdesc0 = (((sb + SM_KV) & 0x3FFFF) >> 4) | LO_K;
    const int hx = (j & 1) * 3;
    float accA[64], accB[64];
    Att a;
    uint32_t gs = 0;
#define G1_ISSUE(ACC, AD, BD) _Pragma("unroll") for (int k = 0; k < 4; k++) wg_ss_n128<HI_SW128, HI_SW128>(ACC, (AD) + k * 2, (BD) + k * 128);
#define G1_ISSUE_Z(ACC, BD)                                                                                    \
  wg_ss_z_n128<HI_SW128, HI_SW128>(ACC, adesc, BD);                                                            \
  _Pragma("unroll") for (int k = 1; k < 4; k++) wg_ss_n128<HI_SW128, HI_SW128>(ACC, adesc + k * 2, (BD) + k * 128);
#define BF_BAR (bar + 8 * B_BF + 8 * (gs & 3))
#define BF_PH ((gs >> 2) & 1)
#define G1_ONLY() { mbar_wait(BF_BAR, BF_PH); wg_fence(); G1_ISSUE(accA, adesc + gs * 1024, bdesc + (gs & 3) * 1024) wg_commit(); wg_wait<1>(); \
                    mbar_arrive_if(bar + 8 * B_BE + 8 * ((gs - 1) & 3), l0); gs++; }
    {
      const int lr = wr * 16 + (lane & 15);
      uint32_t ra[4];
#pragma unroll
      for (int k = 0; k < 4; k++) ra[k] = sb + SM_XN + lr * 128 + (((2 * k + (lane >> 4)) ^ (lr & 7)) << 4);
      STAMP(26);
      float cs[2][4] = {}, q0 = 0.f, q1 = 0.f, q2 = 0.f, q3 = 0.f;
#pragma unroll 1
      for (int c = 0; c < 9; c++) {
        mbar_wait(bar + 8 * (B_X + c), 0);
        if (c == 0) STAMP(27);
        if (c == 8) STAMP(28);
        uint32_t v[4][4];
#pragma unroll
        for (int k = 0; k < 4; k++) ldsm4(v[k], ra[k] + c * 16384);
#pragma unroll
        for (int k = 0; k < 4; k++) {
          mma_ones(cs[k & 1], v[k]);
#pragma unroll
          for (int e = 0; e < 4; e += 2) {
            const float x0 = bf_lo(v[k][e]), x1 = bf_hi(v[k][e]), y0 = bf_lo(v[k][e + 1]), y1 = bf_hi(v[k][e + 1]);
            q0 = fmaf(x0, x0, q0); q1 = fmaf(x1, x1, q1); q2 = fmaf(y0, y0, q2); q3 = fmaf(y1, y1, q3);
          }
        }
      }
      STAMP(11);
      asm volatile("setmaxnreg.inc.sync.aligned.u32 240;");
      const float mean0 = (cs[0][0] + cs[1][0]) * (1.f / 576.f), mean1 = (cs[0][2] + cs[1][2]) * (1.f / 576.f);
      q0 += q1; q2 += q3;
      q0 += __shfl_xor_sync(0xffffffffu, q0, 1); q2 += __shfl_xor_sync(0xffffffffu, q2, 1);
      q0 += __shfl_xor_sync(0xffffffffu, q0, 2); q2 += __shfl_xor_sync(0xffffffffu, q2, 2);
      float var0 = fmaf(q0, 1.f / 576.f, -mean0 * mean0), var1 = fmaf(q2, 1.f / 576.f, -mean1 * mean1);
      if (__any_sync(0xffffffffu, !(mean0 * mean0 <= 8.f * var0) || !(mean1 * mean1 <= 8.f * var1))) {
        q0 = q2 = 0.f;
#pragma unroll 1
        for (int i = 0; i < 36; i++) {
          uint32_t v[4];
          ldsm4(v, ((ra[0] + (i >> 2) * 16384) ^ ((i & 3) << 5)));
#pragma unroll
          for (int e = 0; e < 4; e += 2) {
            const float x0 = bf_lo(v[e]) - mean0, x1 = bf_hi(v[e]) - mean0, y0 = bf_lo(v[e + 1]) - mean1, y1 = bf_hi(v[e + 1]) - mean1;
            q0 = fmaf(x0, x0, fmaf(x1, x1, q0)); q2 = fmaf(y0, y0, fmaf(y1, y1, q2));
          }
        }
        q0 += __shfl_xor_sync(0xffffffffu, q0, 1); q2 += __shfl_xor_sync(0xffffffffu, q2, 1);
        q0 += __shfl_xor_sync(0xffffffffu, q0, 2); q2 += __shfl_xor_sync(0xffffffffu, q2, 2);
        var0 = q0 * (1.f / 576.f); var1 = q2 * (1.f / 576.f);
      }
      const float inv0 = rcp_fast(bf_round(sqrt_fast(bf_round(bf_round(var0) + 1e-5f)))), inv1 = rcp_fast(bf_round(sqrt_fast(bf_round(bf_round(var1) + 1e-5f))));
      const uint32_t mb0 = pack(mean0, mean0), mb1 = pack(mean1, mean1);
      const uint32_t h0 = pack(inv0, inv0), h1 = pack(inv1, inv1);
      const uint32_t e0 = pack(inv0 - bf_lo(h0), inv0 - bf_lo(h0)), e1 = pack(inv1 - bf_lo(h1), inv1 - bf_lo(h1));
#define NORM_STORE(C)                                                                                          \
  {                                                                                                            \
    _Pragma("unroll") for (int k = 0; k < 4; k++)                                                              \
      stsm4(ra[k] + (C) * 16384, bscale2(bsub2(v[k][0], mb0), h0, e0), bscale2(bsub2(v[k][1], mb1), h1, e1),   \
            bscale2(bsub2(v[k][2], mb0), h0, e0), bscale2(bsub2(v[k][3], mb1), h1, e1));                       \
    asm volatile("fence.proxy.async.shared::cta;" ::: "memory");                                               \
    __syncwarp();                                                                                              \
    mbar_arrive_if(bar + 8 * B_NR + 8 * wg, l0);                                                               \
  }
      float aq[96], ar[12];
      {
        uint32_t v[4][4];
#pragma unroll
        for (int k = 0; k < 4; k++) ldsm4(v[k], ra[k]);
        NORM_STORE(0)
      }
#pragma unroll
      for (int i = 0; i < 96; i++) aq[i] = 0.f;
#pragma unroll
      for (int i = 0; i < 12; i++) ar[i] = 0.f;
      pin<96>(aq); pin<12>(ar);
      STAMP(1);
      const uint32_t rdesc = (((sb + SM_RING + 24576) & 0x3FFFF) >> 4) | LO_R;
      uint32_t s = 0, ph = 0;
#pragma unroll 1
      for (int kb = 0; kb < 9; kb++) {
        uint32_t v[4][4];
        const int cn = kb < 8 ? kb + 1 : 8;
#pragma unroll
        for (int k = 0; k < 4; k++) ldsm4(v[k], ra[k] + cn * 16384);
        mbar_wait(bar + 8 * B_QF + 8 * s, ph);
        mbar_wait(bar + 8 * B_NR + 8 * wg, kb & 1);
        wg_fence();
#pragma unroll
        for (int k = 0; k < 4; k++) {
          wg_ss_n192<HI_SW128, HI_SW128>(aq, adesc + kb * 1024 + k * 2, bdesc + s * (QST >> 4) + k * 128);
          wg_ss_n24<HI_SW128, HI_R>(ar, adesc + kb * 1024 + k * 2, rdesc + s * (QST >> 4) + k * 16);
        }
        wg_commit();
        if (kb < 8) NORM_STORE(cn)
        wg_wait<1>();
        mbar_arrive_if(bar + 8 * B_QE + (s == 0 ? 16 : 8 * s - 8), l0 & (kb > 0));
        if (++s == 3) { s = 0; ph ^= 1; }
      }
      wg_wait<0>();
      pin<96>(aq); pin<12>(ar);
      mbar_arrive_if(bar + 8 * (B_QE + 2), l0);
      STAMP(2);
      uint32_t* kvp = g_KV + (size_t)(4 * j) * SEQ * 20 + (16 * m + 2 * wr) * 160 + lane;
      uint32_t pk[2][9][2];
#pragma unroll
      for (int p = 0; p < 2; p++)
#pragma unroll
        for (int i = 0; i < 9; i++) {
          const float* src = i < 8 ? &aq[(8 * (p + 1) + i) * 4] : &ar[4 * (p + 1)];
          pk[p][i][0] = pack(src[0], src[1]); pk[p][i][1] = pack(src[2], src[3]);
        }
      if (hx) store_kv_head<3>(pk, kvp, lane); else store_kv_head<0>(pk, kvp, lane);
      __syncwarp();
      mbar_arrive_if(bar + 8 * B_SK1, l0);
      STAMP(3);
      mbar_wait(bar + 8 * B_BF, 0);
      wg_fence();
      G1_ISSUE_Z(accA, bdesc)
      wg_commit();
      gs = 1;
      uint32_t pq[9][2];
#pragma unroll
      for (int i = 0; i < 9; i++) {
        const float* src = i < 8 ? &aq[i * 4] : &ar[0];
        pq[i][0] = pack(bf_round(src[0]) * QSCALE, bf_round(src[1]) * QSCALE); pq[i][1] = pack(bf_round(src[2]) * QSCALE, bf_round(src[3]) * QSCALE);
      }
      pin<18>(&pq[0][0]);
#pragma unroll 1
      while (gs < 3) G1_ONLY()
      if (hx) store_kv_head<0>(pk, kvp, lane); else store_kv_head<3>(pk, kvp, lane);
      store_kv_head<1>(pk, kvp, lane);
      store_kv_head<2>(pk, kvp, lane);
      __syncwarp();
      mbar_arrive_if(bar + 8 * B_SK2, l0);
      G1_ONLY()
      uint4* qp = reinterpret_cast<uint4*>(g_Q) + cta * 4 * 512 + tid;
#pragma unroll
      for (int hp = 0; hp < 4; hp++) {
        const bool up = t < hp;
        const uint4 u = make_uint4(up ? pq[2 * hp + 1][0] : pq[2 * hp][0], up ? pq[2 * hp + 1][1] : pq[2 * hp][1],
                                   up ? pq[2 * hp + 2][0] : pq[2 * hp + 1][0], up ? pq[2 * hp + 2][1] : pq[2 * hp + 1][1]);
        const uint4 v = make_uint4(t == hp ? pq[2 * hp + 2][0] : 0u, t == hp ? pq[2 * hp + 2][1] : 0u, 0u, 0u);
        qp[hp * 512] = u; qp[hp * 512 + 256] = v;
        if (hp == 0 || (hp == 3 && hx)) { a.q[0] = u.x; a.q[1] = u.y; a.q[2] = u.z; a.q[3] = u.w; a.q[4] = v.x; a.q[5] = v.y; }
      }
      a.q[6] = __shfl_sync(0xffffffffu, lane, 0); a.q[7] = __shfl_sync(0xffffffffu, lane >> 1, 1);
#pragma unroll
      for (int i = 0; i < 16; i++) a.p[i] = 0;
#pragma unroll
      for (int i = 0; i < 12; i++) a.o[i] = 0.f;
      pin<16>(a.p); pin<12>(a.o); pin<8>(a.q);
    }
    static_assert(NG0 == 5, "slot / item alignment below assumes NG0 == 5");
    G1_ONLY()
    STAMP(4);
    mbar_wait(BF_BAR, BF_PH);
    mbar_wait(bar + 8 * B_KF, 0);
    STAMP(23);
    uint32_t k8 = 0, kph = 0, kd = kdesc0;
    uint32_t it = 0;
    uint32_t ox0 = 0, ox1 = 0;
    bool special = true;
    uint32_t* hdst = g_H + ((m * 576 + 72 * j + (t >> 1)) * 128 + 16 * wr + (lane >> 2)) * 4 + 2 * (t & 1);
    uint32_t ad = adesc + NG0 * 1024, bd = bdesc + (gs & 3) * 1024;

#define ITEM_FIRST()                                                                                           \
  {                                                                                                            \
    pin<12>(a.o);                                                                                              \
    if (it != 0) {                                                                                             \
      uint32_t w[4];                                                                                           \
      o_normalise(a.o, w, ox0, ox1, ((it >> 5) - 1) ^ hx, lane, sb + SM_BAD, wr);                              \
      uint32_t* d = g_O + cta * 9 * 512 + (((it >> 5) - 1) ^ hx) * 1024 + wr * 64 + lane;                      \
      d[0] = w[0]; d[32] = w[1]; d[512] = w[2]; d[544] = w[3];                                                 \
    }                                                                                                          \
    if (it == 96) mbar_arrive_if(bar + 8 * B_SO1, l0 & (bad_heads(sb + SM_BAD, wr) == 0));                     \
    first_tile(a, (it >> 5) ^ hx, lane);                                                                       \
  }
#define ITEM_NEXTQ() { if (it & 2) load_q(a, cta, ((it >> 5) + 1) ^ hx, tid); else prefetch_q(cta, ((it >> 5) + 1) ^ hx, tid); }
#define KV_ADVANCE() { kd += 384; k8 += 8; if (k8 == 24) { k8 = 0; kd = kdesc0; kph ^= 1; } it++; special = ((it + 3) & 31) < 4; }
#define WAIT_UNLESS(OK, BA, PA, BB, PB) if (__builtin_expect(!__all_sync(0xffffffffu, OK), 0)) { mbar_wait(BA, PA); mbar_wait(BB, PB); }
#define EPI_STEP(ACCN, ACCO)                                                                                   \
  {                                                                                                            \
    wg_fence();                                                                                                \
    G1_ISSUE_Z(ACCN, bd)                                                                                       \
    wg_commit();                                                                                               \
    wg_wait<1>();                                                                                              \
    pin<64>(ACCO);                                                                                             \
    mbar_arrive_if(bar + 8 * B_BE + 8 * ((gs - 1) & 3), l0);                                                   \
    gs++;                                                                                                      \
    ad = adesc + 1024; bd = bdesc + (gs & 3) * 1024;                                                           \
    const uint32_t ok = mbar_test(BF_BAR, BF_PH);                                                              \
    h_epilogue(ACCO, hdst);                                                                                    \
    hdst += 4096;                                                                                              \
    __syncwarp();                                                                                              \
    mbar_arrive_if(bar + 8 * B_SH, l0);                                                                        \
    WAIT_UNLESS(ok, BF_BAR, BF_PH, BF_BAR, BF_PH)                                                              \
  }
#define ATT_LOOP1(ACC, ITEMS)                                                                                  \
  do {                                                                                                         \
    wg_fence();                                                                                                \
    issue_att(a, kd);                                                                                          \
    wg_commit();                                                                                               \
    G1_ISSUE(ACC, ad, bd)                                                                                      \
    wg_commit();                                                                                               \
    wg_wait<1>();                                                                                              \
    pin<32>(a.s);                                                                                              \
    mbar_arrive_if(bar + 8 * B_BE + 8 * ((gs - 1) & 3), l0);                                                   \
    mbar_arrive_if(bar + 8 * B_KE + k8, l0);                                                                   \
    TRACE()                                                                                                    \
    if (ITEMS) { if (__builtin_expect(special, 0)) { if (it & 1) ITEM_NEXTQ() else if (!(it & 2)) ITEM_FIRST() } } \
    else __syncwarp();                                                                                         \
    gs++;                                                                                                      \
    KV_ADVANCE()                                                                                               \
    ad += 1024; bd = bdesc + (gs & 3) * 1024;                                                                  \
    const uint32_t ok = mbar_test(BF_BAR, BF_PH) & mbar_test(bar + 8 * B_KF + k8, kph);                        \
    softmax_a(a);                                                                                              \
    WAIT_UNLESS(ok, BF_BAR, BF_PH, bar + 8 * B_KF + k8, kph)                                                   \
    softmax_b(a);                                                                                              \
    pin<8>(a.q);                                                                                               \
  } while (ad != adesc + 9 * 1024);
#pragma unroll 1
    for (int pr = 0;; pr++) {
      ATT_LOOP1(accA, true)
      if (pr == 4) break;
      EPI_STEP(accB, accA)
      ATT_LOOP1(accB, false)
      EPI_STEP(accA, accB)
    }
    STAMP(5);
    wg_wait<0>();
    pin<64>(accA);
    mbar_arrive_if(bar + 8 * B_BE, l0);
    h_epilogue(accA, hdst);
    __syncwarp();
    mbar_arrive_if(bar + 8 * B_SH, l0);
    STAMP(6);
    mbar_wait(bar + 8 * B_GF, 0);
    STAMP(12);

    float acc2[144];
    const uint32_t a2desc = (((sb + wg * 1024) & 0x3FFFF) >> 4) | LO_O;
    const uint32_t b2desc = (((sb + 12288) & 0x3FFFF) >> 4) | LO_B48;
    uint32_t gb = 0;
    ad = a2desc; bd = b2desc;
#define G2_LO(K) wg_ss_n128<HI_O, HI_SW128>(acc2, ad + (K) * 256, bd + (K) * 128);
#define G2_HI(K) wg_ss_n160<HI_O, HI_SW128>(acc2 + 64, ad + (K) * 256, bd + (K) * 128 + 768);
#define ATT_PAIR(ZERO)                                                                                         \
  {                                                                                                            \
    wg_fence();                                                                                                \
    issue_att(a, kd);                                                                                          \
    wg_commit();                                                                                               \
    if (ZERO) { wg_ss_z_n128<HI_O, HI_SW128>(acc2, ad, bd); wg_ss_z_n160<HI_O, HI_SW128>(acc2 + 64, ad, bd + 768); } \
    else { G2_LO(0) G2_HI(0) }                                                                                 \
    G2_LO(1)                                                                                                   \
    wg_commit();                                                                                               \
    wg_wait<1>();                                                                                              \
    pin<32>(a.s);                                                                                              \
    mbar_arrive_if(bar + 8 * B_KE + k8, l0);                                                                   \
    if (!(ZERO)) mbar_arrive_if(bar + 8 * B_GE + 8 * ((gb - 1) & 3), l0);                                      \
    TRACE()                                                                                                    \
    if (!(ZERO)) { if (__builtin_expect(it == 96, 0)) ITEM_FIRST() }                                           \
    KV_ADVANCE()                                                                                               \
    uint32_t ok = mbar_test(bar + 8 * B_KF + k8, kph);                                                         \
    softmax_a(a);                                                                                              \
    WAIT_UNLESS(ok, bar + 8 * B_KF + k8, kph, bar + 8 * B_KF + k8, kph)                                        \
    softmax_b(a);                                                                                              \
    pin<8>(a.q);                                                                                               \
    wg_fence();                                                                                                \
    issue_att(a, kd);                                                                                          \
    wg_commit();                                                                                               \
    G2_HI(1) G2_LO(2) G2_HI(2)                                                                                 \
    wg_commit();                                                                                               \
    wg_wait<1>();                                                                                              \
    pin<32>(a.s);                                                                                              \
    mbar_arrive_if(bar + 8 * B_KE + k8, l0);                                                                   \
    TRACE()                                                                                                    \
    if (!(ZERO)) { if (__builtin_expect(it - 93 < 3, 0)) ITEM_NEXTQ() }                                        \
    KV_ADVANCE()                                                                                               \
    gb++;                                                                                                      \
    ad = a2desc + (gb & 3) * 2688; bd = b2desc + (gb & 3) * 2688;                                              \
         \
    const uint32_t nb = gb == 26 ? bar + 8 * (B_GE + 3) : bar + 8 * B_GF + 8 * (gb & 3), np = gb == 26 ? 1 : (gb >> 2) & 1; \
    ok = mbar_test(nb, np) & mbar_test(bar + 8 * B_KF + k8, kph);                                              \
    softmax_a(a);                                                                                              \
    WAIT_UNLESS(ok, nb, np, bar + 8 * B_KF + k8, kph)                                                          \
    softmax_b(a);                                                                                              \
    pin<8>(a.q);                                                                                               \
    if (!(ZERO) && __builtin_expect(gb == 23, 0)) {      \
      const uint32_t bad = bad_heads(sb + SM_BAD, wr);                                                         \
      if (bad) { repair_rows(cta, wr, bad, 3 ^ hx, false); mbar_arrive_if(bar + 8 * B_SO1, l0); }              \
    }                                                                                                          \
  }
    ATT_PAIR(true)
    do ATT_PAIR(false) while (gb != 26);
    STAMP(13);
#define ATT_ONLY()                                                                                             \
  {                                                                                                            \
    wg_fence();                                                                                                \
    issue_att(a, kd);                                                                                          \
    wg_commit();                                                                                               \
    wg_wait<0>();                                                                                              \
    pin<32>(a.s);                                                                                              \
    mbar_arrive_if(bar + 8 * B_KE + k8, l0);                                                                   \
    TRACE()                                                                                                    \
    KV_ADVANCE()                                                                                               \
    const uint32_t ok = mbar_test(bar + 8 * B_KF + k8, kph);                                                   \
    softmax_a(a);                                                                                              \
    WAIT_UNLESS(ok, bar + 8 * B_KF + k8, kph, bar + 8 * B_KF + k8, kph)                                        \
    softmax_b(a);                                                                                              \
  }
    float fin[48];
    wg_wait<0>(); pin<144>(acc2); mbar_arrive_if(bar + 8 * (B_GE + 1), l0);
    stage_partials(acc2, sb + SM_SEND, fresh_tid());
    asm volatile("fence.proxy.async.shared::cta;" ::: "memory");
    __syncwarp();
    mbar_arrive_if(bar + 8 * B_SP, l0);
    do ATT_ONLY() while (it != 128);
    STAMP(7);
    wg_fence();
    issue_pv(a, kd);
    wg_commit();
    int tid2, bid2;
    asm volatile("mov.u32 %0, %%tid.x;" : "=r"(tid2));
    asm volatile("mov.u32 %0, %%ctaid.x;" : "=r"(bid2));
    const int m2 = bid2 & 15, j2 = bid2 >> 4;
    uint32_t tag;
    asm volatile("ld.shared.u32 %0, [%1];" : "=r"(tag) : "r"(sb + SM_TAG) : "memory");
    wg_wait<0>();
    pin<12>(a.o);
    {
      uint32_t w[4];
      o_normalise(a.o, w, ox0, ox1, 3 ^ hx, lane, sb + SM_BAD, wr);
      ox0 = __shfl_xor_sync(0xffffffffu, ox0, 2); ox1 = __shfl_xor_sync(0xffffffffu, ox1, 2);
      const uint32_t bad = bad_heads(sb + SM_BAD, wr);
      if (bad) {
        uint32_t* d = g_O + cta * 9 * 512 + wr * 64 + lane;
        uint32_t* h = d + (3 ^ hx) * 1024;
        h[0] = w[0]; h[32] = w[1]; h[512] = w[2]; h[544] = w[3]; d[4096] = ox0; d[4128] = ox1;
        __syncwarp();
        repair_rows(cta, wr, bad, 3 ^ hx, true);
        w[0] = __ldcg(h); w[1] = __ldcg(h + 32); w[2] = __ldcg(h + 512); w[3] = __ldcg(h + 544); ox0 = __ldcg(d + 4096); ox1 = __ldcg(d + 4128);
      }
      asm volatile("st.relaxed.gpu.global.v4.b32 [%0], {%1,%2,%3,%4};" ::"l"(g_L + (m2 * 8 + j2) * 384 + tid2), "r"((w[0] & ~1u) | tag), "r"((w[1] & ~1u) | tag),
                   "r"((w[2] & ~1u) | tag), "r"((w[3] & ~1u) | tag) : "memory");
      asm volatile("st.relaxed.gpu.global.v2.b32 [%0], {%1,%2};" ::"l"(reinterpret_cast<uint2*>(g_L + (m2 * 8 + j2) * 384 + 256) + tid2), "r"((ox0 & ~1u) | tag),
                   "r"((ox1 & ~1u) | tag) : "memory");
    }
    STAMP(8);
    uint32_t xv[18];
    load_residual(xv, prm, m2, j2 & 1, j2 >> 1, tid2);
    uint32_t la[48];
    for (uint32_t tries = 0;; tries++) {
      const uint4* p4 = g_L + m2 * 8 * 384 + tid2;
      const uint2* p2 = reinterpret_cast<const uint2*>(g_L + m2 * 8 * 384 + 256) + tid2;
      uint32_t bad = 0;
#pragma unroll
      for (int c = 0; c < 8; c++) {
        asm volatile("ld.relaxed.gpu.global.v4.b32 {%0,%1,%2,%3}, [%4];" : "=r"(la[4 * c]), "=r"(la[4 * c + 1]), "=r"(la[4 * c + 2]), "=r"(la[4 * c + 3]) : "l"(p4 + c * 384) : "memory");
        asm volatile("ld.relaxed.gpu.global.v2.b32 {%0,%1}, [%2];" : "=r"(la[32 + 2 * c]), "=r"(la[33 + 2 * c]) : "l"(p2 + c * 768) : "memory");
      }
#pragma unroll
      for (int i = 0; i < 48; i++) { la[i] ^= tag; bad |= la[i]; }
      if (__all_sync(0xffffffffu, !(bad & 1))) break;
      if (tries > 0x400000u) break;
    }
    pin<48>(la); pin<18>(xv);
    STAMP(19);
    const uint32_t ldesc = (((sb + SM_LB) & 0x3FFFF) >> 4) | LO_BL;
    mbar_wait(bar + 8 * B_OL, 0);
    STAMP(14);
    wg_fence();
    wg_rs_z_n96<HI_SW128>(fin, la[0], la[1], la[2], la[3], ldesc);
#pragma unroll
    for (int k = 1; k < 12; k++) wg_rs_n96<HI_SW128>(fin, la[4 * k], la[4 * k + 1], la[4 * k + 2], la[4 * k + 3], ldesc + k * 128);
    wg_commit();
    mbar_wait(bar + 8 * B_RX, 0);
    STAMP(24);
    wg_wait<0>();
    pin<48>(fin);
#pragma unroll
    for (int i = 0; i < 48; i++) fin[i] += acc2[96 + i];
    STAMP(9);
    final_epilogue(fin, xv, sb + SM_RECV, prm, m2, j2 & 1, j2 >> 1, tid2);
    STAMP(10);
  }
}

typedef CUresult (*EncodeFn)(CUtensorMap*, CUtensorMapDataType, cuuint32_t, void*, const cuuint64_t*, const cuuint64_t*, const cuuint32_t*, const cuuint32_t*,
                             CUtensorMapInterleave, CUtensorMapSwizzle, CUtensorMapL2promotion, CUtensorMapFloatOOBfill);

void enc2d(EncodeFn enc, CUtensorMap* tm, const void* base, uint64_t w, uint64_t h, uint64_t pitch_elems, uint32_t bw, uint32_t bh, CUtensorMapSwizzle sw) {
  cuuint64_t dims[2] = {w, h}, str[1] = {pitch_elems * 2};
  cuuint32_t box[2] = {bw, bh}, es[2] = {1, 1};
  enc(tm, CU_TENSOR_MAP_DATA_TYPE_BFLOAT16, 2, const_cast<void*>(base), dims, str, box, es, CU_TENSOR_MAP_INTERLEAVE_NONE, sw,
      CU_TENSOR_MAP_L2_PROMOTION_L2_128B, CU_TENSOR_MAP_FLOAT_OOB_FILL_NONE);
}

}

extern "C" void kernel_launch(void* const* d_in, const int* in_sizes, int n_in, void* d_out, int out_size) {
  (void)in_sizes; (void)n_in; (void)out_size;
  const __nv_bfloat16* x = (const __nv_bfloat16*)d_in[0];
  const __nv_bfloat16* wqkv = (const __nv_bfloat16*)d_in[1];
  const __nv_bfloat16* wo = (const __nv_bfloat16*)d_in[2];
  const __nv_bfloat16* wg = (const __nv_bfloat16*)d_in[4];
  const __nv_bfloat16* wu = (const __nv_bfloat16*)d_in[5];
  const __nv_bfloat16* wd = (const __nv_bfloat16*)d_in[6];
  void* fn = nullptr;
  cudaDriverEntryPointQueryResult qr;
  cudaGetDriverEntryPoint("cuTensorMapEncodeTiled", &fn, cudaEnableDefault, &qr);
  EncodeFn enc = (EncodeFn)fn;
  void* kvp = nullptr;
  cudaGetSymbolAddress(&kvp, g_KV);
  Params p;
  enc2d(enc, &p.xm, x, DM, SEQ, DM, 64, 128, CU_TENSOR_MAP_SWIZZLE_128B);
  enc2d(enc, &p.kv, kvp, 320, 32 * 256, 320, 192, 8, CU_TENSOR_MAP_SWIZZLE_NONE);
  enc2d(enc, &p.wqkv64, wqkv, 3 * DM, DM, 3 * DM, 64, 64, CU_TENSOR_MAP_SWIZZLE_128B);
  enc2d(enc, &p.wqkv8, wqkv, 3 * DM, DM, 3 * DM, 8, 64, CU_TENSOR_MAP_SWIZZLE_NONE);
  enc2d(enc, &p.wg, wg, FF, DM, FF, 64, 64, CU_TENSOR_MAP_SWIZZLE_128B);
  enc2d(enc, &p.wu, wu, FF, DM, FF, 64, 64, CU_TENSOR_MAP_SWIZZLE_128B);
  for (int v = 0; v < 3; v++) {
    const cuuint64_t wdt = v ? 32 : DM;
    const int c0 = v ? 256 + 32 * (v - 1) : 0;
    for (int e = 0; e < 3; e++) {
      cuuint64_t d3[3] = {wdt, e == 2 ? 2u : 16u, 32}, s3[2] = {DM * 2, 18 * DM * 2};
      cuuint32_t b3[3] = {64, e == 2 ? 2u : 16u, e == 0 ? 3u : e == 1 ? 2u : 8u}, e3[3] = {1, 1, 1};
      enc(e == 0 ? &p.wo3[v] : e == 1 ? &p.wo2[v] : &p.wo16[v], CU_TENSOR_MAP_DATA_TYPE_BFLOAT16, 3, (void*)(wo + c0 + (e == 2 ? 16 * DM : 0)), d3, s3, b3, e3,
          CU_TENSOR_MAP_INTERLEAVE_NONE, CU_TENSOR_MAP_SWIZZLE_128B, CU_TENSOR_MAP_L2_PROMOTION_L2_128B, CU_TENSOR_MAP_FLOAT_OOB_FILL_NONE);
    }
    cuuint64_t dims[5] = {wdt, 2, 2, 4, FF / 16}, str[4] = {DM * 2, 8 * DM * 2, 2 * DM * 2, 16 * DM * 2};
    cuuint32_t box[5] = {64, 2, 2, 4, 3}, es[5] = {1, 1, 1, 1, 1};
    enc(&p.wd[v], CU_TENSOR_MAP_DATA_TYPE_BFLOAT16, 5, (void*)(wd + c0), dims, str, box, es, CU_TENSOR_MAP_INTERLEAVE_NONE,
        CU_TENSOR_MAP_SWIZZLE_128B, CU_TENSOR_MAP_L2_PROMOTION_L2_128B, CU_TENSOR_MAP_FLOAT_OOB_FILL_NONE);
  }
  p.x = x;
  p.out = (__nv_bfloat16*)d_out;
  cudaFuncSetAttribute(fused_kernel, cudaFuncAttributeMaxDynamicSharedMemorySize, SM_TOTAL);
  fused_kernel<<<NCTA, 384, SM_TOTAL, cudaStreamPerThread>>>(p);
}
```

```cpp
#include <cuda_runtime.h>
#include <cuda.h>
#include <cuda_bf16.h>
#include <stdint.h>

namespace {

constexpr int SEQ = 2048, DM = 576, FF = 4608;
constexpr int NCTA = 128;

constexpr uint32_t SM_XN = 0;
constexpr uint32_t SM_RING = 147456;
constexpr uint32_t SM_KV = 212992;
constexpr uint32_t QST = 27648, BST = 16384, KVST = 6144;
constexpr uint32_t G2ST = 43008;
constexpr uint32_t SM_LB = 0, SM_RES = 49152, SM_SEND = 86016, SM_RECV = 143360;
constexpr uint32_t SM_QS = 204800;
constexpr uint32_t SM_BAR = 231936;
constexpr uint32_t SM_TAG = 232436;
constexpr uint32_t SM_BAD = 232432;
constexpr uint32_t SM_TOTAL = 232448;
enum { B_QF = 0, B_QE = 3, B_BF = 6, B_BE = 10, B_GF = 14, B_GE = 18, B_KF = 22, B_KE = 25, B_SK1 = 28, B_SK2 = 29, B_SH = 30, B_SO1 = 31,
       B_SO2 = 32, B_OL = 33, B_SP = 34, B_RX = 35, B_X = 36, B_NR = 45, B_N = 47 };
#define EXP_DELAY 1000
#define EXP_PFD 1500
#define EXP_NOST 0
#define PF_X 0
#define PF_Q 6
constexpr int PF_G1 = 1;
constexpr int NG0 = 5;

constexpr uint32_t HI_SW128 = 0x40000040u;
constexpr uint32_t LO_A = 1u << 16;
constexpr uint32_t LO_B = 512u << 16;
constexpr uint32_t HI_R = 64u, LO_R = 8u << 16;
constexpr uint32_t HI_K = 24u, LO_K = 8u << 16;
constexpr uint32_t HI_V = 8u, LO_V = 24u << 16;
constexpr uint32_t LO_B48 = 384u << 16;
constexpr uint32_t HI_O = 8u, LO_O = 128u << 16;
constexpr uint32_t LO_BL = 1536u << 16;

constexpr float QSCALE = 0.23570226039551584f * 1.4426950408889634f;
constexpr float MOFF = 90.f;

struct __align__(64) Params {
  CUtensorMap xm, wqkv64, wqkv8, wg, wu, kv, wd[3], wo3[3], wo2[3], wo16[3];
  const __nv_bfloat16 *x, *pwqkv, *pwo, *pwg, *pwu, *pwd;
  __nv_bfloat16* out;
};

__device__ __align__(1024) uint32_t g_H[16 * 576 * 512];
__device__ __align__(1024) uint32_t g_O[NCTA * 9 * 512];
__device__ __align__(1024) uint32_t g_KV[32 * SEQ * 20];
__device__ __align__(1024) uint32_t g_Q[NCTA * 4 * 256 * 8];
__device__ __align__(1024) uint4 g_P[NCTA * 3 * 1152];
__device__ __align__(1024) uint4 g_L[NCTA * 384];
__device__ float g_S[NCTA * 8 * SEQ];
__device__ uint32_t g_flags[16 * 32 + NCTA * 32 * 4];
#define FLAG_KV(l, j) (&g_flags[((l) * 8 + (j)) * 32])
#define FLAG_H(c) (&g_flags[16 * 32 + (c) * 32])
#define FLAG_O(c) (&g_flags[16 * 32 + NCTA * 32 + (c) * 32])
#define FLAG_P(c) (&g_flags[16 * 32 + NCTA * 64 + (c) * 32])
#define FLAG_EPOCH(c) (&g_flags[16 * 32 + NCTA * 96 + (c) * 32])
#define STAMP(i)
#define STAMPW(i)
#define TRACE()

template<uint32_t AHI, uint32_t BHI> __device__ __forceinline__ void wg_ss_n192(float* d, uint32_t a, uint32_t b) {
  asm volatile("{\n.reg .pred p;\n.reg .b64 da, db;\nsetp.ne.b32 p, 1, 0;\nmov.b64 da, {%96, %98};\nmov.b64 db, {%97, %99};\n"
    "wgmma.mma_async.sync.aligned.m64n192k16.f32.bf16.bf16 {%0, %1, %2, %3, %4, %5, %6, %7, %8, %9, %10, %11, %12, %13, %14, %15, %16, %17, %18, %19, %20, %21, %22, %23, %24, %25, %26, %27, %28, %29, %30, %31, %32, %33, %34, %35, %36, %37, %38, %39, %40, %41, %42, %43, %44, %45, %46, %47, %48, %49, %50, %51, %52, %53, %54, %55, %56, %57, %58, %59, %60, %61, %62, %63, %64, %65, %66, %67, %68, %69, %70, %71, %72, %73, %74, %75, %76, %77, %78, %79, %80, %81, %82, %83, %84, %85, %86, %87, %88, %89, %90, %91, %92, %93, %94, %95}, da, db, p, 1, 1, 0, 1;\n}\n"
    : "+f"(d[0]), "+f"(d[1]), "+f"(d[2]), "+f"(d[3]), "+f"(d[4]), "+f"(d[5]), "+f"(d[6]), "+f"(d[7]), "+f"(d[8]), "+f"(d[9]), "+f"(d[10]), "+f"(d[11]), "+f"(d[12]), "+f"(d[13]), "+f"(d[14]), "+f"(d[15]), "+f"(d[16]), "+f"(d[17]), "+f"(d[18]), "+f"(d[19]), "+f"(d[20]), "+f"(d[21]), "+f"(d[22]), "+f"(d[23]), "+f"(d[24]), "+f"(d[25]), "+f"(d[26]), "+f"(d[27]), "+f"(d[28]), "+f"(d[29]), "+f"(d[30]), "+f"(d[31]), "+f"(d[32]), "+f"(d[33]), "+f"(d[34]), "+f"(d[35]), "+f"(d[36]), "+f"(d[37]), "+f"(d[38]), "+f"(d[39]), "+f"(d[40]), "+f"(d[41]), "+f"(d[42]), "+f"(d[43]), "+f"(d[44]), "+f"(d[45]), "+f"(d[46]), "+f"(d[47]), "+f"(d[48]), "+f"(d[49]), "+f"(d[50]), "+f"(d[51]), "+f"(d[52]), "+f"(d[53]), "+f"(d[54]), "+f"(d[55]), "+f"(d[56]), "+f"(d[57]), "+f"(d[58]), "+f"(d[59]), "+f"(d[60]), "+f"(d[61]), "+f"(d[62]), "+f"(d[63]), "+f"(d[64]), "+f"(d[65]), "+f"(d[66]), "+f"(d[67]), "+f"(d[68]), "+f"(d[69]), "+f"(d[70]), "+f"(d[71]), "+f"(d[72]), "+f"(d[73]), "+f"(d[74]), "+f"(d[75]), "+f"(d[76]), "+f"(d[77]), "+f"(d[78]), "+f"(d[79]), "+f"(d[80]), "+f"(d[81]), "+f"(d[82]), "+f"(d[83]), "+f"(d[84]), "+f"(d[85]), "+f"(d[86]), "+f"(d[87]), "+f"(d[88]), "+f"(d[89]), "+f"(d[90]), "+f"(d[91]), "+f"(d[92]), "+f"(d[93]), "+f"(d[94]), "+f"(d[95])
    : "r"(a), "r"(b), "n"(AHI), "n"(BHI));
}
template<uint32_t AHI, uint32_t BHI> __device__ __forceinline__ void wg_ss_z_n192(float* d, uint32_t a, uint32_t b) {
  asm volatile("{\n.reg .pred p;\n.reg .b64 da, db;\nsetp.ne.b32 p, 0, 0;\nmov.b64 da, {%96, %98};\nmov.b64 db, {%97, %99};\n"
    "wgmma.mma_async.sync.aligned.m64n192k16.f32.bf16.bf16 {%0, %1, %2, %3, %4, %5, %6, %7, %8, %9, %10, %11, %12, %13, %14, %15, %16, %17, %18, %19, %20, %21, %22, %23, %24, %25, %26, %27, %28, %29, %30, %31, %32, %33, %34, %35, %36, %37, %38, %39, %40, %41, %42, %43, %44, %45, %46, %47, %48, %49, %50, %51, %52, %53, %54, %55, %56, %57, %58, %59, %60, %61, %62, %63, %64, %65, %66, %67, %68, %69, %70, %71, %72, %73, %74, %75, %76, %77, %78, %79, %80, %81, %82, %83, %84, %85, %86, %87, %88, %89, %90, %91, %92, %93, %94, %95}, da, db, p, 1, 1, 0, 1;\n}\n"
    : "=f"(d[0]), "=f"(d[1]), "=f"(d[2]), "=f"(d[3]), "=f"(d[4]), "=f"(d[5]), "=f"(d[6]), "=f"(d[7]), "=f"(d[8]), "=f"(d[9]), "=f"(d[10]), "=f"(d[11]), "=f"(d[12]), "=f"(d[13]), "=f"(d[14]), "=f"(d[15]), "=f"(d[16]), "=f"(d[17]), "=f"(d[18]), "=f"(d[19]), "=f"(d[20]), "=f"(d[21]), "=f"(d[22]), "=f"(d[23]), "=f"(d[24]), "=f"(d[25]), "=f"(d[26]), "=f"(d[27]), "=f"(d[28]), "=f"(d[29]), "=f"(d[30]), "=f"(d[31]), "=f"(d[32]), "=f"(d[33]), "=f"(d[34]), "=f"(d[35]), "=f"(d[36]), "=f"(d[37]), "=f"(d[38]), "=f"(d[39]), "=f"(d[40]), "=f"(d[41]), "=f"(d[42]), "=f"(d[43]), "=f"(d[44]), "=f"(d[45]), "=f"(d[46]), "=f"(d[47]), "=f"(d[48]), "=f"(d[49]), "=f"(d[50]), "=f"(d[51]), "=f"(d[52]), "=f"(d[53]), "=f"(d[54]), "=f"(d[55]), "=f"(d[56]), "=f"(d[57]), "=f"(d[58]), "=f"(d[59]), "=f"(d[60]), "=f"(d[61]), "=f"(d[62]), "=f"(d[63]), "=f"(d[64]), "=f"(d[65]), "=f"(d[66]), "=f"(d[67]), "=f"(d[68]), "=f"(d[69]), "=f"(d[70]), "=f"(d[71]), "=f"(d[72]), "=f"(d[73]), "=f"(d[74]), "=f"(d[75]), "=f"(d[76]), "=f"(d[77]), "=f"(d[78]), "=f"(d[79]), "=f"(d[80]), "=f"(d[81]), "=f"(d[82]), "=f"(d[83]), "=f"(d[84]), "=f"(d[85]), "=f"(d[86]), "=f"(d[87]), "=f"(d[88]), "=f"(d[89]), "=f"(d[90]), "=f"(d[91]), "=f"(d[92]), "=f"(d[93]), "=f"(d[94]), "=f"(d[95])
    : "r"(a), "r"(b), "n"(AHI), "n"(BHI));
}
template<uint32_t AHI, uint32_t BHI> __device__ __forceinline__ void wg_ss_n24(float* d, uint32_t a, uint32_t b) {
  asm volatile("{\n.reg .pred p;\n.reg .b64 da, db;\nsetp.ne.b32 p, 1, 0;\nmov.b64 da, {%12, %14};\nmov.b64 db, {%13, %15};\n"
    "wgmma.mma_async.sync.aligned.m64n24k16.f32.bf16.bf16 {%0, %1, %2, %3, %4, %5, %6, %7, %8, %9, %10, %11}, da, db, p, 1, 1, 0, 1;\n}\n"
    : "+f"(d[0]), "+f"(d[1]), "+f"(d[2]), "+f"(d[3]), "+f"(d[4]), "+f"(d[5]), "+f"(d[6]), "+f"(d[7]), "+f"(d[8]), "+f"(d[9]), "+f"(d[10]), "+f"(d[11])
    : "r"(a), "r"(b), "n"(AHI), "n"(BHI));
}
template<uint32_t AHI, uint32_t BHI> __device__ __forceinline__ void wg_ss_z_n24(float* d, uint32_t a, uint32_t b) {
  asm volatile("{\n.reg .pred p;\n.reg .b64 da, db;\nsetp.ne.b32 p, 0, 0;\nmov.b64 da, {%12, %14};\nmov.b64 db, {%13, %15};\n"
    "wgmma.mma_async.sync.aligned.m64n24k16.f32.bf16.bf16 {%0, %1, %2, %3, %4, %5, %6, %7, %8, %9, %10, %11}, da, db, p, 1, 1, 0, 1;\n}\n"
    : "=f"(d[0]), "=f"(d[1]), "=f"(d[2]), "=f"(d[3]), "=f"(d[4]), "=f"(d[5]), "=f"(d[6]), "=f"(d[7]), "=f"(d[8]), "=f"(d[9]), "=f"(d[10]), "=f"(d[11])
    : "r"(a), "r"(b), "n"(AHI), "n"(BHI));
}
template<uint32_t AHI, uint32_t BHI> __device__ __forceinline__ void wg_ss_n128(float* d, uint32_t a, uint32_t b) {
  asm volatile("{\n.reg .pred p;\n.reg .b64 da, db;\nsetp.ne.b32 p, 1, 0;\nmov.b64 da, {%64, %66};\nmov.b64 db, {%65, %67};\n"
    "wgmma.mma_async.sync.aligned.m64n128k16.f32.bf16.bf16 {%0, %1, %2, %3, %4, %5, %6, %7, %8, %9, %10, %11, %12, %13, %14, %15, %16, %17, %18, %19, %20, %21, %22, %23, %24, %25, %26, %27, %28, %29, %30, %31, %32, %33, %34, %35, %36, %37, %38, %39, %40, %41, %42, %43, %44, %45, %46, %47, %48, %49, %50, %51, %52, %53, %54, %55, %56, %57, %58, %59, %60, %61, %62, %63}, da, db, p, 1, 1, 0, 1;\n}\n"
    : "+f"(d[0]), "+f"(d[1]), "+f"(d[2]), "+f"(d[3]), "+f"(d[4]), "+f"(d[5]), "+f"(d[6]), "+f"(d[7]), "+f"(d[8]), "+f"(d[9]), "+f"(d[10]), "+f"(d[11]), "+f"(d[12]), "+f"(d[13]), "+f"(d[14]), "+f"(d[15]), "+f"(d[16]), "+f"(d[17]), "+f"(d[18]), "+f"(d[19]), "+f"(d[20]), "+f"(d[21]), "+f"(d[22]), "+f"(d[23]), "+f"(d[24]), "+f"(d[25]), "+f"(d[26]), "+f"(d[27]), "+f"(d[28]), "+f"(d[29]), "+f"(d[30]), "+f"(d[31]), "+f"(d[32]), "+f"(d[33]), "+f"(d[34]), "+f"(d[35]), "+f"(d[36]), "+f"(d[37]), "+f"(d[38]), "+f"(d[39]), "+f"(d[40]), "+f"(d[41]), "+f"(d[42]), "+f"(d[43]), "+f"(d[44]), "+f"(d[45]), "+f"(d[46]), "+f"(d[47]), "+f"(d[48]), "+f"(d[49]), "+f"(d[50]), "+f"(d[51]), "+f"(d[52]), "+f"(d[53]), "+f"(d[54]), "+f"(d[55]), "+f"(d[56]), "+f"(d[57]), "+f"(d[58]), "+f"(d[59]), "+f"(d[60]), "+f"(d[61]), "+f"(d[62]), "+f"(d[63])
    : "r"(a), "r"(b), "n"(AHI), "n"(BHI));
}
template<uint32_t AHI, uint32_t BHI> __device__ __forceinline__ void wg_ss_z_n128(float* d, uint32_t a, uint32_t b) {
  asm volatile("{\n.reg .pred p;\n.reg .b64 da, db;\nsetp.ne.b32 p, 0, 0;\nmov.b64 da, {%64, %66};\nmov.b64 db, {%65, %67};\n"
    "wgmma.mma_async.sync.aligned.m64n128k16.f32.bf16.bf16 {%0, %1, %2, %3, %4, %5, %6, %7, %8, %9, %10, %11, %12, %13, %14, %15, %16, %17, %18, %19, %20, %21, %22, %23, %24, %25, %26, %27, %28, %29, %30, %31, %32, %33, %34, %35, %36, %37, %38, %39, %40, %41, %42, %43, %44, %45, %46, %47, %48, %49, %50, %51, %52, %53, %54, %55, %56, %57, %58, %59, %60, %61, %62, %63}, da, db, p, 1, 1, 0, 1;\n}\n"
    : "=f"(d[0]), "=f"(d[1]), "=f"(d[2]), "=f"(d[3]), "=f"(d[4]), "=f"(d[5]), "=f"(d[6]), "=f"(d[7]), "=f"(d[8]), "=f"(d[9]), "=f"(d[10]), "=f"(d[11]), "=f"(d[12]), "=f"(d[13]), "=f"(d[14]), "=f"(d[15]), "=f"(d[16]), "=f"(d[17]), "=f"(d[18]), "=f"(d[19]), "=f"(d[20]), "=f"(d[21]), "=f"(d[22]), "=f"(d[23]), "=f"(d[24]), "=f"(d[25]), "=f"(d[26]), "=f"(d[27]), "=f"(d[28]), "=f"(d[29]), "=f"(d[30]), "=f"(d[31]), "=f"(d[32]), "=f"(d[33]), "=f"(d[34]), "=f"(d[35]), "=f"(d[36]), "=f"(d[37]), "=f"(d[38]), "=f"(d[39]), "=f"(d[40]), "=f"(d[41]), "=f"(d[42]), "=f"(d[43]), "=f"(d[44]), "=f"(d[45]), "=f"(d[46]), "=f"(d[47]), "=f"(d[48]), "=f"(d[49]), "=f"(d[50]), "=f"(d[51]), "=f"(d[52]), "=f"(d[53]), "=f"(d[54]), "=f"(d[55]), "=f"(d[56]), "=f"(d[57]), "=f"(d[58]), "=f"(d[59]), "=f"(d[60]), "=f"(d[61]), "=f"(d[62]), "=f"(d[63])
    : "r"(a), "r"(b), "n"(AHI), "n"(BHI));
}
template<uint32_t AHI, uint32_t BHI> __device__ __forceinline__ void wg_ss_n160(float* d, uint32_t a, uint32_t b) {
  asm volatile("{\n.reg .pred p;\n.reg .b64 da, db;\nsetp.ne.b32 p, 1, 0;\nmov.b64 da, {%80, %82};\nmov.b64 db, {%81, %83};\n"
    "wgmma.mma_async.sync.aligned.m64n160k16.f32.bf16.bf16 {%0, %1, %2, %3, %4, %5, %6, %7, %8, %9, %10, %11, %12, %13, %14, %15, %16, %17, %18, %19, %20, %21, %22, %23, %24, %25, %26, %27, %28, %29, %30, %31, %32, %33, %34, %35, %36, %37, %38, %39, %40, %41, %42, %43, %44, %45, %46, %47, %48, %49, %50, %51, %52, %53, %54, %55, %56, %57, %58, %59, %60, %61, %62, %63, %64, %65, %66, %67, %68, %69, %70, %71, %72, %73, %74, %75, %76, %77, %78, %79}, da, db, p, 1, 1, 0, 1;\n}\n"
    : "+f"(d[0]), "+f"(d[1]), "+f"(d[2]), "+f"(d[3]), "+f"(d[4]), "+f"(d[5]), "+f"(d[6]), "+f"(d[7]), "+f"(d[8]), "+f"(d[9]), "+f"(d[10]), "+f"(d[11]), "+f"(d[12]), "+f"(d[13]), "+f"(d[14]), "+f"(d[15]), "+f"(d[16]), "+f"(d[17]), "+f"(d[18]), "+f"(d[19]), "+f"(d[20]), "+f"(d[21]), "+f"(d[22]), "+f"(d[23]), "+f"(d[24]), "+f"(d[25]), "+f"(d[26]), "+f"(d[27]), "+f"(d[28]), "+f"(d[29]), "+f"(d[30]), "+f"(d[31]), "+f"(d[32]), "+f"(d[33]), "+f"(d[34]), "+f"(d[35]), "+f"(d[36]), "+f"(d[37]), "+f"(d[38]), "+f"(d[39]), "+f"(d[40]), "+f"(d[41]), "+f"(d[42]), "+f"(d[43]), "+f"(d[44]), "+f"(d[45]), "+f"(d[46]), "+f"(d[47]), "+f"(d[48]), "+f"(d[49]), "+f"(d[50]), "+f"(d[51]), "+f"(d[52]), "+f"(d[53]), "+f"(d[54]), "+f"(d[55]), "+f"(d[56]), "+f"(d[57]), "+f"(d[58]), "+f"(d[59]), "+f"(d[60]), "+f"(d[61]), "+f"(d[62]), "+f"(d[63]), "+f"(d[64]), "+f"(d[65]), "+f"(d[66]), "+f"(d[67]), "+f"(d[68]), "+f"(d[69]), "+f"(d[70]), "+f"(d[71]), "+f"(d[72]), "+f"(d[73]), "+f"(d[74]), "+f"(d[75]), "+f"(d[76]), "+f"(d[77]), "+f"(d[78]), "+f"(d[79])
    : "r"(a), "r"(b), "n"(AHI), "n"(BHI));
}
template<uint32_t AHI, uint32_t BHI> __device__ __forceinline__ void wg_ss_z_n160(float* d, uint32_t a, uint32_t b) {
  asm volatile("{\n.reg .pred p;\n.reg .b64 da, db;\nsetp.ne.b32 p, 0, 0;\nmov.b64 da, {%80, %82};\nmov.b64 db, {%81, %83};\n"
    "wgmma.mma_async.sync.aligned.m64n160k16.f32.bf16.bf16 {%0, %1, %2, %3, %4, %5, %6, %7, %8, %9, %10, %11, %12, %13, %14, %15, %16, %17, %18, %19, %20, %21, %22, %23, %24, %25, %26, %27, %28, %29, %30, %31, %32, %33, %34, %35, %36, %37, %38, %39, %40, %41, %42, %43, %44, %45, %46, %47, %48, %49, %50, %51, %52, %53, %54, %55, %56, %57, %58, %59, %60, %61, %62, %63, %64, %65, %66, %67, %68, %69, %70, %71, %72, %73, %74, %75, %76, %77, %78, %79}, da, db, p, 1, 1, 0, 1;\n}\n"
    : "=f"(d[0]), "=f"(d[1]), "=f"(d[2]), "=f"(d[3]), "=f"(d[4]), "=f"(d[5]), "=f"(d[6]), "=f"(d[7]), "=f"(d[8]), "=f"(d[9]), "=f"(d[10]), "=f"(d[11]), "=f"(d[12]), "=f"(d[13]), "=f"(d[14]), "=f"(d[15]), "=f"(d[16]), "=f"(d[17]), "=f"(d[18]), "=f"(d[19]), "=f"(d[20]), "=f"(d[21]), "=f"(d[22]), "=f"(d[23]), "=f"(d[24]), "=f"(d[25]), "=f"(d[26]), "=f"(d[27]), "=f"(d[28]), "=f"(d[29]), "=f"(d[30]), "=f"(d[31]), "=f"(d[32]), "=f"(d[33]), "=f"(d[34]), "=f"(d[35]), "=f"(d[36]), "=f"(d[37]), "=f"(d[38]), "=f"(d[39]), "=f"(d[40]), "=f"(d[41]), "=f"(d[42]), "=f"(d[43]), "=f"(d[44]), "=f"(d[45]), "=f"(d[46]), "=f"(d[47]), "=f"(d[48]), "=f"(d[49]), "=f"(d[50]), "=f"(d[51]), "=f"(d[52]), "=f"(d[53]), "=f"(d[54]), "=f"(d[55]), "=f"(d[56]), "=f"(d[57]), "=f"(d[58]), "=f"(d[59]), "=f"(d[60]), "=f"(d[61]), "=f"(d[62]), "=f"(d[63]), "=f"(d[64]), "=f"(d[65]), "=f"(d[66]), "=f"(d[67]), "=f"(d[68]), "=f"(d[69]), "=f"(d[70]), "=f"(d[71]), "=f"(d[72]), "=f"(d[73]), "=f"(d[74]), "=f"(d[75]), "=f"(d[76]), "=f"(d[77]), "=f"(d[78]), "=f"(d[79])
    : "r"(a), "r"(b), "n"(AHI), "n"(BHI));
}
template<uint32_t BHI> __device__ __forceinline__ void wg_rs_n96(float* d, uint32_t a0, uint32_t a1, uint32_t a2, uint32_t a3, uint32_t b) {
  asm volatile("{\n.reg .pred p;\n.reg .b64 db;\nsetp.ne.b32 p, 1, 0;\nmov.b64 db, {%52, %53};\n"
    "wgmma.mma_async.sync.aligned.m64n96k16.f32.bf16.bf16 {%0, %1, %2, %3, %4, %5, %6, %7, %8, %9, %10, %11, %12, %13, %14, %15, %16, %17, %18, %19, %20, %21, %22, %23, %24, %25, %26, %27, %28, %29, %30, %31, %32, %33, %34, %35, %36, %37, %38, %39, %40, %41, %42, %43, %44, %45, %46, %47}, {%48, %49, %50, %51}, db, p, 1, 1, 1;\n}\n"
    : "+f"(d[0]), "+f"(d[1]), "+f"(d[2]), "+f"(d[3]), "+f"(d[4]), "+f"(d[5]), "+f"(d[6]), "+f"(d[7]), "+f"(d[8]), "+f"(d[9]), "+f"(d[10]), "+f"(d[11]), "+f"(d[12]), "+f"(d[13]), "+f"(d[14]), "+f"(d[15]), "+f"(d[16]), "+f"(d[17]), "+f"(d[18]), "+f"(d[19]), "+f"(d[20]), "+f"(d[21]), "+f"(d[22]), "+f"(d[23]), "+f"(d[24]), "+f"(d[25]), "+f"(d[26]), "+f"(d[27]), "+f"(d[28]), "+f"(d[29]), "+f"(d[30]), "+f"(d[31]), "+f"(d[32]), "+f"(d[33]), "+f"(d[34]), "+f"(d[35]), "+f"(d[36]), "+f"(d[37]), "+f"(d[38]), "+f"(d[39]), "+f"(d[40]), "+f"(d[41]), "+f"(d[42]), "+f"(d[43]), "+f"(d[44]), "+f"(d[45]), "+f"(d[46]), "+f"(d[47])
    : "r"(a0), "r"(a1), "r"(a2), "r"(a3), "r"(b), "n"(BHI));
}
template<uint32_t BHI> __device__ __forceinline__ void wg_rs_z_n96(float* d, uint32_t a0, uint32_t a1, uint32_t a2, uint32_t a3, uint32_t b) {
  asm volatile("{\n.reg .pred p;\n.reg .b64 db;\nsetp.ne.b32 p, 0, 0;\nmov.b64 db, {%52, %53};\n"
    "wgmma.mma_async.sync.aligned.m64n96k16.f32.bf16.bf16 {%0, %1, %2, %3, %4, %5, %6, %7, %8, %9, %10, %11, %12, %13, %14, %15, %16, %17, %18, %19, %20, %21, %22, %23, %24, %25, %26, %27, %28, %29, %30, %31, %32, %33, %34, %35, %36, %37, %38, %39, %40, %41, %42, %43, %44, %45, %46, %47}, {%48, %49, %50, %51}, db, p, 1, 1, 1;\n}\n"
    : "=f"(d[0]), "=f"(d[1]), "=f"(d[2]), "=f"(d[3]), "=f"(d[4]), "=f"(d[5]), "=f"(d[6]), "=f"(d[7]), "=f"(d[8]), "=f"(d[9]), "=f"(d[10]), "=f"(d[11]), "=f"(d[12]), "=f"(d[13]), "=f"(d[14]), "=f"(d[15]), "=f"(d[16]), "=f"(d[17]), "=f"(d[18]), "=f"(d[19]), "=f"(d[20]), "=f"(d[21]), "=f"(d[22]), "=f"(d[23]), "=f"(d[24]), "=f"(d[25]), "=f"(d[26]), "=f"(d[27]), "=f"(d[28]), "=f"(d[29]), "=f"(d[30]), "=f"(d[31]), "=f"(d[32]), "=f"(d[33]), "=f"(d[34]), "=f"(d[35]), "=f"(d[36]), "=f"(d[37]), "=f"(d[38]), "=f"(d[39]), "=f"(d[40]), "=f"(d[41]), "=f"(d[42]), "=f"(d[43]), "=f"(d[44]), "=f"(d[45]), "=f"(d[46]), "=f"(d[47])
    : "r"(a0), "r"(a1), "r"(a2), "r"(a3), "r"(b), "n"(BHI));
}
template<uint32_t BHI> __device__ __forceinline__ void wg_rs_n64(float* d, uint32_t a0, uint32_t a1, uint32_t a2, uint32_t a3, uint32_t b) {
  asm volatile("{\n.reg .pred p;\n.reg .b64 db;\nsetp.ne.b32 p, 1, 0;\nmov.b64 db, {%36, %37};\n"
    "wgmma.mma_async.sync.aligned.m64n64k16.f32.bf16.bf16 {%0, %1, %2, %3, %4, %5, %6, %7, %8, %9, %10, %11, %12, %13, %14, %15, %16, %17, %18, %19, %20, %21, %22, %23, %24, %25, %26, %27, %28, %29, %30, %31}, {%32, %33, %34, %35}, db, p, 1, 1, 0;\n}\n"
    : "+f"(d[0]), "+f"(d[1]), "+f"(d[2]), "+f"(d[3]), "+f"(d[4]), "+f"(d[5]), "+f"(d[6]), "+f"(d[7]), "+f"(d[8]), "+f"(d[9]), "+f"(d[10]), "+f"(d[11]), "+f"(d[12]), "+f"(d[13]), "+f"(d[14]), "+f"(d[15]), "+f"(d[16]), "+f"(d[17]), "+f"(d[18]), "+f"(d[19]), "+f"(d[20]), "+f"(d[21]), "+f"(d[22]), "+f"(d[23]), "+f"(d[24]), "+f"(d[25]), "+f"(d[26]), "+f"(d[27]), "+f"(d[28]), "+f"(d[29]), "+f"(d[30]), "+f"(d[31])
    : "r"(a0), "r"(a1), "r"(a2), "r"(a3), "r"(b), "n"(BHI));
}
template<uint32_t BHI> __device__ __forceinline__ void wg_rs_z_n64(float* d, uint32_t a0, uint32_t a1, uint32_t a2, uint32_t a3, uint32_t b) {
  asm volatile("{\n.reg .pred p;\n.reg .b64 db;\nsetp.ne.b32 p, 0, 0;\nmov.b64 db, {%36, %37};\n"
    "wgmma.mma_async.sync.aligned.m64n64k16.f32.bf16.bf16 {%0, %1, %2, %3, %4, %5, %6, %7, %8, %9, %10, %11, %12, %13, %14, %15, %16, %17, %18, %19, %20, %21, %22, %23, %24, %25, %26, %27, %28, %29, %30, %31}, {%32, %33, %34, %35}, db, p, 1, 1, 0;\n}\n"
    : "=f"(d[0]), "=f"(d[1]), "=f"(d[2]), "=f"(d[3]), "=f"(d[4]), "=f"(d[5]), "=f"(d[6]), "=f"(d[7]), "=f"(d[8]), "=f"(d[9]), "=f"(d[10]), "=f"(d[11]), "=f"(d[12]), "=f"(d[13]), "=f"(d[14]), "=f"(d[15]), "=f"(d[16]), "=f"(d[17]), "=f"(d[18]), "=f"(d[19]), "=f"(d[20]), "=f"(d[21]), "=f"(d[22]), "=f"(d[23]), "=f"(d[24]), "=f"(d[25]), "=f"(d[26]), "=f"(d[27]), "=f"(d[28]), "=f"(d[29]), "=f"(d[30]), "=f"(d[31])
    : "r"(a0), "r"(a1), "r"(a2), "r"(a3), "r"(b), "n"(BHI));
}
template<uint32_t BHI> __device__ __forceinline__ void wg_rs_n24(float* d, uint32_t a0, uint32_t a1, uint32_t a2, uint32_t a3, uint32_t b) {
  asm volatile("{\n.reg .pred p;\n.reg .b64 db;\nsetp.ne.b32 p, 1, 0;\nmov.b64 db, {%16, %17};\n"
    "wgmma.mma_async.sync.aligned.m64n24k16.f32.bf16.bf16 {%0, %1, %2, %3, %4, %5, %6, %7, %8, %9, %10, %11}, {%12, %13, %14, %15}, db, p, 1, 1, 1;\n}\n"
    : "+f"(d[0]), "+f"(d[1]), "+f"(d[2]), "+f"(d[3]), "+f"(d[4]), "+f"(d[5]), "+f"(d[6]), "+f"(d[7]), "+f"(d[8]), "+f"(d[9]), "+f"(d[10]), "+f"(d[11])
    : "r"(a0), "r"(a1), "r"(a2), "r"(a3), "r"(b), "n"(BHI));
}
template<uint32_t BHI> __device__ __forceinline__ void wg_rs_z_n24(float* d, uint32_t a0, uint32_t a1, uint32_t a2, uint32_t a3, uint32_t b) {
  asm volatile("{\n.reg .pred p;\n.reg .b64 db;\nsetp.ne.b32 p, 0, 0;\nmov.b64 db, {%16, %17};\n"
    "wgmma.mma_async.sync.aligned.m64n24k16.f32.bf16.bf16 {%0, %1, %2, %3, %4, %5, %6, %7, %8, %9, %10, %11}, {%12, %13, %14, %15}, db, p, 1, 1, 1;\n}\n"
    : "=f"(d[0]), "=f"(d[1]), "=f"(d[2]), "=f"(d[3]), "=f"(d[4]), "=f"(d[5]), "=f"(d[6]), "=f"(d[7]), "=f"(d[8]), "=f"(d[9]), "=f"(d[10]), "=f"(d[11])
    : "r"(a0), "r"(a1), "r"(a2), "r"(a3), "r"(b), "n"(BHI));
}

__device__ __forceinline__ void wg_fence() { asm volatile("wgmma.fence.sync.aligned;" ::: "memory"); }
__device__ __forceinline__ void wg_commit() { asm volatile("wgmma.commit_group.sync.aligned;" ::: "memory"); }
template <int N> __device__ __forceinline__ void wg_wait() { asm volatile("wgmma.wait_group.sync.aligned %0;" ::"n"(N) : "memory"); }
template <int R> __device__ __forceinline__ void pin(float* d) {
#pragma unroll
  for (int i = 0; i < R; i++) asm volatile("" : "+f"(d[i])::"memory");
}
template <int R> __device__ __forceinline__ void pin(uint32_t* d) {
#pragma unroll
  for (int i = 0; i < R; i++) asm volatile("" : "+r"(d[i])::"memory");
}
__device__ __forceinline__ float ex2(float x) { float y; asm("ex2.approx.ftz.f32 %0, %1;" : "=f"(y) : "f"(x)); return y; }
__device__ __forceinline__ float tanh_fast(float x) { float y; asm("tanh.approx.f32 %0, %1;" : "=f"(y) : "f"(x)); return y; }
__device__ __forceinline__ uint32_t pack(float lo, float hi) { uint32_t r; asm("cvt.rn.bf16x2.f32 %0, %1, %2;" : "=r"(r) : "f"(hi), "f"(lo)); return r; }
__device__ __forceinline__ float bf_lo(uint32_t v) { return __uint_as_float(v << 16); }
__device__ __forceinline__ float bf_hi(uint32_t v) { return __uint_as_float(v & 0xffff0000u); }
__device__ __forceinline__ float bf_round(float x) { return bf_lo(pack(x, 0.f)); }

__device__ __forceinline__ void mbar_init(uint32_t bar, uint32_t cnt) { asm volatile("mbarrier.init.shared::cta.b64 [%0], %1;" ::"r"(bar), "r"(cnt) : "memory"); }
__device__ __forceinline__ void mbar_expect(uint32_t bar, uint32_t bytes) { asm volatile("mbarrier.arrive.expect_tx.shared::cta.b64 _, [%0], %1;" ::"r"(bar), "r"(bytes) : "memory"); }
__device__ __forceinline__ void mbar_arrive(uint32_t bar) { asm volatile("mbarrier.arrive.shared::cta.b64 _, [%0];" ::"r"(bar) : "memory"); }
__device__ __forceinline__ void mbar_wait(uint32_t bar, uint32_t parity) {
  asm volatile(
      "{\n.reg .pred p;\n.reg .u32 c;\n"
      "mbarrier.try_wait.parity.shared::cta.b64 p, [%0], %1;\n"
      "@p bra.uni DONE;\n"
      "mov.u32 c, 0;\n"
      "LOOP:\n"
      "mbarrier.try_wait.parity.shared::cta.b64 p, [%0], %1;\n"
      "@p bra.uni DONE;\n"
      "add.u32 c, c, 1;\n"
      "setp.lt.u32 p, c, 0x4000000;\n"
      "@p bra.uni LOOP;\n"
      "trap;\n"
      "DONE:\n}\n" ::"r"(bar), "r"(parity) : "memory");
}
__device__ __forceinline__ uint32_t mbar_test(uint32_t bar, uint32_t parity) {
  uint32_t ok;
  asm volatile("{\n.reg .pred p;\nmbarrier.test_wait.parity.shared::cta.b64 p, [%1], %2;\nselp.u32 %0, 1, 0, p;\n}\n" : "=r"(ok) : "r"(bar), "r"(parity) : "memory");
  return ok;
}
__device__ __forceinline__ void mbar_arrive_if(uint32_t bar, uint32_t cond) {
  asm volatile("{\n.reg .pred p;\nsetp.ne.u32 p, %1, 0;\n@p mbarrier.arrive.shared::cta.b64 _, [%0];\n}\n" ::"r"(bar), "r"(cond) : "memory");
}
__device__ __forceinline__ uint32_t bsub2(uint32_t a, uint32_t b) { uint32_t d; asm("sub.rn.bf16x2 %0, %1, %2;" : "=r"(d) : "r"(a), "r"(b)); return d; }
__device__ __forceinline__ uint32_t bscale2(uint32_t d, uint32_t hi, uint32_t lo) {
  uint32_t t, r;
  asm("mul.rn.bf16x2 %0, %1, %2;" : "=r"(t) : "r"(d), "r"(lo));
  asm("fma.rn.bf16x2 %0, %1, %2, %3;" : "=r"(r) : "r"(d), "r"(hi), "r"(t));
  return r;
}
__device__ __forceinline__ void flag_wait(const uint32_t* f, uint32_t target) {
  asm volatile(
      "{\n.reg .pred p;\n.reg .u32 c, v;\n"
      "mov.u32 c, 0;\n"
      "LOOP:\n"
      "ld.acquire.gpu.global.u32 v, [%0];\n"
      "sub.u32 v, v, %1;\n"
      "setp.ge.s32 p, v, 0;\n"
      "@p bra DONE;\n"
      "add.u32 c, c, 1;\n"
      "setp.lt.u32 p, c, 0x1000000;\n"
      "@p bra LOOP;\n"
      "trap;\n"
      "DONE:\n}\n" ::"l"(f), "r"(target) : "memory");
}
__device__ __forceinline__ uint32_t flag_wait_v(const uint32_t* f, uint32_t target) {
  uint32_t v;
  asm volatile(
      "{\n.reg .pred p;\n.reg .u32 c, d;\n"
      "mov.u32 c, 0;\n"
      "LOOP:\n"
      "ld.acquire.gpu.global.u32 %0, [%1];\n"
      "sub.u32 d, %0, %2;\n"
      "setp.ge.s32 p, d, 0;\n"
      "@p bra DONE;\n"
      "add.u32 c, c, 1;\n"
      "setp.lt.u32 p, c, 0x1000000;\n"
      "@p bra LOOP;\n"
      "trap;\n"
      "DONE:\n}\n" : "=&r"(v) : "l"(f), "r"(target) : "memory");
  return v;
}
__device__ __forceinline__ float sqrt_fast(float x) { float y; asm("sqrt.approx.f32 %0, %1;" : "=f"(y) : "f"(x)); return y; }
__device__ __forceinline__ float rcp_fast(float x) { float y; asm("rcp.approx.ftz.f32 %0, %1;" : "=f"(y) : "f"(x)); return y; }
__device__ __forceinline__ void ldsm4(uint32_t* v, uint32_t addr) {
  asm volatile("ldmatrix.sync.aligned.m8n8.x4.shared.b16 {%0,%1,%2,%3}, [%4];" : "=r"(v[0]), "=r"(v[1]), "=r"(v[2]), "=r"(v[3]) : "r"(addr) : "memory");
}
__device__ __forceinline__ void stsm4(uint32_t addr, uint32_t a, uint32_t b, uint32_t c, uint32_t d) {
  asm volatile("stmatrix.sync.aligned.m8n8.x4.shared.b16 [%0], {%1,%2,%3,%4};" ::"r"(addr), "r"(a), "r"(b), "r"(c), "r"(d) : "memory");
}
__device__ __forceinline__ void flag_add(uint32_t* f) { asm volatile("red.relaxed.gpu.global.add.u32 [%0], 1;" ::"l"(f) : "memory"); }
__device__ __forceinline__ void fence_gpu() { asm volatile("fence.acq_rel.gpu;" ::: "memory"); }
#define FENCE_G 1
__device__ __forceinline__ void fence_async() { if (FENCE_G) asm volatile("fence.proxy.async.global;" ::: "memory"); else asm volatile("fence.proxy.async;" ::: "memory"); }
__device__ __forceinline__ void tma2d(uint32_t dst, const CUtensorMap* tm, uint32_t bar, int c0, int c1) {
  asm volatile("cp.async.bulk.tensor.2d.shared::cluster.global.mbarrier::complete_tx::bytes [%0], [%1, {%3, %4}], [%2];" ::"r"(dst), "l"(tm), "r"(bar), "r"(c0), "r"(c1) : "memory");
}
__device__ __forceinline__ void tma2d_h(uint32_t dst, const CUtensorMap* tm, uint32_t bar, int c0, int c1, uint64_t pol) {
  asm volatile("cp.async.bulk.tensor.2d.shared::cluster.global.mbarrier::complete_tx::bytes.L2::cache_hint [%0], [%1, {%3, %4}], [%2], %5;" ::"r"(dst), "l"(tm), "r"(bar), "r"(c0), "r"(c1), "l"(pol) : "memory");
}
__device__ __forceinline__ void bulk_s2g(void* dst, uint32_t src, uint32_t bytes) {
  asm volatile("cp.async.bulk.global.shared::cta.bulk_group [%0], [%1], %2;" ::"l"(dst), "r"(src), "r"(bytes) : "memory");
}
__device__ __forceinline__ void mma_ones(float* c, const uint32_t* a) {
  asm("mma.sync.aligned.m16n8k16.row.col.f32.bf16.bf16.f32 {%0,%1,%2,%3}, {%4,%5,%6,%7}, {%8,%8}, {%0,%1,%2,%3};"
      : "+f"(c[0]), "+f"(c[1]), "+f"(c[2]), "+f"(c[3]) : "r"(a[0]), "r"(a[1]), "r"(a[2]), "r"(a[3]), "r"(0x3f803f80u));
}
__device__ __forceinline__ void tma5d(uint32_t dst, const CUtensorMap* tm, uint32_t bar, int c0, int c4) {
  asm volatile("cp.async.bulk.tensor.5d.shared::cluster.global.mbarrier::complete_tx::bytes [%0], [%1, {%3, %5, %5, %5, %4}], [%2];" ::"r"(dst), "l"(tm), "r"(bar), "r"(c0), "r"(c4), "r"(0) : "memory");
}
__device__ __forceinline__ void tma3d(uint32_t dst, const CUtensorMap* tm, uint32_t bar, int c0, int c2) {
  asm volatile("cp.async.bulk.tensor.3d.shared::cluster.global.mbarrier::complete_tx::bytes [%0], [%1, {%3, %5, %4}], [%2];" ::"r"(dst), "l"(tm), "r"(bar), "r"(c0), "r"(c2), "r"(0) : "memory");
}
__device__ __forceinline__ void bulk_g2s(uint32_t dst, const void* src, uint32_t bytes, uint32_t bar) {
  asm volatile("cp.async.bulk.shared::cluster.global.mbarrier::complete_tx::bytes [%0], [%1], %2, [%3];" ::"r"(dst), "l"(src), "r"(bytes), "r"(bar) : "memory");
}
__device__ __forceinline__ void pf_line(const void* p) { asm volatile("prefetch.global.L2 [%0];" ::"l"(p) : "memory"); }
__device__ __forceinline__ int fresh_tid() { int v; asm volatile("mov.u32 %0, %%tid.x;" : "=r"(v)); return v; }
struct Att {
  float s[32];
  float o[12];
  uint32_t p[16];
  uint32_t q[8];
};

__device__ __forceinline__ float warp_sum(float v) {
#pragma unroll 1
  for (int d = 16; d; d >>= 1) v += __shfl_xor_sync(0xffffffffu, v, d);
  return v;
}
#define OPAQUE(x) asm volatile("" : "+r"(x))
__device__ __forceinline__ void attn_slow_row(int cta, uint32_t& w) {
  float mx = -INFINITY;
#pragma unroll 1
  for (uint32_t key = threadIdx.x & 31; key < SEQ; key += 32) {
    float s = 0.f;
#pragma unroll 1
    for (uint32_t v = 0; v < 9; v++) {
      OPAQUE(w); OPAQUE(key);
      const uint32_t hp = (w >> 4) & 3, pos = (v + hp) & 3;
      const uint32_t q = g_Q[(((cta * 4 + hp) * 2 + (v >> 3)) * 256 + ((w >> 6) & 7) * 32 + (w & 7) * 4 + pos) * 4 + 2 * ((v >> 2) & 1) + ((w >> 3) & 1)];
      const uint32_t u = g_KV[(4 * (cta & 7) + hp) * SEQ * 20 + (key >> 3) * 160 + (key & 7) * 4 + (v >> 2) * 32 + pos];
      s = fmaf(bf_lo(q), bf_lo(u), fmaf(bf_hi(q), bf_hi(u), s));
    }
    g_S[(cta * 8 + ((w >> 6) & 7)) * SEQ + key] = s;
    mx = fmaxf(mx, s);
  }
#pragma unroll 1
  for (int d = 16; d; d >>= 1) mx = fmaxf(mx, __shfl_xor_sync(0xffffffffu, mx, d));
  float l = 0.f;
#pragma unroll 1
  for (uint32_t key = threadIdx.x & 31; key < SEQ; key += 32) l += ex2(g_S[(cta * 8 + ((w >> 6) & 7)) * SEQ + key] - mx);
  l = 2.f * rcp_fast(warp_sum(l));
#pragma unroll 1
  for (uint32_t v = w >> 9; v < 9; v++) {
    float a = 0.f, b = 0.f;
#pragma unroll 1
    for (uint32_t key = threadIdx.x & 31; key < SEQ; key += 32) {
      OPAQUE(w); OPAQUE(v);
      const uint32_t hp = (w >> 4) & 3;
      const uint32_t u = g_KV[(4 * (cta & 7) + hp) * SEQ * 20 + (key >> 3) * 160 + (key & 7) * 4 + (v < 8 ? (3 + (v >> 2)) * 32 + (v & 3) : 64 + ((hp + 2) & 3))];
      const float p = ex2(g_S[(cta * 8 + ((w >> 6) & 7)) * SEQ + key] - mx);
      a = fmaf(p, bf_lo(u), a); b = fmaf(p, bf_hi(u), b);
    }
    a = warp_sum(a); b = warp_sum(b);
    OPAQUE(w);
    const uint32_t hp = (w >> 4) & 3;
    if ((threadIdx.x & 31) == 0) g_O[cta * 9 * 512 + (((w >> 6) & 7) * 16 + (w & 15)) * 4 + (v < 8 ? (2 * hp + (v >> 2)) * 512 + (v & 3) : 8 * 512 + hp)] = pack(a * l, b * l);
  }
}

__device__ __forceinline__ uint32_t bad_heads(uint32_t bad_addr, int wr) {
  uint32_t bad;
  __syncwarp();
  asm volatile("ld.volatile.shared.u32 %0, [%1];" : "=r"(bad) : "r"(bad_addr) : "memory");
  return __shfl_sync(0xffffffffu, (bad >> (4 * wr)) & 15, 0);
}
__device__ __forceinline__ void repair_rows(int cta, int wr, uint32_t bad, int last_head, bool final) {
#pragma unroll 1
  for (uint32_t w = wr * 64; w < wr * 64 + 64; w++) {
    if (!((bad >> ((w >> 4) & 3)) & 1)) continue;
    if (final && ((w >> 4) & 3) != last_head) w |= 8u << 9;
    attn_slow_row(cta, w);
    w &= 511;
  }
  __syncwarp();
}
__device__ __forceinline__ void o_normalise(const float* o, uint32_t* w, uint32_t& x0, uint32_t& x1, int hp, int lane, uint32_t bad_addr, int wr) {
  const int src = (lane & ~3) | ((hp + 1) & 3);
  float l0 = __shfl_sync(0xffffffffu, o[0], src), l1 = __shfl_sync(0xffffffffu, o[2], src);
  float sa = 0.f;
#pragma unroll
  for (int i = 0; i < 12; i++) sa += fabsf(o[i]);
  bool ok = (l0 <= 1.329228e36f) && (l1 <= 1.329228e36f) && (l0 > 0.f) && (l1 > 0.f) && (sa <= 3.0e38f);
  float i0 = 2.f * rcp_fast(l0), i1 = 2.f * rcp_fast(l1);
  w[0] = pack(o[4] * i0, o[5] * i0);
  w[1] = pack(o[6] * i1, o[7] * i1);
  w[2] = pack(o[8] * i0, o[9] * i0);
  w[3] = pack(o[10] * i1, o[11] * i1);
  if ((lane & 3) == ((hp + 2) & 3)) { x0 = pack(o[0] * i0, o[1] * i0); x1 = pack(o[2] * i1, o[3] * i1); }
  if (!ok) asm volatile("red.shared.or.b32 [%0], %1;" ::"r"(bad_addr), "r"(1u << (4 * wr + hp)) : "memory");
}

__device__ __forceinline__ void issue_pv(Att& a, uint32_t kdesc) {
  const uint32_t vdesc = kdesc + 192 + (LO_V - LO_K);
#pragma unroll
  for (int k = 0; k < 4; k++) wg_rs_n24<HI_V>(a.o, a.p[4 * k], a.p[4 * k + 1], a.p[4 * k + 2], a.p[4 * k + 3], vdesc + k * 48);
}
__device__ __forceinline__ void issue_att(Att& a, uint32_t kdesc) {
  issue_pv(a, kdesc);
  wg_rs_z_n64<HI_K>(a.s, a.q[0], a.q[1], a.q[2], a.q[3], kdesc);
  wg_rs_n64<HI_K>(a.s, a.q[4], a.q[5], a.q[6], a.q[7], kdesc + 16);
}
__device__ __forceinline__ void softmax_a(Att& a) {
#pragma unroll
  for (int i = 0; i < 9; i++) a.p[i] = pack(ex2(a.s[2 * i]), ex2(a.s[2 * i + 1]));
  a.s[18] = ex2(a.s[18]); a.s[19] = ex2(a.s[19]);
  pin<9>(a.p); pin<2>(a.s + 18);
}
__device__ __forceinline__ void softmax_b(Att& a) {
  a.p[9] = pack(a.s[18], a.s[19]);
#pragma unroll
  for (int i = 10; i < 16; i++) a.p[i] = pack(ex2(a.s[2 * i]), ex2(a.s[2 * i + 1]));
  pin<7>(a.p + 9);
}
__device__ __forceinline__ void first_tile(Att& a, int hp, int lane) {
  float m0 = fmaxf(a.s[0], a.s[1]), m1 = fmaxf(a.s[2], a.s[3]);
#pragma unroll
  for (int i = 4; i < 32; i += 4) { m0 = fmaxf(m0, fmaxf(a.s[i], a.s[i + 1])); m1 = fmaxf(m1, fmaxf(a.s[i + 2], a.s[i + 3])); }
  m0 = fmaxf(m0, __shfl_xor_sync(0xffffffffu, m0, 1)); m1 = fmaxf(m1, __shfl_xor_sync(0xffffffffu, m1, 1));
  m0 = fmaxf(m0, __shfl_xor_sync(0xffffffffu, m0, 2)); m1 = fmaxf(m1, __shfl_xor_sync(0xffffffffu, m1, 2));
  float n0 = -(m0 + MOFF), n1 = -(m1 + MOFF);
  float h0 = bf_round(n0), h1 = bf_round(n1);
  uint32_t e0 = pack(h0, n0 - h0), e1 = pack(h1, n1 - h1);
  n0 = h0 + bf_hi(e0); n1 = h1 + bf_hi(e1);
  if ((lane & 3) == ((hp + 1) & 3)) { a.q[4] = e0; a.q[5] = e1; }
#pragma unroll
  for (int i = 0; i < 32; i += 4) { a.s[i] += n0; a.s[i + 1] += n0; a.s[i + 2] += n1; a.s[i + 3] += n1; }
#pragma unroll
  for (int i = 0; i < 12; i++) a.o[i] = 0.f;
  pin<12>(a.o); pin<8>(a.q);
}
__device__ __forceinline__ void fetch_q(uint32_t* q, int cta, int hp, int tid) {
  const uint4* src = reinterpret_cast<const uint4*>(g_Q) + (cta * 4 + hp) * 512 + tid;
  const uint4 u = __ldcg(src);
  const uint2 v = __ldcg(reinterpret_cast<const uint2*>(src + 256));
  q[0] = u.x; q[1] = u.y; q[2] = u.z; q[3] = u.w; q[4] = v.x; q[5] = v.y;
}
__device__ __forceinline__ void h_epilogue(const float* acc, uint32_t* dst) {
#pragma unroll
  for (int b = 0; b < 4; b++) {
    uint32_t w[2][2];
#pragma unroll
    for (int i = 0; i < 2; i++) {
      float h[4];
#pragma unroll
      for (int e = 0; e < 4; e++) {
        const float g = acc[(2 * b + i) * 4 + e], u = acc[32 + (2 * b + i) * 4 + e];
        h[e] = fmaf(tanh_fast(0.5f * g), u, u);
      }
      w[0][i] = pack(h[0], h[1]); w[1][i] = pack(h[2], h[3]);
    }
    if (!EXP_NOST || w[0][0] == 0x12345678) {
    *reinterpret_cast<uint2*>(dst + 1024 * b) = make_uint2(w[0][0], w[0][1]);
    *reinterpret_cast<uint2*>(dst + 1024 * b + 32) = make_uint2(w[1][0], w[1][1]);
    }
  }
}
__device__ __forceinline__ void rotate9(uint32_t (&v)[9][2]) {
#pragma unroll
  for (int rh = 0; rh < 2; rh++) {
    const uint32_t r = v[8][rh];
#pragma unroll
    for (int i = 8; i > 0; i--) v[i][rh] = v[i - 1][rh];
    v[0][rh] = r;
  }
}
template <int HP> __device__ __forceinline__ void store_kv_head(uint32_t (&pk)[2][9][2], uint32_t* kvp, int lane) {
  const int t = lane & 3;
  const bool up = t < HP;
#pragma unroll
  for (int rh = 0; rh < 2; rh++) {
    uint32_t* d = kvp + HP * SEQ * 20 + rh * 160;
    d[0] = up ? pk[0][2 * HP + 1][rh] : pk[0][2 * HP][rh];
    d[32] = up ? pk[0][2 * HP + 2][rh] : pk[0][2 * HP + 1][rh];
    d[96 + ((t - HP) & 3) - t] = up ? pk[1][2 * HP + 1][rh] : pk[1][2 * HP][rh];
    d[128 + ((t - HP) & 3) - t] = up ? pk[1][2 * HP + 2][rh] : pk[1][2 * HP + 1][rh];
    const uint32_t v9 = __shfl_sync(0xffffffffu, pk[1][2 * HP + 2][rh], (lane & ~3) | HP);
    d[64] = t == HP ? pk[0][2 * HP + 2][rh] : t == ((HP + 1) & 3) ? 0x3f803f80u : t == ((HP + 2) & 3) ? v9 : 0u;
  }
}

__device__ __forceinline__ void stage_partials(const float* acc, uint32_t dst, int tid) {
#pragma unroll
  for (int i = 0; i < 12; i++) {
    const float* v = acc + 8 * i;
    asm volatile("st.shared.v4.b32 [%0], {%1,%2,%3,%4};" ::"r"(dst + i * 4096 + tid * 16), "r"(pack(v[0], v[1])), "r"(pack(v[2], v[3])), "r"(pack(v[4], v[5])), "r"(pack(v[6], v[7])) : "memory");
  }
#pragma unroll
  for (int d = 0; d < 4; d++) {
    const float* v = acc + 128 + 8 * (d & 1) + 2 * (d >> 1);
    asm volatile("st.shared.v2.b32 [%0], {%1,%2};" ::"r"(dst + 49152 + d * 2048 + tid * 8), "r"(pack(v[0], v[1])), "r"(pack(v[4], v[5])) : "memory");
  }
}
__device__ __forceinline__ void load_residual(uint32_t* xv, uint32_t res, int q, int tid) {
  const int g = (tid & 31) >> 2;
  const uint32_t r0 = res + ((tid >> 5) * 16 + g) * 128 + (tid & 3) * 4;
#pragma unroll
  for (int i = 0; i < 16; i++) asm volatile("ld.shared.b32 %0, [%1];" : "=r"(xv[i]) : "r"(r0 + (i & 1) * 1024 + (((i >> 1) ^ g) << 4)) : "memory");
#pragma unroll
  for (int i = 0; i < 2; i++) asm volatile("ld.shared.b32 %0, [%1];" : "=r"(xv[16 + i]) : "r"(r0 + 16384 + (q >> 1) * 1024 + (((2 * (q & 1) + i) ^ g) << 4)) : "memory");
}
__device__ __forceinline__ void final_epilogue(const float* acc, const uint32_t* xv, uint32_t recv, const Params& prm, int m, int hh, int q, int tid) {
  float own[4];
#pragma unroll
  for (int e = 0; e < 4; e++) {
    const int o = 32 + (e & 1) + 4 * (e >> 1);
    const float s0 = (q & 2) ? acc[o + 2] : acc[o], s1 = (q & 2) ? acc[o + 10] : acc[o + 8];
    own[e] = (q & 1) ? s1 : s0;
  }
  uint32_t v[3][18];
#pragma unroll
  for (int d = 0; d < 3; d++) {
#pragma unroll
    for (int i = 0; i < 4; i++)
      asm volatile("ld.shared.v4.b32 {%0,%1,%2,%3}, [%4];" : "=r"(v[d][4 * i]), "=r"(v[d][4 * i + 1]), "=r"(v[d][4 * i + 2]), "=r"(v[d][4 * i + 3])
                   : "r"(recv + d * 18432 + i * 4096 + tid * 16) : "memory");
    asm volatile("ld.shared.v2.b32 {%0,%1}, [%2];" : "=r"(v[d][16]), "=r"(v[d][17]) : "r"(recv + d * 18432 + 16384 + tid * 8) : "memory");
  }
  const size_t off = (size_t)(128 * m + (tid >> 5) * 16 + ((tid & 31) >> 2)) * DM + 2 * (tid & 3);
  const bool odd = tid & 1;
  uint32_t* o1 = reinterpret_cast<uint32_t*>(prm.out + off + 320 * hh + 64 * q) + (odd ? 3 : 0);
  uint32_t* o2 = reinterpret_cast<uint32_t*>(prm.out + off + 256 + 32 * hh + 16 * (q & 1) + (q >> 1) * 8 * DM) + (odd ? 3 : 0);
  uint32_t r[18];
#pragma unroll
  for (int i = 0; i < 18; i++) {
    const float lo = (i < 16 ? acc[2 * i] : own[2 * (i - 16)]) + ((bf_lo(v[0][i]) + bf_lo(v[1][i])) + bf_lo(v[2][i]));
    const float hi = (i < 16 ? acc[2 * i + 1] : own[2 * (i - 16) + 1]) + ((bf_hi(v[0][i]) + bf_hi(v[1][i])) + bf_hi(v[2][i]));
    r[i] = pack(fmaf(lo, 0.5f, bf_lo(xv[i])), fmaf(hi, 0.5f, bf_hi(xv[i])));
  }
#pragma unroll
  for (int i = 0; i < 9; i++) {
    const uint32_t A = i < 8 ? r[4 * (i >> 1) + (i & 1)] : r[16], B = i < 8 ? r[4 * (i >> 1) + 2 + (i & 1)] : r[17];
    const uint32_t y = __shfl_xor_sync(0xffffffffu, odd ? A : B, 1);
    *reinterpret_cast<uint2*>(i < 8 ? o1 + 8 * (i >> 1) + (i & 1) * 8 * (DM / 2) : o2) = odd ? make_uint2(y, B) : make_uint2(A, y);
  }
}

__global__ void __launch_bounds__(384, 1) fused_kernel(const __grid_constant__ Params prm) {
  extern __shared__ __align__(1024) uint8_t smem[];
  const uint32_t sb = (uint32_t)__cvta_generic_to_shared(smem);
  const uint32_t bar = sb + SM_BAR;
  const int m = blockIdx.x & 15, j = blockIdx.x >> 4;
  const int cta = m * 8 + j;
  const int wr = __shfl_sync(0xffffffffu, (int)(threadIdx.x >> 5), 0);
  const int wg = wr >> 2;
  const int lane = threadIdx.x & 31;
  STAMP(0);
  if (PF_X && threadIdx.x < 144) pf_line(prm.x + (size_t)cta * 16 * DM + threadIdx.x * 64);
  if (wg == 2 && lane == 0) {
    if (wr == 8) {
      asm volatile("prefetch.tensormap [%0];" ::"l"(&prm.xm) : "memory");
#pragma unroll
      for (int c = 0; c < 9; c++) mbar_init(bar + 8 * (B_X + c), 1);
#pragma unroll
      for (int c = 0; c < 9; c++) mbar_expect(bar + 8 * (B_X + c), 16384);
      asm volatile("fence.proxy.async.shared::cta;" ::: "memory");
#pragma unroll
      for (int c = 0; c < 3; c++) tma2d(sb + SM_XN + c * 16384, &prm.xm, bar + 8 * (B_X + c), 64 * c, 128 * m);
    } else {
      const uint32_t b0 = bar + 112 * (wr - 9);
#pragma unroll
      for (int i = 0; i < 14; i++) {
        const uint32_t c0 = (i < 3 || (i >= 6 && i < 10)) ? 1 : 8, c1 = (i < 4 || (i >= 8 && i < 11)) ? 1 : 8, c2 = (i == 5 || i == 7) ? 1 : 8;
        if (i < 8 || wr != 11) mbar_init(b0 + 8 * i, wr == 9 ? c0 : wr == 10 ? c1 : c2);
      }
      if (wr == 11) {
        mbar_init(bar + 8 * B_NR, 4); mbar_init(bar + 8 * (B_NR + 1), 4);
        asm volatile("st.shared.u32 [%0], 0;" ::"r"(sb + SM_BAD) : "memory");
        if (sb & 1023) asm volatile("trap;");
      }
      asm volatile("fence.proxy.async.shared::cta;" ::: "memory");
    }
  }
  static_assert(B_QE == 3 && B_BF == 6 && B_BE == 10 && B_GF == 14 && B_GE == 18 && B_KF == 22 && B_KE == 25 && B_SK1 == 28 && B_OL == 33 && B_RX == 35, "");
  __syncthreads();

  if (wg == 2) {
    asm volatile("setmaxnreg.dec.sync.aligned.u32 24;");
    const int pw = wr & 3;
    const uint32_t epoch = *(volatile uint32_t*)FLAG_EPOCH(cta);
    const int hh = j & 1;
#define ACOL(A) (320 * hh + 64 * (((j >> 1) + 1 + (A)) & 3))
    if (pw == 0) {
      if (lane == 0) {
#pragma unroll
        for (int c = 3; c < 9; c++) tma2d(sb + SM_XN + c * 16384, &prm.xm, bar + 8 * (B_X + c), 64 * c, 128 * m);
        STAMPW(21);
        uint64_t pol;
        asm volatile("createpolicy.fractional.L2::evict_first.b64 %0, 1.0;" : "=l"(pol));
#pragma unroll 1
        for (int kb = 0; kb < 9; kb++) {
          const int s = kb % 3;
          if (kb >= 3) mbar_wait(bar + 8 * (B_QE + s), (kb / 3 - 1) & 1);
          const uint32_t fb = bar + 8 * (B_QF + s), dst = sb + SM_RING + s * QST;
          mbar_expect(fb, QST);
#pragma unroll
          for (int p = 0; p < 3; p++) {
            tma2d(dst + p * 8192, &prm.wqkv64, fb, 576 * p + 72 * j + 8 * hh, 64 * kb);
            tma2d(dst + 24576 + p * 1024, &prm.wqkv8, fb, 576 * p + 72 * j + 64 - 64 * hh, 64 * kb);
          }
        }
        asm volatile("st.shared.u32 [%0], %1;" ::"r"(sb + SM_TAG), "r"((epoch + 1) & 1) : "memory");
        int col = 576 * j, kr = 0;
#pragma unroll 1
        for (int s = 0; s < 81; s++) {
          const int slot = s & 3;
          if (s >= 4) mbar_wait(bar + 8 * (B_BE + slot), ((s >> 2) - 1) & 1);
          else if (s != 2) mbar_wait(bar + 8 * (B_QE + (s == 3 ? 2 : s)), 0);
          const uint32_t fb = bar + 8 * (B_BF + slot), dst = sb + SM_RING + slot * BST;
          mbar_expect(fb, BST);
          tma2d_h(dst, &prm.wg, fb, col, kr, pol);
          tma2d_h(dst + 8192, &prm.wu, fb, col, kr, pol);
          if ((kr += 64) == 576) { kr = 0; col += 64; }
        }
        mbar_arrive(bar + 8 * (B_BF + 1));
        uint32_t seen = flag_wait_v(FLAG_H(cta), 9 * epoch + 1) - 9 * epoch;
        fence_async();
#pragma unroll 1
        for (int b = 0; b < 26; b++) {
          const int st = b & 3;
          if (b >= 4) mbar_wait(bar + 8 * (B_GE + st), ((b >> 2) - 1) & 1);
          else if (b) mbar_wait(bar + 8 * (B_BE + (b == 1 ? 1 : b == 2 ? 3 : 0)), b != 3);
          const uint32_t fb = bar + 8 * (B_GF + st), dst = sb + st * G2ST;
          if (b == 0) STAMPW(16);
          mbar_expect(fb, G2ST);
          if (b < 24) {
            const int jj = (b < 10 || b == 20 || b == 21) ? j : (j ^ 1), lb = b < 10 ? b : b < 20 ? b - 10 : 10 + (b & 1);
            bulk_g2s(dst, g_H + (m * 576 + 72 * jj + 6 * lb) * 512, 12288, fb);
#pragma unroll
            for (int a = 0; a < 4; a++) tma5d(dst + 12288 + a * 6144, &prm.wd[0], fb, ACOL(a), 36 * jj + 3 * lb);
            tma5d(dst + 36864, &prm.wd[1 + hh], fb, 0, 36 * jj + 3 * lb);
          } else {
            const int r = b - 24;
            bulk_g2s(dst, g_O + ((cta & ~1) + r) * 9 * 512 + r * 1024, 12288, fb);
#pragma unroll
            for (int a = 0; a < 4; a++) tma3d(dst + 12288 + a * 6144, &prm.wo3[0], fb, ACOL(a), 4 * (j & 6) + 5 * r);
            tma3d(dst + 36864, &prm.wo3[1 + hh], fb, 0, 4 * (j & 6) + 5 * r);
          }
          if (b == 0) STAMPW(17);
          if (b < 23) {
            const int n = b + 1, lb = n < 10 ? n : n < 20 ? n - 10 : 10 + (n & 1), need = (3 * lb + 6) >> 2;
            if (n == 10 || n == 20 || n == 22) seen = 0;
            if (seen < need) { seen = flag_wait_v(FLAG_H((n < 10 || n == 20 || n == 21) ? cta : (cta ^ 1)), 9 * epoch + need) - 9 * epoch; fence_async(); }
          } else if (b == 23) { flag_wait(FLAG_O(cta), epoch + 1); flag_wait(FLAG_O(cta ^ 1), epoch + 1); fence_async(); }
        }
        mbar_wait(bar + 8 * (B_GE + 1), 0);
        mbar_expect(bar + 8 * B_OL, 49152 + 32768);
        tma2d(sb + SM_RES, &prm.xm, bar + 8 * B_OL, ACOL(3), 128 * m);
        tma2d(sb + SM_RES + 16384, &prm.xm, bar + 8 * B_OL, 256 + 32 * hh, 128 * m);
#pragma unroll 1
        for (int i = 0; i < 4; i++) {
          tma3d(sb + SM_LB + i * 4096, &prm.wo2[0], bar + 8 * B_OL, ACOL(3), 8 * i + 3);
          tma3d(sb + SM_LB + 24576 + i * 4096, &prm.wo2[1 + hh], bar + 8 * B_OL, 0, 8 * i + 3);
          tma3d(sb + SM_LB + 16384 + i * 2048, &prm.wo16[0], bar + 8 * B_OL, ACOL(3), 8 * i);
          tma3d(sb + SM_LB + 40960 + i * 2048, &prm.wo16[1 + hh], bar + 8 * B_OL, 0, 8 * i);
          __nanosleep(200);
        }
      }
    } else if (pw == 1) {
      if (lane == 0) {
        flag_wait(FLAG_KV(0, j), 16 * epoch + 16);
        STAMPW(29);
        fence_async();
        STAMPW(18);
        int slot = 0, ph = 1, vrow = 0;
        const int hx = (j & 1) * 3;
#pragma unroll 1
        for (int u = 0; u <= 128; u++) {
          if (u >= 3) mbar_wait(bar + 8 * (B_KE + slot), ph);
          const uint32_t fb = bar + 8 * (B_KF + slot), dst = sb + SM_KV + slot * KVST;
          const int krow = (4 * j + ((u >> 5) ^ hx)) * 256 + ((u + 2 * m) & 31) * 8;
          if (u == 0) vrow = krow;
          mbar_expect(fb, u < 128 ? KVST : KVST / 2);
          if (u < 128) tma2d(dst, &prm.kv, fb, 0, krow);
          tma2d(dst + 3072, &prm.kv, fb, 128, vrow);
          vrow = krow;
          if (++slot == 3) { slot = 0; ph ^= 1; }
          if (u == 16) { flag_wait(FLAG_KV(1, j), 16 * epoch + 16); fence_async(); }
        }
      }
    } else if (pw == 2) {
      if (lane == 0) {
#pragma unroll 1
        for (int i = 1; i < 18; i++) asm volatile("prefetch.tensormap [%0];" ::"l"(&prm.xm + i) : "memory");
        mbar_wait(bar + 8 * B_SK1, 0);
        STAMPW(22);
        fence_gpu(); flag_add(FLAG_KV(0, j));
        STAMPW(20);
        mbar_wait(bar + 8 * B_SK2, 0);
        fence_gpu(); flag_add(FLAG_KV(1, j));
#pragma unroll 1
        for (int t = 0; t < 9; t++) { mbar_wait(bar + 8 * B_SH, t & 1); if (EXP_DELAY) __nanosleep(EXP_DELAY); fence_gpu(); flag_add(FLAG_H(cta)); }
        mbar_wait(bar + 8 * B_SO1, 0);
        fence_gpu(); flag_add(FLAG_O(cta));
      }
    } else {
      mbar_wait(bar + 8 * (B_X + PF_Q), 0);
#pragma unroll 1
      for (int i = lane; i < 122; i += 32) pf_line(prm.pwqkv + (size_t)min(i * 128 + cta, 15551) * 64);
      mbar_wait(bar + 8 * (B_QE + PF_G1), 0);
#pragma unroll 1
      for (int t = -3; t < 9; t++) {
        if (t >= 0) { mbar_wait(bar + 8 * B_SH, t & 1); if (EXP_PFD) __nanosleep(EXP_PFD); }
        if (t < 6) {
#pragma unroll 1
          for (int i = lane; i < 72; i += 32) pf_line((i >= 36 ? prm.pwu : prm.pwg) + (size_t)(36 * m + (i >= 36 ? i - 36 : i)) * FF + 576 * j + 64 * (t + 3));
        }
        if (t >= 5) {
#pragma unroll 1
          for (int i = lane; i < 81; i += 32) {
            const int l = (2 * m + hh) * 81 + i, r = l / 9;
            pf_line(prm.pwd + (size_t)(1152 * (j >> 1) + 576 * (r / 144) + 144 * (t - 5) + r % 144) * DM + 64 * (l % 9));
          }
        }
      }
      if (cta * 41 + lane < 5184) pf_line(prm.pwo + (size_t)(cta * 41 + lane) * 64);
      if (lane < 9 && cta * 41 + 32 + lane < 5184) pf_line(prm.pwo + (size_t)(cta * 41 + 32 + lane) * 64);
      if (lane == 0) {
      mbar_wait(bar + 8 * B_SP, 0);
      const int q = j >> 1;
#pragma unroll 1
      for (int i = 0; i < 15; i++) {
        const int a = i / 5, p = i % 5, d = (q + 1 + a) & 3;
        bulk_s2g(g_P + ((m * 8 + 2 * d + hh) * 3 + a) * 1152 + p * 256, p < 4 ? sb + SM_SEND + a * 16384 + p * 4096 : sb + SM_SEND + 49152 + d * 2048, p < 4 ? 4096 : 2048);
        asm volatile("cp.async.bulk.commit_group;\ncp.async.bulk.wait_group.read 1;" ::: "memory");
      }
      asm volatile("cp.async.bulk.wait_group 0;" ::: "memory");
      fence_gpu();
#pragma unroll 1
      for (int a = 0; a < 3; a++) flag_add(FLAG_P(m * 8 + 2 * ((q + 1 + a) & 3) + hh));
      STAMPW(15);
      flag_wait(FLAG_P(cta), 3 * epoch + 3);
      fence_async();
      STAMPW(25);
      mbar_expect(bar + 8 * B_RX, 55296);
#pragma unroll 1
      for (int i = 0; i < 9; i++) { bulk_g2s(sb + SM_RECV + i * 6144, g_P + cta * 3 * 1152 + i * 384, 6144, bar + 8 * B_RX); __nanosleep(64); }
      *FLAG_EPOCH(cta) = epoch + 1;
      }
    }
  } else {
    const int tid = threadIdx.x;
    const int t = lane & 3;
    const uint32_t l0 = lane == 0;
    const uint32_t adesc = (((sb + SM_XN + wg * 8192) & 0x3FFFF) >> 4) | LO_A;
    const uint32_t bdesc = (((sb + SM_RING) & 0x3FFFF) >> 4) | LO_B;
    const uint32_t kdesc0 = (((sb + SM_KV) & 0x3FFFF) >> 4) | LO_K;
    const int hx = (j & 1) * 3;
    float accA[64], accB[64];
    Att a;
    uint32_t gs = 0;
#define G1_ISSUE(ACC, AD, BD) _Pragma("unroll") for (int k = 0; k < 4; k++) wg_ss_n128<HI_SW128, HI_SW128>(ACC, (AD) + k * 2, (BD) + k * 128);
#define G1_ISSUE_Z(ACC, BD)                                                                                    \
  wg_ss_z_n128<HI_SW128, HI_SW128>(ACC, adesc, BD);                                                            \
  _Pragma("unroll") for (int k = 1; k < 4; k++) wg_ss_n128<HI_SW128, HI_SW128>(ACC, adesc + k * 2, (BD) + k * 128);
#define BF_BAR (bar + 8 * B_BF + 8 * (gs & 3))
#define BF_PH ((gs >> 2) & 1)
#define G1_ONLY() { mbar_wait(BF_BAR, BF_PH); wg_fence(); G1_ISSUE(accA, adesc + gs * 1024, bdesc + (gs & 3) * 1024) wg_commit(); wg_wait<1>(); \
                    mbar_arrive_if(bar + 8 * B_BE + 8 * ((gs - 1) & 3), l0); gs++; }
    {
      const int lr = wr * 16 + (lane & 15);
      uint32_t ra[4];
#pragma unroll
      for (int k = 0; k < 4; k++) ra[k] = sb + SM_XN + lr * 128 + (((2 * k + (lane >> 4)) ^ (lr & 7)) << 4);
      STAMP(26);
      float cs[2][4] = {}, q0 = 0.f, q1 = 0.f, q2 = 0.f, q3 = 0.f;
#pragma unroll 1
      for (int c = 0; c < 9; c++) {
        mbar_wait(bar + 8 * (B_X + c), 0);
        if (c == 0) STAMP(27);
        if (c == 8) STAMP(28);
        uint32_t v[4][4];
#pragma unroll
        for (int k = 0; k < 4; k++) ldsm4(v[k], ra[k] + c * 16384);
#pragma unroll
        for (int k = 0; k < 4; k++) {
          mma_ones(cs[k & 1], v[k]);
#pragma unroll
          for (int e = 0; e < 4; e += 2) {
            const float x0 = bf_lo(v[k][e]), x1 = bf_hi(v[k][e]), y0 = bf_lo(v[k][e + 1]), y1 = bf_hi(v[k][e + 1]);
            q0 = fmaf(x0, x0, q0); q1 = fmaf(x1, x1, q1); q2 = fmaf(y0, y0, q2); q3 = fmaf(y1, y1, q3);
          }
        }
      }
      STAMP(11);
      asm volatile("setmaxnreg.inc.sync.aligned.u32 240;");
      const float mean0 = (cs[0][0] + cs[1][0]) * (1.f / 576.f), mean1 = (cs[0][2] + cs[1][2]) * (1.f / 576.f);
      q0 += q1; q2 += q3;
      q0 += __shfl_xor_sync(0xffffffffu, q0, 1); q2 += __shfl_xor_sync(0xffffffffu, q2, 1);
      q0 += __shfl_xor_sync(0xffffffffu, q0, 2); q2 += __shfl_xor_sync(0xffffffffu, q2, 2);
      float var0 = fmaf(q0, 1.f / 576.f, -mean0 * mean0), var1 = fmaf(q2, 1.f / 576.f, -mean1 * mean1);
      if (__any_sync(0xffffffffu, !(mean0 * mean0 <= 8.f * var0) || !(mean1 * mean1 <= 8.f * var1))) {
        q0 = q2 = 0.f;
#pragma unroll 1
        for (int i = 0; i < 36; i++) {
          uint32_t v[4];
          ldsm4(v, ((ra[0] + (i >> 2) * 16384) ^ ((i & 3) << 5)));
#pragma unroll
          for (int e = 0; e < 4; e += 2) {
            const float x0 = bf_lo(v[e]) - mean0, x1 = bf_hi(v[e]) - mean0, y0 = bf_lo(v[e + 1]) - mean1, y1 = bf_hi(v[e + 1]) - mean1;
            q0 = fmaf(x0, x0, fmaf(x1, x1, q0)); q2 = fmaf(y0, y0, fmaf(y1, y1, q2));
          }
        }
        q0 += __shfl_xor_sync(0xffffffffu, q0, 1); q2 += __shfl_xor_sync(0xffffffffu, q2, 1);
        q0 += __shfl_xor_sync(0xffffffffu, q0, 2); q2 += __shfl_xor_sync(0xffffffffu, q2, 2);
        var0 = q0 * (1.f / 576.f); var1 = q2 * (1.f / 576.f);
      }
      const float inv0 = rcp_fast(bf_round(sqrt_fast(bf_round(bf_round(var0) + 1e-5f)))), inv1 = rcp_fast(bf_round(sqrt_fast(bf_round(bf_round(var1) + 1e-5f))));
      const uint32_t mb0 = pack(mean0, mean0), mb1 = pack(mean1, mean1);
      const uint32_t h0 = pack(inv0, inv0), h1 = pack(inv1, inv1);
      const uint32_t e0 = pack(inv0 - bf_lo(h0), inv0 - bf_lo(h0)), e1 = pack(inv1 - bf_lo(h1), inv1 - bf_lo(h1));
#define NORM_STORE(C)                                                                                          \
  {                                                                                                            \
    _Pragma("unroll") for (int k = 0; k < 4; k++)                                                              \
      stsm4(ra[k] + (C) * 16384, bscale2(bsub2(v[k][0], mb0), h0, e0), bscale2(bsub2(v[k][1], mb1), h1, e1),   \
            bscale2(bsub2(v[k][2], mb0), h0, e0), bscale2(bsub2(v[k][3], mb1), h1, e1));                       \
    asm volatile("fence.proxy.async.shared::cta;" ::: "memory");                                               \
    __syncwarp();                                                                                              \
    mbar_arrive_if(bar + 8 * B_NR + 8 * wg, l0);                                                               \
  }
      float aq[96], ar[12];
      {
        uint32_t v[4][4];
#pragma unroll
        for (int k = 0; k < 4; k++) ldsm4(v[k], ra[k]);
        NORM_STORE(0)
      }
#pragma unroll
      for (int i = 0; i < 96; i++) aq[i] = 0.f;
#pragma unroll
      for (int i = 0; i < 12; i++) ar[i] = 0.f;
      pin<96>(aq); pin<12>(ar);
      STAMP(1);
      const uint32_t rdesc = (((sb + SM_RING + 24576) & 0x3FFFF) >> 4) | LO_R;
      uint32_t s = 0, ph = 0;
#pragma unroll 1
      for (int kb = 0; kb < 9; kb++) {
        uint32_t v[4][4];
        const int cn = kb < 8 ? kb + 1 : 8;
#pragma unroll
        for (int k = 0; k < 4; k++) ldsm4(v[k], ra[k] + cn * 16384);
        mbar_wait(bar + 8 * B_QF + 8 * s, ph);
        mbar_wait(bar + 8 * B_NR + 8 * wg, kb & 1);
        wg_fence();
#pragma unroll
        for (int k = 0; k < 4; k++) {
          wg_ss_n192<HI_SW128, HI_SW128>(aq, adesc + kb * 1024 + k * 2, bdesc + s * (QST >> 4) + k * 128);
          wg_ss_n24<HI_SW128, HI_R>(ar, adesc + kb * 1024 + k * 2, rdesc + s * (QST >> 4) + k * 16);
        }
        wg_commit();
        if (kb < 8) NORM_STORE(cn)
        wg_wait<1>();
        mbar_arrive_if(bar + 8 * B_QE + (s == 0 ? 16 : 8 * s - 8), l0 & (kb > 0));
        if (++s == 3) { s = 0; ph ^= 1; }
      }
      wg_wait<0>();
      pin<96>(aq); pin<12>(ar);
      mbar_arrive_if(bar + 8 * (B_QE + 2), l0);
      STAMP(2);
      uint32_t* kvp = g_KV + (size_t)(4 * j) * SEQ * 20 + (16 * m + 2 * wr) * 160 + lane;
      uint32_t pk[2][9][2];
#pragma unroll
      for (int p = 0; p < 2; p++)
#pragma unroll
        for (int i = 0; i < 9; i++) {
          const float* src = i < 8 ? &aq[(8 * (p + 1) + i) * 4] : &ar[4 * (p + 1)];
          pk[p][i][0] = pack(src[0], src[1]); pk[p][i][1] = pack(src[2], src[3]);
        }
      if (hx) {
#pragma unroll
        for (int p = 0; p < 2; p++) { rotate9(pk[p]); }
        store_kv_head<3>(pk, kvp, lane);
      } else store_kv_head<0>(pk, kvp, lane);
      __syncwarp();
      mbar_arrive_if(bar + 8 * B_SK1, l0);
      STAMP(3);
      mbar_wait(bar + 8 * B_BF, 0);
      wg_fence();
      G1_ISSUE_Z(accA, bdesc)
      wg_commit();
      gs = 1;
      uint32_t pq[9][2];
#pragma unroll
      for (int i = 0; i < 9; i++) {
        const float* src = i < 8 ? &aq[i * 4] : &ar[0];
        pq[i][0] = pack(bf_round(src[0]) * QSCALE, bf_round(src[1]) * QSCALE); pq[i][1] = pack(bf_round(src[2]) * QSCALE, bf_round(src[3]) * QSCALE);
      }
      if (hx) rotate9(pq);
      pin<18>(&pq[0][0]);
#pragma unroll 1
      while (gs < 3) G1_ONLY()
      if (hx) store_kv_head<0>(pk, kvp, lane); else store_kv_head<3>(pk, kvp, lane);
      store_kv_head<1>(pk, kvp, lane);
      store_kv_head<2>(pk, kvp, lane);
      __syncwarp();
      mbar_arrive_if(bar + 8 * B_SK2, l0);
      G1_ONLY()
      uint4* qp = reinterpret_cast<uint4*>(g_Q) + cta * 4 * 512 + tid;
#pragma unroll
      for (int hp = 0; hp < 4; hp++) {
        const bool up = t < hp;
        const uint4 u = make_uint4(up ? pq[2 * hp + 1][0] : pq[2 * hp][0], up ? pq[2 * hp + 1][1] : pq[2 * hp][1],
                                   up ? pq[2 * hp + 2][0] : pq[2 * hp + 1][0], up ? pq[2 * hp + 2][1] : pq[2 * hp + 1][1]);
        const uint4 v = make_uint4(t == hp ? pq[2 * hp + 2][0] : 0u, t == hp ? pq[2 * hp + 2][1] : 0u, 0u, 0u);
        qp[hp * 512] = u; qp[hp * 512 + 256] = v;
        if (hp == 0 || (hp == 3 && hx)) { a.q[0] = u.x; a.q[1] = u.y; a.q[2] = u.z; a.q[3] = u.w; a.q[4] = v.x; a.q[5] = v.y; }
      }
      a.q[6] = __shfl_sync(0xffffffffu, lane, 0); a.q[7] = __shfl_sync(0xffffffffu, lane >> 1, 1);
#pragma unroll
      for (int i = 0; i < 16; i++) a.p[i] = 0;
#pragma unroll
      for (int i = 0; i < 12; i++) a.o[i] = 0.f;
      pin<16>(a.p); pin<12>(a.o); pin<8>(a.q);
    }
    static_assert(NG0 == 5, "slot / item alignment below assumes NG0 == 5");
    G1_ONLY()
    STAMP(4);
    mbar_wait(BF_BAR, BF_PH);
    mbar_wait(bar + 8 * B_KF, 0);
    STAMP(23);
    uint32_t k8 = 0, kph = 0, kd = kdesc0;
    uint32_t it = 0;
    uint32_t ox0 = 0, ox1 = 0;
    bool special = true;
    uint32_t qn[6] = {0, 0, 0, 0, 0, 0};
    uint32_t* hdst = g_H + ((m * 576 + 72 * j + (t >> 1)) * 128 + 16 * wr + (lane >> 2)) * 4 + 2 * (t & 1);
    uint32_t ad = adesc + NG0 * 1024, bd = bdesc + (gs & 3) * 1024;

#define ITEM_FIRST()                                                                                           \
  {                                                                                                            \
    pin<12>(a.o);                                                                                              \
    if (it != 0) {                                                                                             \
      uint32_t w[4];                                                                                           \
      o_normalise(a.o, w, ox0, ox1, ((it >> 5) - 1) ^ hx, lane, sb + SM_BAD, wr);                              \
      uint32_t* d = g_O + cta * 9 * 512 + (((it >> 5) - 1) ^ hx) * 1024 + wr * 64 + lane;                      \
      d[0] = w[0]; d[32] = w[1]; d[512] = w[2]; d[544] = w[3];                                                 \
    }                                                                                                          \
    if (it == 96) mbar_arrive_if(bar + 8 * B_SO1, l0 & (bad_heads(sb + SM_BAD, wr) == 0));                     \
    first_tile(a, (it >> 5) ^ hx, lane);                                                                       \
  }
#define ITEM_NEXTQ() { if (it & 2) { _Pragma("unroll") for (int i = 0; i < 6; i++) a.q[i] = qn[i]; } else fetch_q(qn, cta, ((it >> 5) + 1) ^ hx, tid); }
#define KV_ADVANCE() { kd += 384; k8 += 8; if (k8 == 24) { k8 = 0; kd = kdesc0; kph ^= 1; } it++; special = ((it + 3) & 31) < 4; }
#define WAIT_UNLESS(OK, BA, PA, BB, PB) if (__builtin_expect(!__all_sync(0xffffffffu, OK), 0)) { mbar_wait(BA, PA); mbar_wait(BB, PB); }
#define EPI_STEP(ACCN, ACCO)                                                                                   \
  {                                                                                                            \
    wg_fence();                                                                                                \
    G1_ISSUE_Z(ACCN, bd)                                                                                       \
    wg_commit();                                                                                               \
    wg_wait<1>();                                                                                              \
    pin<64>(ACCO);                                                                                             \
    mbar_arrive_if(bar + 8 * B_BE + 8 * ((gs - 1) & 3), l0);                                                   \
    gs++;                                                                                                      \
    ad = adesc + 1024; bd = bdesc + (gs & 3) * 1024;                                                           \
    const uint32_t ok = mbar_test(BF_BAR, BF_PH);                                                              \
    h_epilogue(ACCO, hdst);                                                                                    \
    hdst += 4096;                                                                                              \
    __syncwarp();                                                                                              \
    mbar_arrive_if(bar + 8 * B_SH, l0);                                                                        \
    WAIT_UNLESS(ok, BF_BAR, BF_PH, BF_BAR, BF_PH)                                                              \
  }
#define ATT_LOOP1(ACC, ITEMS)                                                                                  \
  do {                                                                                                         \
    wg_fence();                                                                                                \
    issue_att(a, kd);                                                                                          \
    wg_commit();                                                                                               \
    G1_ISSUE(ACC, ad, bd)                                                                                      \
    wg_commit();                                                                                               \
    wg_wait<1>();                                                                                              \
    pin<32>(a.s);                                                                                              \
    mbar_arrive_if(bar + 8 * B_BE + 8 * ((gs - 1) & 3), l0);                                                   \
    mbar_arrive_if(bar + 8 * B_KE + k8, l0);                                                                   \
    TRACE()                                                                                                    \
    if (ITEMS) { if (__builtin_expect(special, 0)) { if (it & 1) ITEM_NEXTQ() else if (!(it & 2)) ITEM_FIRST() } } \
    else __syncwarp();                                                                                         \
    gs++;                                                                                                      \
    KV_ADVANCE()                                                                                               \
    ad += 1024; bd = bdesc + (gs & 3) * 1024;                                                                  \
    const uint32_t ok = mbar_test(BF_BAR, BF_PH) & mbar_test(bar + 8 * B_KF + k8, kph);                        \
    softmax_a(a);                                                                                              \
    WAIT_UNLESS(ok, BF_BAR, BF_PH, bar + 8 * B_KF + k8, kph)                                                   \
    softmax_b(a);                                                                                              \
    pin<8>(a.q);                                                                                               \
  } while (ad != adesc + 9 * 1024);
#pragma unroll 1
    for (int pr = 0;; pr++) {
      ATT_LOOP1(accA, true)
      if (pr == 4) break;
      EPI_STEP(accB, accA)
      ATT_LOOP1(accB, false)
      EPI_STEP(accA, accB)
    }
    STAMP(5);
    fetch_q(qn, cta, 3 ^ hx, tid);
    wg_wait<0>();
    pin<64>(accA);
    mbar_arrive_if(bar + 8 * B_BE, l0);
    h_epilogue(accA, hdst);
    __syncwarp();
    mbar_arrive_if(bar + 8 * B_SH, l0);
    mbar_wait(bar + 8 * (B_BE + 3), 1);
    asm volatile("st.shared.v4.b32 [%0], {%1,%2,%3,%4};\nst.shared.v2.b32 [%5], {%6,%7};" ::"r"(sb + SM_QS + tid * 16), "r"(qn[0]), "r"(qn[1]), "r"(qn[2]), "r"(qn[3]),
                 "r"(sb + SM_QS + 4096 + tid * 8), "r"(qn[4]), "r"(qn[5]) : "memory");
    STAMP(6);
    mbar_wait(bar + 8 * B_GF, 0);
    STAMP(12);

    float acc2[144];
    const uint32_t a2desc = (((sb + wg * 1024) & 0x3FFFF) >> 4) | LO_O;
    const uint32_t b2desc = (((sb + 12288) & 0x3FFFF) >> 4) | LO_B48;
    uint32_t gb = 0;
    ad = a2desc; bd = b2desc;
#define G2_LO(K) wg_ss_n128<HI_O, HI_SW128>(acc2, ad + (K) * 256, bd + (K) * 128);
#define G2_HI(K) wg_ss_n160<HI_O, HI_SW128>(acc2 + 64, ad + (K) * 256, bd + (K) * 128 + 768);
#define ATT_PAIR(ZERO)                                                                                         \
  {                                                                                                            \
    wg_fence();                                                                                                \
    issue_att(a, kd);                                                                                          \
    wg_commit();                                                                                               \
    if (ZERO) { wg_ss_z_n128<HI_O, HI_SW128>(acc2, ad, bd); wg_ss_z_n160<HI_O, HI_SW128>(acc2 + 64, ad, bd + 768); } \
    else { G2_LO(0) G2_HI(0) }                                                                                 \
    G2_LO(1)                                                                                                   \
    wg_commit();                                                                                               \
    wg_wait<1>();                                                                                              \
    pin<32>(a.s);                                                                                              \
    mbar_arrive_if(bar + 8 * B_KE + k8, l0);                                                                   \
    if (!(ZERO)) mbar_arrive_if(bar + 8 * B_GE + 8 * ((gb - 1) & 3), l0);                                      \
    TRACE()                                                                                                    \
    if (!(ZERO)) { if (__builtin_expect(it == 96, 0)) ITEM_FIRST() }                                           \
    KV_ADVANCE()                                                                                               \
    uint32_t ok = mbar_test(bar + 8 * B_KF + k8, kph);                                                         \
    softmax_a(a);                                                                                              \
    WAIT_UNLESS(ok, bar + 8 * B_KF + k8, kph, bar + 8 * B_KF + k8, kph)                                        \
    softmax_b(a);                                                                                              \
    pin<8>(a.q);                                                                                               \
    wg_fence();                                                                                                \
    issue_att(a, kd);                                                                                          \
    wg_commit();                                                                                               \
    G2_HI(1) G2_LO(2) G2_HI(2)                                                                                 \
    wg_commit();                                                                                               \
    wg_wait<1>();                                                                                              \
    pin<32>(a.s);                                                                                              \
    mbar_arrive_if(bar + 8 * B_KE + k8, l0);                                                                   \
    TRACE()                                                                                                    \
    if (!(ZERO) && __builtin_expect(it == 95, 0)) {                                                            \
      const int ft = fresh_tid();                                                                              \
      asm volatile("ld.shared.v4.b32 {%0,%1,%2,%3}, [%6];\nld.shared.v2.b32 {%4,%5}, [%7];" : "=r"(a.q[0]), "=r"(a.q[1]), "=r"(a.q[2]), "=r"(a.q[3]), \
                   "=r"(a.q[4]), "=r"(a.q[5]) : "r"(sb + SM_QS + ft * 16), "r"(sb + SM_QS + 4096 + ft * 8) : "memory"); \
    }                                                                                                          \
    KV_ADVANCE()                                                                                               \
    gb++;                                                                                                      \
    ad = a2desc + (gb & 3) * 2688; bd = b2desc + (gb & 3) * 2688;                                              \
         \
    const uint32_t nb = gb == 26 ? bar + 8 * (B_GE + 3) : bar + 8 * B_GF + 8 * (gb & 3), np = gb == 26 ? 1 : (gb >> 2) & 1; \
    ok = mbar_test(nb, np) & mbar_test(bar + 8 * B_KF + k8, kph);                                              \
    softmax_a(a);                                                                                              \
    WAIT_UNLESS(ok, nb, np, bar + 8 * B_KF + k8, kph)                                                          \
    softmax_b(a);                                                                                              \
    pin<8>(a.q);                                                                                               \
    if (!(ZERO) && __builtin_expect(gb == 23, 0)) {      \
      const uint32_t bad = bad_heads(sb + SM_BAD, wr);                                                         \
      if (bad) { repair_rows(cta, wr, bad, 3 ^ hx, false); mbar_arrive_if(bar + 8 * B_SO1, l0); }              \
    }                                                                                                          \
  }
    ATT_PAIR(true)
    do ATT_PAIR(false) while (gb != 26);
    STAMP(13);
#define ATT_ONLY()                                                                                             \
  {                                                                                                            \
    wg_fence();                                                                                                \
    issue_att(a, kd);                                                                                          \
    wg_commit();                                                                                               \
    wg_wait<0>();                                                                                              \
    pin<32>(a.s);                                                                                              \
    mbar_arrive_if(bar + 8 * B_KE + k8, l0);                                                                   \
    TRACE()                                                                                                    \
    KV_ADVANCE()                                                                                               \
    const uint32_t ok = mbar_test(bar + 8 * B_KF + k8, kph);                                                   \
    softmax_a(a);                                                                                              \
    WAIT_UNLESS(ok, bar + 8 * B_KF + k8, kph, bar + 8 * B_KF + k8, kph)                                        \
    softmax_b(a);                                                                                              \
  }
    float fin[48];
    wg_wait<0>(); pin<144>(acc2); mbar_arrive_if(bar + 8 * (B_GE + 1), l0);
    stage_partials(acc2, sb + SM_SEND, fresh_tid());
    asm volatile("fence.proxy.async.shared::cta;" ::: "memory");
    __syncwarp();
    mbar_arrive_if(bar + 8 * B_SP, l0);
    do ATT_ONLY() while (it != 128);
    STAMP(7);
    wg_fence();
    issue_pv(a, kd);
    wg_commit();
    int tid2, bid2;
    asm volatile("mov.u32 %0, %%tid.x;" : "=r"(tid2));
    asm volatile("mov.u32 %0, %%ctaid.x;" : "=r"(bid2));
    const int m2 = bid2 & 15, j2 = bid2 >> 4;
    uint32_t tag;
    asm volatile("ld.shared.u32 %0, [%1];" : "=r"(tag) : "r"(sb + SM_TAG) : "memory");
    wg_wait<0>();
    pin<12>(a.o);
    {
      uint32_t w[4];
      o_normalise(a.o, w, ox0, ox1, 3 ^ hx, lane, sb + SM_BAD, wr);
      ox0 = __shfl_xor_sync(0xffffffffu, ox0, 2); ox1 = __shfl_xor_sync(0xffffffffu, ox1, 2);
      const uint32_t bad = bad_heads(sb + SM_BAD, wr);
      if (bad) {
        uint32_t* d = g_O + cta * 9 * 512 + wr * 64 + lane;
        uint32_t* h = d + (3 ^ hx) * 1024;
        h[0] = w[0]; h[32] = w[1]; h[512] = w[2]; h[544] = w[3]; d[4096] = ox0; d[4128] = ox1;
        __syncwarp();
        repair_rows(cta, wr, bad, 3 ^ hx, true);
        w[0] = __ldcg(h); w[1] = __ldcg(h + 32); w[2] = __ldcg(h + 512); w[3] = __ldcg(h + 544); ox0 = __ldcg(d + 4096); ox1 = __ldcg(d + 4128);
      }
      asm volatile("st.relaxed.gpu.global.v4.b32 [%0], {%1,%2,%3,%4};" ::"l"(g_L + (m2 * 8 + j2) * 384 + tid2), "r"((w[0] & ~1u) | tag), "r"((w[1] & ~1u) | tag),
                   "r"((w[2] & ~1u) | tag), "r"((w[3] & ~1u) | tag) : "memory");
      asm volatile("st.relaxed.gpu.global.v2.b32 [%0], {%1,%2};" ::"l"(reinterpret_cast<uint2*>(g_L + (m2 * 8 + j2) * 384 + 256) + tid2), "r"((ox0 & ~1u) | tag),
                   "r"((ox1 & ~1u) | tag) : "memory");
    }
    STAMP(8);
    uint32_t la[48];
    for (uint32_t tries = 0;; tries++) {
      const uint4* p4 = g_L + m2 * 8 * 384 + tid2;
      const uint2* p2 = reinterpret_cast<const uint2*>(g_L + m2 * 8 * 384 + 256) + tid2;
      uint32_t bad = 0;
#pragma unroll
      for (int c = 0; c < 8; c++)
        asm volatile("ld.relaxed.gpu.global.v2.b32 {%0,%1}, [%2];" : "=r"(la[32 + 2 * c]), "=r"(la[33 + 2 * c]) : "l"(p2 + c * 768) : "memory");
#pragma unroll
      for (int i = 32; i < 48; i++) { la[i] ^= tag; bad |= la[i]; }
      if (__all_sync(0xffffffffu, !(bad & 1))) {
#pragma unroll
        for (int c = 0; c < 8; c++)
          asm volatile("ld.relaxed.gpu.global.v4.b32 {%0,%1,%2,%3}, [%4];" : "=r"(la[4 * c]), "=r"(la[4 * c + 1]), "=r"(la[4 * c + 2]), "=r"(la[4 * c + 3]) : "l"(p4 + c * 384) : "memory");
#pragma unroll
        for (int i = 0; i < 32; i++) { la[i] ^= tag; bad |= la[i]; }
        if (__all_sync(0xffffffffu, !(bad & 1))) break;
      }
      if (tries > 0x400000u) break;
    }
    pin<48>(la);
    STAMP(19);
    const uint32_t ldesc = (((sb + SM_LB) & 0x3FFFF) >> 4) | LO_BL;
    mbar_wait(bar + 8 * B_OL, 0);
    STAMP(14);
    wg_fence();
    wg_rs_z_n96<HI_SW128>(fin, la[0], la[1], la[2], la[3], ldesc);
#pragma unroll
    for (int k = 1; k < 12; k++) wg_rs_n96<HI_SW128>(fin, la[4 * k], la[4 * k + 1], la[4 * k + 2], la[4 * k + 3], ldesc + k * 128);
    wg_commit();
    uint32_t xv[18];
    load_residual(xv, sb + SM_RES, j2 >> 1, tid2);
    mbar_wait(bar + 8 * B_RX, 0);
    STAMP(24);
    wg_wait<0>();
    pin<48>(fin);
#pragma unroll
    for (int i = 0; i < 48; i++) fin[i] += acc2[96 + i];
    STAMP(9);
    final_epilogue(fin, xv, sb + SM_RECV, prm, m2, j2 & 1, j2 >> 1, tid2);
    STAMP(10);
  }
}

typedef CUresult (*EncodeFn)(CUtensorMap*, CUtensorMapDataType, cuuint32_t, void*, const cuuint64_t*, const cuuint64_t*, const cuuint32_t*, const cuuint32_t*,
                             CUtensorMapInterleave, CUtensorMapSwizzle, CUtensorMapL2promotion, CUtensorMapFloatOOBfill);

void enc2d(EncodeFn enc, CUtensorMap* tm, const void* base, uint64_t w, uint64_t h, uint64_t pitch_elems, uint32_t bw, uint32_t bh, CUtensorMapSwizzle sw) {
  cuuint64_t dims[2] = {w, h}, str[1] = {pitch_elems * 2};
  cuuint32_t box[2] = {bw, bh}, es[2] = {1, 1};
  enc(tm, CU_TENSOR_MAP_DATA_TYPE_BFLOAT16, 2, const_cast<void*>(base), dims, str, box, es, CU_TENSOR_MAP_INTERLEAVE_NONE, sw,
      CU_TENSOR_MAP_L2_PROMOTION_L2_128B, CU_TENSOR_MAP_FLOAT_OOB_FILL_NONE);
}

}

extern "C" void kernel_launch(void* const* d_in, const int* in_sizes, int n_in, void* d_out, int out_size) {
  (void)in_sizes; (void)n_in; (void)out_size;
  const __nv_bfloat16* x = (const __nv_bfloat16*)d_in[0];
  const __nv_bfloat16* wqkv = (const __nv_bfloat16*)d_in[1];
  const __nv_bfloat16* wo = (const __nv_bfloat16*)d_in[2];
  const __nv_bfloat16* wg = (const __nv_bfloat16*)d_in[4];
  const __nv_bfloat16* wu = (const __nv_bfloat16*)d_in[5];
  const __nv_bfloat16* wd = (const __nv_bfloat16*)d_in[6];
  void* fn = nullptr;
  cudaDriverEntryPointQueryResult qr;
  cudaGetDriverEntryPoint("cuTensorMapEncodeTiled", &fn, cudaEnableDefault, &qr);
  EncodeFn enc = (EncodeFn)fn;
  void* kvp = nullptr;
  cudaGetSymbolAddress(&kvp, g_KV);
  Params p;
  enc2d(enc, &p.xm, x, DM, SEQ, DM, 64, 128, CU_TENSOR_MAP_SWIZZLE_128B);
  enc2d(enc, &p.kv, kvp, 320, 32 * 256, 320, 192, 8, CU_TENSOR_MAP_SWIZZLE_NONE);
  enc2d(enc, &p.wqkv64, wqkv, 3 * DM, DM, 3 * DM, 64, 64, CU_TENSOR_MAP_SWIZZLE_128B);
  enc2d(enc, &p.wqkv8, wqkv, 3 * DM, DM, 3 * DM, 8, 64, CU_TENSOR_MAP_SWIZZLE_NONE);
  enc2d(enc, &p.wg, wg, FF, DM, FF, 64, 64, CU_TENSOR_MAP_SWIZZLE_128B);
  enc2d(enc, &p.wu, wu, FF, DM, FF, 64, 64, CU_TENSOR_MAP_SWIZZLE_128B);
  for (int v = 0; v < 3; v++) {
    const cuuint64_t wdt = v ? 32 : DM;
    const int c0 = v ? 256 + 32 * (v - 1) : 0;
    for (int e = 0; e < 3; e++) {
      cuuint64_t d3[3] = {wdt, e == 2 ? 2u : 16u, 32}, s3[2] = {DM * 2, 18 * DM * 2};
      cuuint32_t b3[3] = {64, e == 2 ? 2u : 16u, e == 0 ? 3u : e == 1 ? 2u : 8u}, e3[3] = {1, 1, 1};
      enc(e == 0 ? &p.wo3[v] : e == 1 ? &p.wo2[v] : &p.wo16[v], CU_TENSOR_MAP_DATA_TYPE_BFLOAT16, 3, (void*)(wo + c0 + (e == 2 ? 16 * DM : 0)), d3, s3, b3, e3,
          CU_TENSOR_MAP_INTERLEAVE_NONE, CU_TENSOR_MAP_SWIZZLE_128B, CU_TENSOR_MAP_L2_PROMOTION_L2_128B, CU_TENSOR_MAP_FLOAT_OOB_FILL_NONE);
    }
    cuuint64_t dims[5] = {wdt, 2, 2, 4, FF / 16}, str[4] = {DM * 2, 8 * DM * 2, 2 * DM * 2, 16 * DM * 2};
    cuuint32_t box[5] = {64, 2, 2, 4, 3}, es[5] = {1, 1, 1, 1, 1};
    enc(&p.wd[v], CU_TENSOR_MAP_DATA_TYPE_BFLOAT16, 5, (void*)(wd + c0), dims, str, box, es, CU_TENSOR_MAP_INTERLEAVE_NONE,
        CU_TENSOR_MAP_SWIZZLE_128B, CU_TENSOR_MAP_L2_PROMOTION_L2_128B, CU_TENSOR_MAP_FLOAT_OOB_FILL_NONE);
  }
  p.x = x; p.pwqkv = wqkv; p.pwo = wo; p.pwg = wg; p.pwu = wu; p.pwd = wd;
  p.out = (__nv_bfloat16*)d_out;
  cudaFuncSetAttribute(fused_kernel, cudaFuncAttributeMaxDynamicSharedMemorySize, SM_TOTAL);
  fused_kernel<<<NCTA, 384, SM_TOTAL, cudaStreamPerThread>>>(p);
}
```

```cpp
#include <cuda_runtime.h>
#include <cuda.h>
#include <cuda_bf16.h>
#include <stdint.h>

namespace {

constexpr int SEQ = 2048, DM = 576, FF = 4608;
constexpr int NCTA = 128;

constexpr uint32_t SM_XN = 0;
constexpr uint32_t SM_RING = 147456;
constexpr uint32_t SM_KV = 212992;
constexpr uint32_t QST = 27648, BST = 16384, KVST = 6144;
constexpr uint32_t G2ST = 43008;
constexpr uint32_t SM_LB = 0, SM_RES = 49152, SM_SEND = 86016, SM_RECV = SM_SEND;
constexpr uint32_t SM_QS = 204800;
constexpr uint32_t SM_ID = 231424;
constexpr uint32_t SM_BAR = 231936;
constexpr uint32_t SM_TAG = 232436;
constexpr uint32_t SM_BAD = 232432;
constexpr uint32_t SM_TOTAL = 232448;
enum { B_F = 0, B_E = 8, B_QF = 16, B_QE = 19, B_SK1 = 22, B_SK2 = 23, B_SH = 24, B_SO1 = 25, B_SP = 26, B_OL = 27, B_RX = 28, B_NR = 29, B_X = 31, B_N = 40 };
constexpr int N_G2 = 81, N_AO = 133;
#define EXP_DELAY 1000
#define EXP_PFD 1500
#define EXP_NOST 0
#define SEND_DEPTH 2
#define RX_SLEEP 0
#define EXP_NOKV 0
#define EXP_NOB 0
#define VOTE 0
#define PF_X 0
#define PF_Q 6
constexpr int PF_G1 = 1;
constexpr int NG0 = 5;

constexpr uint32_t HI_SW128 = 0x40000040u;
constexpr uint32_t LO_A = 1u << 16;
constexpr uint32_t LO_B = 512u << 16;
constexpr uint32_t HI_R = 64u, LO_R = 8u << 16;
constexpr uint32_t HI_K = 24u, LO_K = 8u << 16;
constexpr uint32_t HI_V = 8u, LO_V = 24u << 16;
constexpr uint32_t LO_B48 = 384u << 16;
constexpr uint32_t HI_O = 8u, LO_O = 128u << 16;
constexpr uint32_t HI_SW64 = 0x80000020u;

constexpr float QSCALE = 0.23570226039551584f * 1.4426950408889634f;
constexpr float MOFF = 90.f;

struct __align__(64) Params {
  CUtensorMap xm, wqkv64, wqkv8, wg, wu, kv, wd[3], wo3[3], wo2[3], wo16[3];
  const __nv_bfloat16 *x, *pwqkv, *pwo, *pwg, *pwu, *pwd;
  __nv_bfloat16* out;
};

__device__ __align__(1024) uint32_t g_H[16 * 576 * 512];
__device__ __align__(1024) uint32_t g_O[NCTA * 9 * 512];
__device__ __align__(1024) uint32_t g_KV[32 * SEQ * 20];
__device__ __align__(1024) uint32_t g_Q[NCTA * 4 * 256 * 8];
__device__ __align__(1024) uint4 g_P[NCTA * 3584];
__device__ __align__(1024) uint4 g_L[NCTA * 384];
__device__ float g_S[NCTA * 8 * SEQ];
__device__ uint32_t g_flags[16 * 32 + NCTA * 32 * 4];
#define FLAG_KV(l, j) (&g_flags[((l) * 8 + (j)) * 32])
#define FLAG_H(c) (&g_flags[16 * 32 + (c) * 32])
#define FLAG_O(c) (&g_flags[16 * 32 + NCTA * 32 + (c) * 32])
#define FLAG_P(c) (&g_flags[16 * 32 + NCTA * 64 + (c) * 32])
#define FLAG_EPOCH(c) (&g_flags[16 * 32 + NCTA * 96 + (c) * 32])
#define STAMP(i)
#define STAMPW(i)
#define TRACE()

template<uint32_t AHI, uint32_t BHI> __device__ __forceinline__ void wg_ss_n192(float* d, uint32_t a, uint32_t b) {
  asm volatile("{\n.reg .pred p;\n.reg .b64 da, db;\nsetp.ne.b32 p, 1, 0;\nmov.b64 da, {%96, %98};\nmov.b64 db, {%97, %99};\n"
    "wgmma.mma_async.sync.aligned.m64n192k16.f32.bf16.bf16 {%0, %1, %2, %3, %4, %5, %6, %7, %8, %9, %10, %11, %12, %13, %14, %15, %16, %17, %18, %19, %20, %21, %22, %23, %24, %25, %26, %27, %28, %29, %30, %31, %32, %33, %34, %35, %36, %37, %38, %39, %40, %41, %42, %43, %44, %45, %46, %47, %48, %49, %50, %51, %52, %53, %54, %55, %56, %57, %58, %59, %60, %61, %62, %63, %64, %65, %66, %67, %68, %69, %70, %71, %72, %73, %74, %75, %76, %77, %78, %79, %80, %81, %82, %83, %84, %85, %86, %87, %88, %89, %90, %91, %92, %93, %94, %95}, da, db, p, 1, 1, 0, 1;\n}\n"
    : "+f"(d[0]), "+f"(d[1]), "+f"(d[2]), "+f"(d[3]), "+f"(d[4]), "+f"(d[5]), "+f"(d[6]), "+f"(d[7]), "+f"(d[8]), "+f"(d[9]), "+f"(d[10]), "+f"(d[11]), "+f"(d[12]), "+f"(d[13]), "+f"(d[14]), "+f"(d[15]), "+f"(d[16]), "+f"(d[17]), "+f"(d[18]), "+f"(d[19]), "+f"(d[20]), "+f"(d[21]), "+f"(d[22]), "+f"(d[23]), "+f"(d[24]), "+f"(d[25]), "+f"(d[26]), "+f"(d[27]), "+f"(d[28]), "+f"(d[29]), "+f"(d[30]), "+f"(d[31]), "+f"(d[32]), "+f"(d[33]), "+f"(d[34]), "+f"(d[35]), "+f"(d[36]), "+f"(d[37]), "+f"(d[38]), "+f"(d[39]), "+f"(d[40]), "+f"(d[41]), "+f"(d[42]), "+f"(d[43]), "+f"(d[44]), "+f"(d[45]), "+f"(d[46]), "+f"(d[47]), "+f"(d[48]), "+f"(d[49]), "+f"(d[50]), "+f"(d[51]), "+f"(d[52]), "+f"(d[53]), "+f"(d[54]), "+f"(d[55]), "+f"(d[56]), "+f"(d[57]), "+f"(d[58]), "+f"(d[59]), "+f"(d[60]), "+f"(d[61]), "+f"(d[62]), "+f"(d[63]), "+f"(d[64]), "+f"(d[65]), "+f"(d[66]), "+f"(d[67]), "+f"(d[68]), "+f"(d[69]), "+f"(d[70]), "+f"(d[71]), "+f"(d[72]), "+f"(d[73]), "+f"(d[74]), "+f"(d[75]), "+f"(d[76]), "+f"(d[77]), "+f"(d[78]), "+f"(d[79]), "+f"(d[80]), "+f"(d[81]), "+f"(d[82]), "+f"(d[83]), "+f"(d[84]), "+f"(d[85]), "+f"(d[86]), "+f"(d[87]), "+f"(d[88]), "+f"(d[89]), "+f"(d[90]), "+f"(d[91]), "+f"(d[92]), "+f"(d[93]), "+f"(d[94]), "+f"(d[95])
    : "r"(a), "r"(b), "n"(AHI), "n"(BHI));
}
template<uint32_t AHI, uint32_t BHI> __device__ __forceinline__ void wg_ss_z_n192(float* d, uint32_t a, uint32_t b) {
  asm volatile("{\n.reg .pred p;\n.reg .b64 da, db;\nsetp.ne.b32 p, 0, 0;\nmov.b64 da, {%96, %98};\nmov.b64 db, {%97, %99};\n"
    "wgmma.mma_async.sync.aligned.m64n192k16.f32.bf16.bf16 {%0, %1, %2, %3, %4, %5, %6, %7, %8, %9, %10, %11, %12, %13, %14, %15, %16, %17, %18, %19, %20, %21, %22, %23, %24, %25, %26, %27, %28, %29, %30, %31, %32, %33, %34, %35, %36, %37, %38, %39, %40, %41, %42, %43, %44, %45, %46, %47, %48, %49, %50, %51, %52, %53, %54, %55, %56, %57, %58, %59, %60, %61, %62, %63, %64, %65, %66, %67, %68, %69, %70, %71, %72, %73, %74, %75, %76, %77, %78, %79, %80, %81, %82, %83, %84, %85, %86, %87, %88, %89, %90, %91, %92, %93, %94, %95}, da, db, p, 1, 1, 0, 1;\n}\n"
    : "=f"(d[0]), "=f"(d[1]), "=f"(d[2]), "=f"(d[3]), "=f"(d[4]), "=f"(d[5]), "=f"(d[6]), "=f"(d[7]), "=f"(d[8]), "=f"(d[9]), "=f"(d[10]), "=f"(d[11]), "=f"(d[12]), "=f"(d[13]), "=f"(d[14]), "=f"(d[15]), "=f"(d[16]), "=f"(d[17]), "=f"(d[18]), "=f"(d[19]), "=f"(d[20]), "=f"(d[21]), "=f"(d[22]), "=f"(d[23]), "=f"(d[24]), "=f"(d[25]), "=f"(d[26]), "=f"(d[27]), "=f"(d[28]), "=f"(d[29]), "=f"(d[30]), "=f"(d[31]), "=f"(d[32]), "=f"(d[33]), "=f"(d[34]), "=f"(d[35]), "=f"(d[36]), "=f"(d[37]), "=f"(d[38]), "=f"(d[39]), "=f"(d[40]), "=f"(d[41]), "=f"(d[42]), "=f"(d[43]), "=f"(d[44]), "=f"(d[45]), "=f"(d[46]), "=f"(d[47]), "=f"(d[48]), "=f"(d[49]), "=f"(d[50]), "=f"(d[51]), "=f"(d[52]), "=f"(d[53]), "=f"(d[54]), "=f"(d[55]), "=f"(d[56]), "=f"(d[57]), "=f"(d[58]), "=f"(d[59]), "=f"(d[60]), "=f"(d[61]), "=f"(d[62]), "=f"(d[63]), "=f"(d[64]), "=f"(d[65]), "=f"(d[66]), "=f"(d[67]), "=f"(d[68]), "=f"(d[69]), "=f"(d[70]), "=f"(d[71]), "=f"(d[72]), "=f"(d[73]), "=f"(d[74]), "=f"(d[75]), "=f"(d[76]), "=f"(d[77]), "=f"(d[78]), "=f"(d[79]), "=f"(d[80]), "=f"(d[81]), "=f"(d[82]), "=f"(d[83]), "=f"(d[84]), "=f"(d[85]), "=f"(d[86]), "=f"(d[87]), "=f"(d[88]), "=f"(d[89]), "=f"(d[90]), "=f"(d[91]), "=f"(d[92]), "=f"(d[93]), "=f"(d[94]), "=f"(d[95])
    : "r"(a), "r"(b), "n"(AHI), "n"(BHI));
}
template<uint32_t AHI, uint32_t BHI> __device__ __forceinline__ void wg_ss_n24(float* d, uint32_t a, uint32_t b) {
  asm volatile("{\n.reg .pred p;\n.reg .b64 da, db;\nsetp.ne.b32 p, 1, 0;\nmov.b64 da, {%12, %14};\nmov.b64 db, {%13, %15};\n"
    "wgmma.mma_async.sync.aligned.m64n24k16.f32.bf16.bf16 {%0, %1, %2, %3, %4, %5, %6, %7, %8, %9, %10, %11}, da, db, p, 1, 1, 0, 1;\n}\n"
    : "+f"(d[0]), "+f"(d[1]), "+f"(d[2]), "+f"(d[3]), "+f"(d[4]), "+f"(d[5]), "+f"(d[6]), "+f"(d[7]), "+f"(d[8]), "+f"(d[9]), "+f"(d[10]), "+f"(d[11])
    : "r"(a), "r"(b), "n"(AHI), "n"(BHI));
}
template<uint32_t AHI, uint32_t BHI> __device__ __forceinline__ void wg_ss_z_n24(float* d, uint32_t a, uint32_t b) {
  asm volatile("{\n.reg .pred p;\n.reg .b64 da, db;\nsetp.ne.b32 p, 0, 0;\nmov.b64 da, {%12, %14};\nmov.b64 db, {%13, %15};\n"
    "wgmma.mma_async.sync.aligned.m64n24k16.f32.bf16.bf16 {%0, %1, %2, %3, %4, %5, %6, %7, %8, %9, %10, %11}, da, db, p, 1, 1, 0, 1;\n}\n"
    : "=f"(d[0]), "=f"(d[1]), "=f"(d[2]), "=f"(d[3]), "=f"(d[4]), "=f"(d[5]), "=f"(d[6]), "=f"(d[7]), "=f"(d[8]), "=f"(d[9]), "=f"(d[10]), "=f"(d[11])
    : "r"(a), "r"(b), "n"(AHI), "n"(BHI));
}
template<uint32_t AHI, uint32_t BHI> __device__ __forceinline__ void wg_ss_n128(float* d, uint32_t a, uint32_t b) {
  asm volatile("{\n.reg .pred p;\n.reg .b64 da, db;\nsetp.ne.b32 p, 1, 0;\nmov.b64 da, {%64, %66};\nmov.b64 db, {%65, %67};\n"
    "wgmma.mma_async.sync.aligned.m64n128k16.f32.bf16.bf16 {%0, %1, %2, %3, %4, %5, %6, %7, %8, %9, %10, %11, %12, %13, %14, %15, %16, %17, %18, %19, %20, %21, %22, %23, %24, %25, %26, %27, %28, %29, %30, %31, %32, %33, %34, %35, %36, %37, %38, %39, %40, %41, %42, %43, %44, %45, %46, %47, %48, %49, %50, %51, %52, %53, %54, %55, %56, %57, %58, %59, %60, %61, %62, %63}, da, db, p, 1, 1, 0, 1;\n}\n"
    : "+f"(d[0]), "+f"(d[1]), "+f"(d[2]), "+f"(d[3]), "+f"(d[4]), "+f"(d[5]), "+f"(d[6]), "+f"(d[7]), "+f"(d[8]), "+f"(d[9]), "+f"(d[10]), "+f"(d[11]), "+f"(d[12]), "+f"(d[13]), "+f"(d[14]), "+f"(d[15]), "+f"(d[16]), "+f"(d[17]), "+f"(d[18]), "+f"(d[19]), "+f"(d[20]), "+f"(d[21]), "+f"(d[22]), "+f"(d[23]), "+f"(d[24]), "+f"(d[25]), "+f"(d[26]), "+f"(d[27]), "+f"(d[28]), "+f"(d[29]), "+f"(d[30]), "+f"(d[31]), "+f"(d[32]), "+f"(d[33]), "+f"(d[34]), "+f"(d[35]), "+f"(d[36]), "+f"(d[37]), "+f"(d[38]), "+f"(d[39]), "+f"(d[40]), "+f"(d[41]), "+f"(d[42]), "+f"(d[43]), "+f"(d[44]), "+f"(d[45]), "+f"(d[46]), "+f"(d[47]), "+f"(d[48]), "+f"(d[49]), "+f"(d[50]), "+f"(d[51]), "+f"(d[52]), "+f"(d[53]), "+f"(d[54]), "+f"(d[55]), "+f"(d[56]), "+f"(d[57]), "+f"(d[58]), "+f"(d[59]), "+f"(d[60]), "+f"(d[61]), "+f"(d[62]), "+f"(d[63])
    : "r"(a), "r"(b), "n"(AHI), "n"(BHI));
}
template<uint32_t AHI, uint32_t BHI> __device__ __forceinline__ void wg_ss_z_n128(float* d, uint32_t a, uint32_t b) {
  asm volatile("{\n.reg .pred p;\n.reg .b64 da, db;\nsetp.ne.b32 p, 0, 0;\nmov.b64 da, {%64, %66};\nmov.b64 db, {%65, %67};\n"
    "wgmma.mma_async.sync.aligned.m64n128k16.f32.bf16.bf16 {%0, %1, %2, %3, %4, %5, %6, %7, %8, %9, %10, %11, %12, %13, %14, %15, %16, %17, %18, %19, %20, %21, %22, %23, %24, %25, %26, %27, %28, %29, %30, %31, %32, %33, %34, %35, %36, %37, %38, %39, %40, %41, %42, %43, %44, %45, %46, %47, %48, %49, %50, %51, %52, %53, %54, %55, %56, %57, %58, %59, %60, %61, %62, %63}, da, db, p, 1, 1, 0, 1;\n}\n"
    : "=f"(d[0]), "=f"(d[1]), "=f"(d[2]), "=f"(d[3]), "=f"(d[4]), "=f"(d[5]), "=f"(d[6]), "=f"(d[7]), "=f"(d[8]), "=f"(d[9]), "=f"(d[10]), "=f"(d[11]), "=f"(d[12]), "=f"(d[13]), "=f"(d[14]), "=f"(d[15]), "=f"(d[16]), "=f"(d[17]), "=f"(d[18]), "=f"(d[19]), "=f"(d[20]), "=f"(d[21]), "=f"(d[22]), "=f"(d[23]), "=f"(d[24]), "=f"(d[25]), "=f"(d[26]), "=f"(d[27]), "=f"(d[28]), "=f"(d[29]), "=f"(d[30]), "=f"(d[31]), "=f"(d[32]), "=f"(d[33]), "=f"(d[34]), "=f"(d[35]), "=f"(d[36]), "=f"(d[37]), "=f"(d[38]), "=f"(d[39]), "=f"(d[40]), "=f"(d[41]), "=f"(d[42]), "=f"(d[43]), "=f"(d[44]), "=f"(d[45]), "=f"(d[46]), "=f"(d[47]), "=f"(d[48]), "=f"(d[49]), "=f"(d[50]), "=f"(d[51]), "=f"(d[52]), "=f"(d[53]), "=f"(d[54]), "=f"(d[55]), "=f"(d[56]), "=f"(d[57]), "=f"(d[58]), "=f"(d[59]), "=f"(d[60]), "=f"(d[61]), "=f"(d[62]), "=f"(d[63])
    : "r"(a), "r"(b), "n"(AHI), "n"(BHI));
}
template<uint32_t AHI, uint32_t BHI> __device__ __forceinline__ void wg_ss_n160(float* d, uint32_t a, uint32_t b) {
  asm volatile("{\n.reg .pred p;\n.reg .b64 da, db;\nsetp.ne.b32 p, 1, 0;\nmov.b64 da, {%80, %82};\nmov.b64 db, {%81, %83};\n"
    "wgmma.mma_async.sync.aligned.m64n160k16.f32.bf16.bf16 {%0, %1, %2, %3, %4, %5, %6, %7, %8, %9, %10, %11, %12, %13, %14, %15, %16, %17, %18, %19, %20, %21, %22, %23, %24, %25, %26, %27, %28, %29, %30, %31, %32, %33, %34, %35, %36, %37, %38, %39, %40, %41, %42, %43, %44, %45, %46, %47, %48, %49, %50, %51, %52, %53, %54, %55, %56, %57, %58, %59, %60, %61, %62, %63, %64, %65, %66, %67, %68, %69, %70, %71, %72, %73, %74, %75, %76, %77, %78, %79}, da, db, p, 1, 1, 0, 1;\n}\n"
    : "+f"(d[0]), "+f"(d[1]), "+f"(d[2]), "+f"(d[3]), "+f"(d[4]), "+f"(d[5]), "+f"(d[6]), "+f"(d[7]), "+f"(d[8]), "+f"(d[9]), "+f"(d[10]), "+f"(d[11]), "+f"(d[12]), "+f"(d[13]), "+f"(d[14]), "+f"(d[15]), "+f"(d[16]), "+f"(d[17]), "+f"(d[18]), "+f"(d[19]), "+f"(d[20]), "+f"(d[21]), "+f"(d[22]), "+f"(d[23]), "+f"(d[24]), "+f"(d[25]), "+f"(d[26]), "+f"(d[27]), "+f"(d[28]), "+f"(d[29]), "+f"(d[30]), "+f"(d[31]), "+f"(d[32]), "+f"(d[33]), "+f"(d[34]), "+f"(d[35]), "+f"(d[36]), "+f"(d[37]), "+f"(d[38]), "+f"(d[39]), "+f"(d[40]), "+f"(d[41]), "+f"(d[42]), "+f"(d[43]), "+f"(d[44]), "+f"(d[45]), "+f"(d[46]), "+f"(d[47]), "+f"(d[48]), "+f"(d[49]), "+f"(d[50]), "+f"(d[51]), "+f"(d[52]), "+f"(d[53]), "+f"(d[54]), "+f"(d[55]), "+f"(d[56]), "+f"(d[57]), "+f"(d[58]), "+f"(d[59]), "+f"(d[60]), "+f"(d[61]), "+f"(d[62]), "+f"(d[63]), "+f"(d[64]), "+f"(d[65]), "+f"(d[66]), "+f"(d[67]), "+f"(d[68]), "+f"(d[69]), "+f"(d[70]), "+f"(d[71]), "+f"(d[72]), "+f"(d[73]), "+f"(d[74]), "+f"(d[75]), "+f"(d[76]), "+f"(d[77]), "+f"(d[78]), "+f"(d[79])
    : "r"(a), "r"(b), "n"(AHI), "n"(BHI));
}
template<uint32_t AHI, uint32_t BHI> __device__ __forceinline__ void wg_ss_z_n160(float* d, uint32_t a, uint32_t b) {
  asm volatile("{\n.reg .pred p;\n.reg .b64 da, db;\nsetp.ne.b32 p, 0, 0;\nmov.b64 da, {%80, %82};\nmov.b64 db, {%81, %83};\n"
    "wgmma.mma_async.sync.aligned.m64n160k16.f32.bf16.bf16 {%0, %1, %2, %3, %4, %5, %6, %7, %8, %9, %10, %11, %12, %13, %14, %15, %16, %17, %18, %19, %20, %21, %22, %23, %24, %25, %26, %27, %28, %29, %30, %31, %32, %33, %34, %35, %36, %37, %38, %39, %40, %41, %42, %43, %44, %45, %46, %47, %48, %49, %50, %51, %52, %53, %54, %55, %56, %57, %58, %59, %60, %61, %62, %63, %64, %65, %66, %67, %68, %69, %70, %71, %72, %73, %74, %75, %76, %77, %78, %79}, da, db, p, 1, 1, 0, 1;\n}\n"
    : "=f"(d[0]), "=f"(d[1]), "=f"(d[2]), "=f"(d[3]), "=f"(d[4]), "=f"(d[5]), "=f"(d[6]), "=f"(d[7]), "=f"(d[8]), "=f"(d[9]), "=f"(d[10]), "=f"(d[11]), "=f"(d[12]), "=f"(d[13]), "=f"(d[14]), "=f"(d[15]), "=f"(d[16]), "=f"(d[17]), "=f"(d[18]), "=f"(d[19]), "=f"(d[20]), "=f"(d[21]), "=f"(d[22]), "=f"(d[23]), "=f"(d[24]), "=f"(d[25]), "=f"(d[26]), "=f"(d[27]), "=f"(d[28]), "=f"(d[29]), "=f"(d[30]), "=f"(d[31]), "=f"(d[32]), "=f"(d[33]), "=f"(d[34]), "=f"(d[35]), "=f"(d[36]), "=f"(d[37]), "=f"(d[38]), "=f"(d[39]), "=f"(d[40]), "=f"(d[41]), "=f"(d[42]), "=f"(d[43]), "=f"(d[44]), "=f"(d[45]), "=f"(d[46]), "=f"(d[47]), "=f"(d[48]), "=f"(d[49]), "=f"(d[50]), "=f"(d[51]), "=f"(d[52]), "=f"(d[53]), "=f"(d[54]), "=f"(d[55]), "=f"(d[56]), "=f"(d[57]), "=f"(d[58]), "=f"(d[59]), "=f"(d[60]), "=f"(d[61]), "=f"(d[62]), "=f"(d[63]), "=f"(d[64]), "=f"(d[65]), "=f"(d[66]), "=f"(d[67]), "=f"(d[68]), "=f"(d[69]), "=f"(d[70]), "=f"(d[71]), "=f"(d[72]), "=f"(d[73]), "=f"(d[74]), "=f"(d[75]), "=f"(d[76]), "=f"(d[77]), "=f"(d[78]), "=f"(d[79])
    : "r"(a), "r"(b), "n"(AHI), "n"(BHI));
}
template<uint32_t BHI> __device__ __forceinline__ void wg_rs_n32(float* d, uint32_t a0, uint32_t a1, uint32_t a2, uint32_t a3, uint32_t b) {
  asm volatile("{\n.reg .pred p;\n.reg .b64 db;\nsetp.ne.b32 p, 1, 0;\nmov.b64 db, {%20, %21};\n"
    "wgmma.mma_async.sync.aligned.m64n32k16.f32.bf16.bf16 {%0, %1, %2, %3, %4, %5, %6, %7, %8, %9, %10, %11, %12, %13, %14, %15}, {%16, %17, %18, %19}, db, p, 1, 1, 1;\n}\n"
    : "+f"(d[0]), "+f"(d[1]), "+f"(d[2]), "+f"(d[3]), "+f"(d[4]), "+f"(d[5]), "+f"(d[6]), "+f"(d[7]), "+f"(d[8]), "+f"(d[9]), "+f"(d[10]), "+f"(d[11]), "+f"(d[12]), "+f"(d[13]), "+f"(d[14]), "+f"(d[15])
    : "r"(a0), "r"(a1), "r"(a2), "r"(a3), "r"(b), "n"(BHI));
}
template<uint32_t BHI> __device__ __forceinline__ void wg_rs_z_n32(float* d, uint32_t a0, uint32_t a1, uint32_t a2, uint32_t a3, uint32_t b) {
  asm volatile("{\n.reg .pred p;\n.reg .b64 db;\nsetp.ne.b32 p, 0, 0;\nmov.b64 db, {%20, %21};\n"
    "wgmma.mma_async.sync.aligned.m64n32k16.f32.bf16.bf16 {%0, %1, %2, %3, %4, %5, %6, %7, %8, %9, %10, %11, %12, %13, %14, %15}, {%16, %17, %18, %19}, db, p, 1, 1, 1;\n}\n"
    : "=f"(d[0]), "=f"(d[1]), "=f"(d[2]), "=f"(d[3]), "=f"(d[4]), "=f"(d[5]), "=f"(d[6]), "=f"(d[7]), "=f"(d[8]), "=f"(d[9]), "=f"(d[10]), "=f"(d[11]), "=f"(d[12]), "=f"(d[13]), "=f"(d[14]), "=f"(d[15])
    : "r"(a0), "r"(a1), "r"(a2), "r"(a3), "r"(b), "n"(BHI));
}
template<uint32_t BHI> __device__ __forceinline__ void wg_rs_n64(float* d, uint32_t a0, uint32_t a1, uint32_t a2, uint32_t a3, uint32_t b) {
  asm volatile("{\n.reg .pred p;\n.reg .b64 db;\nsetp.ne.b32 p, 1, 0;\nmov.b64 db, {%36, %37};\n"
    "wgmma.mma_async.sync.aligned.m64n64k16.f32.bf16.bf16 {%0, %1, %2, %3, %4, %5, %6, %7, %8, %9, %10, %11, %12, %13, %14, %15, %16, %17, %18, %19, %20, %21, %22, %23, %24, %25, %26, %27, %28, %29, %30, %31}, {%32, %33, %34, %35}, db, p, 1, 1, 0;\n}\n"
    : "+f"(d[0]), "+f"(d[1]), "+f"(d[2]), "+f"(d[3]), "+f"(d[4]), "+f"(d[5]), "+f"(d[6]), "+f"(d[7]), "+f"(d[8]), "+f"(d[9]), "+f"(d[10]), "+f"(d[11]), "+f"(d[12]), "+f"(d[13]), "+f"(d[14]), "+f"(d[15]), "+f"(d[16]), "+f"(d[17]), "+f"(d[18]), "+f"(d[19]), "+f"(d[20]), "+f"(d[21]), "+f"(d[22]), "+f"(d[23]), "+f"(d[24]), "+f"(d[25]), "+f"(d[26]), "+f"(d[27]), "+f"(d[28]), "+f"(d[29]), "+f"(d[30]), "+f"(d[31])
    : "r"(a0), "r"(a1), "r"(a2), "r"(a3), "r"(b), "n"(BHI));
}
template<uint32_t BHI> __device__ __forceinline__ void wg_rs_z_n64(float* d, uint32_t a0, uint32_t a1, uint32_t a2, uint32_t a3, uint32_t b) {
  asm volatile("{\n.reg .pred p;\n.reg .b64 db;\nsetp.ne.b32 p, 0, 0;\nmov.b64 db, {%36, %37};\n"
    "wgmma.mma_async.sync.aligned.m64n64k16.f32.bf16.bf16 {%0, %1, %2, %3, %4, %5, %6, %7, %8, %9, %10, %11, %12, %13, %14, %15, %16, %17, %18, %19, %20, %21, %22, %23, %24, %25, %26, %27, %28, %29, %30, %31}, {%32, %33, %34, %35}, db, p, 1, 1, 0;\n}\n"
    : "=f"(d[0]), "=f"(d[1]), "=f"(d[2]), "=f"(d[3]), "=f"(d[4]), "=f"(d[5]), "=f"(d[6]), "=f"(d[7]), "=f"(d[8]), "=f"(d[9]), "=f"(d[10]), "=f"(d[11]), "=f"(d[12]), "=f"(d[13]), "=f"(d[14]), "=f"(d[15]), "=f"(d[16]), "=f"(d[17]), "=f"(d[18]), "=f"(d[19]), "=f"(d[20]), "=f"(d[21]), "=f"(d[22]), "=f"(d[23]), "=f"(d[24]), "=f"(d[25]), "=f"(d[26]), "=f"(d[27]), "=f"(d[28]), "=f"(d[29]), "=f"(d[30]), "=f"(d[31])
    : "r"(a0), "r"(a1), "r"(a2), "r"(a3), "r"(b), "n"(BHI));
}
template<uint32_t BHI> __device__ __forceinline__ void wg_rs_n24(float* d, uint32_t a0, uint32_t a1, uint32_t a2, uint32_t a3, uint32_t b) {
  asm volatile("{\n.reg .pred p;\n.reg .b64 db;\nsetp.ne.b32 p, 1, 0;\nmov.b64 db, {%16, %17};\n"
    "wgmma.mma_async.sync.aligned.m64n24k16.f32.bf16.bf16 {%0, %1, %2, %3, %4, %5, %6, %7, %8, %9, %10, %11}, {%12, %13, %14, %15}, db, p, 1, 1, 1;\n}\n"
    : "+f"(d[0]), "+f"(d[1]), "+f"(d[2]), "+f"(d[3]), "+f"(d[4]), "+f"(d[5]), "+f"(d[6]), "+f"(d[7]), "+f"(d[8]), "+f"(d[9]), "+f"(d[10]), "+f"(d[11])
    : "r"(a0), "r"(a1), "r"(a2), "r"(a3), "r"(b), "n"(BHI));
}
template<uint32_t BHI> __device__ __forceinline__ void wg_rs_z_n24(float* d, uint32_t a0, uint32_t a1, uint32_t a2, uint32_t a3, uint32_t b) {
  asm volatile("{\n.reg .pred p;\n.reg .b64 db;\nsetp.ne.b32 p, 0, 0;\nmov.b64 db, {%16, %17};\n"
    "wgmma.mma_async.sync.aligned.m64n24k16.f32.bf16.bf16 {%0, %1, %2, %3, %4, %5, %6, %7, %8, %9, %10, %11}, {%12, %13, %14, %15}, db, p, 1, 1, 1;\n}\n"
    : "=f"(d[0]), "=f"(d[1]), "=f"(d[2]), "=f"(d[3]), "=f"(d[4]), "=f"(d[5]), "=f"(d[6]), "=f"(d[7]), "=f"(d[8]), "=f"(d[9]), "=f"(d[10]), "=f"(d[11])
    : "r"(a0), "r"(a1), "r"(a2), "r"(a3), "r"(b), "n"(BHI));
}
template<uint32_t BHI> __device__ __forceinline__ void wg_rsb_n64(float* d, uint32_t a0, uint32_t a1, uint32_t a2, uint32_t a3, uint32_t b) {
  asm volatile("{\n.reg .pred p;\n.reg .b64 db;\nsetp.ne.b32 p, 1, 0;\nmov.b64 db, {%36, %37};\n"
    "wgmma.mma_async.sync.aligned.m64n64k16.f32.bf16.bf16 {%0, %1, %2, %3, %4, %5, %6, %7, %8, %9, %10, %11, %12, %13, %14, %15, %16, %17, %18, %19, %20, %21, %22, %23, %24, %25, %26, %27, %28, %29, %30, %31}, {%32, %33, %34, %35}, db, p, 1, 1, 1;\n}\n"
    : "+f"(d[0]), "+f"(d[1]), "+f"(d[2]), "+f"(d[3]), "+f"(d[4]), "+f"(d[5]), "+f"(d[6]), "+f"(d[7]), "+f"(d[8]), "+f"(d[9]), "+f"(d[10]), "+f"(d[11]), "+f"(d[12]), "+f"(d[13]), "+f"(d[14]), "+f"(d[15]), "+f"(d[16]), "+f"(d[17]), "+f"(d[18]), "+f"(d[19]), "+f"(d[20]), "+f"(d[21]), "+f"(d[22]), "+f"(d[23]), "+f"(d[24]), "+f"(d[25]), "+f"(d[26]), "+f"(d[27]), "+f"(d[28]), "+f"(d[29]), "+f"(d[30]), "+f"(d[31])
    : "r"(a0), "r"(a1), "r"(a2), "r"(a3), "r"(b), "n"(BHI));
}
template<uint32_t BHI> __device__ __forceinline__ void wg_rsb_z_n64(float* d, uint32_t a0, uint32_t a1, uint32_t a2, uint32_t a3, uint32_t b) {
  asm volatile("{\n.reg .pred p;\n.reg .b64 db;\nsetp.ne.b32 p, 0, 0;\nmov.b64 db, {%36, %37};\n"
    "wgmma.mma_async.sync.aligned.m64n64k16.f32.bf16.bf16 {%0, %1, %2, %3, %4, %5, %6, %7, %8, %9, %10, %11, %12, %13, %14, %15, %16, %17, %18, %19, %20, %21, %22, %23, %24, %25, %26, %27, %28, %29, %30, %31}, {%32, %33, %34, %35}, db, p, 1, 1, 1;\n}\n"
    : "=f"(d[0]), "=f"(d[1]), "=f"(d[2]), "=f"(d[3]), "=f"(d[4]), "=f"(d[5]), "=f"(d[6]), "=f"(d[7]), "=f"(d[8]), "=f"(d[9]), "=f"(d[10]), "=f"(d[11]), "=f"(d[12]), "=f"(d[13]), "=f"(d[14]), "=f"(d[15]), "=f"(d[16]), "=f"(d[17]), "=f"(d[18]), "=f"(d[19]), "=f"(d[20]), "=f"(d[21]), "=f"(d[22]), "=f"(d[23]), "=f"(d[24]), "=f"(d[25]), "=f"(d[26]), "=f"(d[27]), "=f"(d[28]), "=f"(d[29]), "=f"(d[30]), "=f"(d[31])
    : "r"(a0), "r"(a1), "r"(a2), "r"(a3), "r"(b), "n"(BHI));
}

__device__ __forceinline__ void wg_fence() { asm volatile("wgmma.fence.sync.aligned;" ::: "memory"); }
__device__ __forceinline__ void wg_commit() { asm volatile("wgmma.commit_group.sync.aligned;" ::: "memory"); }
template <int N> __device__ __forceinline__ void wg_wait() { asm volatile("wgmma.wait_group.sync.aligned %0;" ::"n"(N) : "memory"); }
template <int R> __device__ __forceinline__ void pin(float* d) {
#pragma unroll
  for (int i = 0; i < R; i++) asm volatile("" : "+f"(d[i])::"memory");
}
template <int R> __device__ __forceinline__ void pin(uint32_t* d) {
#pragma unroll
  for (int i = 0; i < R; i++) asm volatile("" : "+r"(d[i])::"memory");
}
__device__ __forceinline__ float ex2(float x) { float y; asm("ex2.approx.ftz.f32 %0, %1;" : "=f"(y) : "f"(x)); return y; }
__device__ __forceinline__ float tanh_fast(float x) { float y; asm("tanh.approx.f32 %0, %1;" : "=f"(y) : "f"(x)); return y; }
__device__ __forceinline__ uint32_t pack(float lo, float hi) { uint32_t r; asm("cvt.rn.bf16x2.f32 %0, %1, %2;" : "=r"(r) : "f"(hi), "f"(lo)); return r; }
__device__ __forceinline__ float bf_lo(uint32_t v) { return __uint_as_float(v << 16); }
__device__ __forceinline__ float bf_hi(uint32_t v) { return __uint_as_float(v & 0xffff0000u); }
__device__ __forceinline__ float bf_round(float x) { return bf_lo(pack(x, 0.f)); }

__device__ __forceinline__ void mbar_init(uint32_t bar, uint32_t cnt) { asm volatile("mbarrier.init.shared::cta.b64 [%0], %1;" ::"r"(bar), "r"(cnt) : "memory"); }
__device__ __forceinline__ void mbar_expect(uint32_t bar, uint32_t bytes) { asm volatile("mbarrier.arrive.expect_tx.shared::cta.b64 _, [%0], %1;" ::"r"(bar), "r"(bytes) : "memory"); }
__device__ __forceinline__ void mbar_expect_only(uint32_t bar, uint32_t bytes) { asm volatile("mbarrier.expect_tx.relaxed.cta.shared::cta.b64 [%0], %1;" ::"r"(bar), "r"(bytes) : "memory"); }
__device__ __forceinline__ void mbar_wait(uint32_t bar, uint32_t parity) {
  asm volatile(
      "{\n.reg .pred p;\n.reg .u32 c;\n"
      "mbarrier.try_wait.parity.shared::cta.b64 p, [%0], %1;\n"
      "@p bra.uni DONE;\n"
      "mov.u32 c, 0;\n"
      "LOOP:\n"
      "mbarrier.try_wait.parity.shared::cta.b64 p, [%0], %1;\n"
      "@p bra.uni DONE;\n"
      "add.u32 c, c, 1;\n"
      "setp.lt.u32 p, c, 0x4000000;\n"
      "@p bra.uni LOOP;\n"
      "trap;\n"
      "DONE:\n}\n" ::"r"(bar), "r"(parity) : "memory");
}
__device__ __forceinline__ uint32_t mbar_test(uint32_t bar, uint32_t parity) {
  uint32_t ok;
  asm volatile("{\n.reg .pred p;\nmbarrier.test_wait.parity.shared::cta.b64 p, [%1], %2;\nselp.u32 %0, 1, 0, p;\n}\n" : "=r"(ok) : "r"(bar), "r"(parity) : "memory");
  return ok;
}
__device__ __forceinline__ void mbar_arrive_if(uint32_t bar, uint32_t cond) {
  asm volatile("{\n.reg .pred p;\nsetp.ne.u32 p, %1, 0;\n@p mbarrier.arrive.shared::cta.b64 _, [%0];\n}\n" ::"r"(bar), "r"(cond) : "memory");
}
__device__ __forceinline__ uint32_t bsub2(uint32_t a, uint32_t b) { uint32_t d; asm("sub.rn.bf16x2 %0, %1, %2;" : "=r"(d) : "r"(a), "r"(b)); return d; }
__device__ __forceinline__ uint32_t bscale2(uint32_t d, uint32_t hi, uint32_t lo) {
  uint32_t t, r;
  asm("mul.rn.bf16x2 %0, %1, %2;" : "=r"(t) : "r"(d), "r"(lo));
  asm("fma.rn.bf16x2 %0, %1, %2, %3;" : "=r"(r) : "r"(d), "r"(hi), "r"(t));
  return r;
}
__device__ __forceinline__ void flag_wait(const uint32_t* f, uint32_t target) {
  asm volatile(
      "{\n.reg .pred p;\n.reg .u32 c, v;\n"
      "mov.u32 c, 0;\n"
      "LOOP:\n"
      "ld.acquire.gpu.global.u32 v, [%0];\n"
      "sub.u32 v, v, %1;\n"
      "setp.ge.s32 p, v, 0;\n"
      "@p bra DONE;\n"
      "add.u32 c, c, 1;\n"
      "setp.lt.u32 p, c, 0x1000000;\n"
      "@p bra LOOP;\n"
      "trap;\n"
      "DONE:\n}\n" ::"l"(f), "r"(target) : "memory");
}
__device__ __forceinline__ uint32_t flag_wait_v(const uint32_t* f, uint32_t target) {
  uint32_t v;
  asm volatile(
      "{\n.reg .pred p;\n.reg .u32 c, d;\n"
      "mov.u32 c, 0;\n"
      "LOOP:\n"
      "ld.acquire.gpu.global.u32 %0, [%1];\n"
      "sub.u32 d, %0, %2;\n"
      "setp.ge.s32 p, d, 0;\n"
      "@p bra DONE;\n"
      "add.u32 c, c, 1;\n"
      "setp.lt.u32 p, c, 0x1000000;\n"
      "@p bra LOOP;\n"
      "trap;\n"
      "DONE:\n}\n" : "=&r"(v) : "l"(f), "r"(target) : "memory");
  return v;
}
__device__ __forceinline__ float sqrt_fast(float x) { float y; asm("sqrt.approx.f32 %0, %1;" : "=f"(y) : "f"(x)); return y; }
__device__ __forceinline__ float rcp_fast(float x) { float y; asm("rcp.approx.ftz.f32 %0, %1;" : "=f"(y) : "f"(x)); return y; }
__device__ __forceinline__ void ldsm4(uint32_t* v, uint32_t addr) {
  asm volatile("ldmatrix.sync.aligned.m8n8.x4.shared.b16 {%0,%1,%2,%3}, [%4];" : "=r"(v[0]), "=r"(v[1]), "=r"(v[2]), "=r"(v[3]) : "r"(addr) : "memory");
}
__device__ __forceinline__ void stsm4(uint32_t addr, uint32_t a, uint32_t b, uint32_t c, uint32_t d) {
  asm volatile("stmatrix.sync.aligned.m8n8.x4.shared.b16 [%0], {%1,%2,%3,%4};" ::"r"(addr), "r"(a), "r"(b), "r"(c), "r"(d) : "memory");
}
__device__ __forceinline__ void flag_add(uint32_t* f) { asm volatile("red.relaxed.gpu.global.add.u32 [%0], 1;" ::"l"(f) : "memory"); }
__device__ __forceinline__ void fence_gpu() { asm volatile("fence.acq_rel.gpu;" ::: "memory"); }
#define FENCE_G 1
__device__ __forceinline__ void fence_async() { if (FENCE_G) asm volatile("fence.proxy.async.global;" ::: "memory"); else asm volatile("fence.proxy.async;" ::: "memory"); }
__device__ __forceinline__ void tma2d(uint32_t dst, const CUtensorMap* tm, uint32_t bar, int c0, int c1) {
  asm volatile("cp.async.bulk.tensor.2d.shared::cluster.global.mbarrier::complete_tx::bytes [%0], [%1, {%3, %4}], [%2];" ::"r"(dst), "l"(tm), "r"(bar), "r"(c0), "r"(c1) : "memory");
}
__device__ __forceinline__ void tma2d_h(uint32_t dst, const CUtensorMap* tm, uint32_t bar, int c0, int c1, uint64_t pol) {
  asm volatile("cp.async.bulk.tensor.2d.shared::cluster.global.mbarrier::complete_tx::bytes.L2::cache_hint [%0], [%1, {%3, %4}], [%2], %5;" ::"r"(dst), "l"(tm), "r"(bar), "r"(c0), "r"(c1), "l"(pol) : "memory");
}
__device__ __forceinline__ void bulk_s2g(void* dst, uint32_t src, uint32_t bytes) {
  asm volatile("cp.async.bulk.global.shared::cta.bulk_group [%0], [%1], %2;" ::"l"(dst), "r"(src), "r"(bytes) : "memory");
}
__device__ __forceinline__ void mma_ones(float* c, const uint32_t* a) {
  asm("mma.sync.aligned.m16n8k16.row.col.f32.bf16.bf16.f32 {%0,%1,%2,%3}, {%4,%5,%6,%7}, {%8,%8}, {%0,%1,%2,%3};"
      : "+f"(c[0]), "+f"(c[1]), "+f"(c[2]), "+f"(c[3]) : "r"(a[0]), "r"(a[1]), "r"(a[2]), "r"(a[3]), "r"(0x3f803f80u));
}
__device__ __forceinline__ void tma5d(uint32_t dst, const CUtensorMap* tm, uint32_t bar, int c0, int c4) {
  asm volatile("cp.async.bulk.tensor.5d.shared::cluster.global.mbarrier::complete_tx::bytes [%0], [%1, {%3, %5, %5, %5, %4}], [%2];" ::"r"(dst), "l"(tm), "r"(bar), "r"(c0), "r"(c4), "r"(0) : "memory");
}
__device__ __forceinline__ void tma3d(uint32_t dst, const CUtensorMap* tm, uint32_t bar, int c0, int c2) {
  asm volatile("cp.async.bulk.tensor.3d.shared::cluster.global.mbarrier::complete_tx::bytes [%0], [%1, {%3, %5, %4}], [%2];" ::"r"(dst), "l"(tm), "r"(bar), "r"(c0), "r"(c2), "r"(0) : "memory");
}
__device__ __forceinline__ void bulk_g2s(uint32_t dst, const void* src, uint32_t bytes, uint32_t bar) {
  asm volatile("cp.async.bulk.shared::cluster.global.mbarrier::complete_tx::bytes [%0], [%1], %2, [%3];" ::"r"(dst), "l"(src), "r"(bytes), "r"(bar) : "memory");
}
__device__ __forceinline__ void pf_line(const void* p) { asm volatile("prefetch.global.L2 [%0];" ::"l"(p) : "memory"); }
__device__ __forceinline__ int fresh_tid() { int v; asm volatile("mov.u32 %0, %%tid.x;" : "=r"(v)); return v; }
struct Att {
  float s[32];
  float o[12];
  uint32_t p[16];
  uint32_t q[8];
};

__device__ __forceinline__ float warp_sum(float v) {
#pragma unroll 1
  for (int d = 16; d; d >>= 1) v += __shfl_xor_sync(0xffffffffu, v, d);
  return v;
}
#define OPAQUE(x) asm volatile("" : "+r"(x))
__device__ __forceinline__ void attn_slow_row(int cta, uint32_t& w) {
  float mx = -INFINITY;
#pragma unroll 1
  for (uint32_t key = threadIdx.x & 31; key < SEQ; key += 32) {
    float s = 0.f;
#pragma unroll 1
    for (uint32_t v = 0; v < 9; v++) {
      OPAQUE(w); OPAQUE(key);
      const uint32_t hp = (w >> 4) & 3, pos = (v + hp) & 3;
      const uint32_t q = g_Q[(((cta * 4 + hp) * 2 + (v >> 3)) * 256 + ((w >> 6) & 7) * 32 + (w & 7) * 4 + pos) * 4 + 2 * ((v >> 2) & 1) + ((w >> 3) & 1)];
      const uint32_t u = g_KV[(4 * (cta & 7) + hp) * SEQ * 20 + (key >> 3) * 160 + (key & 7) * 4 + (v >> 2) * 32 + pos];
      s = fmaf(bf_lo(q), bf_lo(u), fmaf(bf_hi(q), bf_hi(u), s));
    }
    g_S[(cta * 8 + ((w >> 6) & 7)) * SEQ + key] = s;
    mx = fmaxf(mx, s);
  }
#pragma unroll 1
  for (int d = 16; d; d >>= 1) mx = fmaxf(mx, __shfl_xor_sync(0xffffffffu, mx, d));
  float l = 0.f;
#pragma unroll 1
  for (uint32_t key = threadIdx.x & 31; key < SEQ; key += 32) l += ex2(g_S[(cta * 8 + ((w >> 6) & 7)) * SEQ + key] - mx);
  l = 2.f * rcp_fast(warp_sum(l));
#pragma unroll 1
  for (uint32_t v = w >> 9; v < 9; v++) {
    float a = 0.f, b = 0.f;
#pragma unroll 1
    for (uint32_t key = threadIdx.x & 31; key < SEQ; key += 32) {
      OPAQUE(w); OPAQUE(v);
      const uint32_t hp = (w >> 4) & 3;
      const uint32_t u = g_KV[(4 * (cta & 7) + hp) * SEQ * 20 + (key >> 3) * 160 + (key & 7) * 4 + (v < 8 ? (3 + (v >> 2)) * 32 + (v & 3) : 64 + ((hp + 2) & 3))];
      const float p = ex2(g_S[(cta * 8 + ((w >> 6) & 7)) * SEQ + key] - mx);
      a = fmaf(p, bf_lo(u), a); b = fmaf(p, bf_hi(u), b);
    }
    a = warp_sum(a); b = warp_sum(b);
    OPAQUE(w);
    const uint32_t hp = (w >> 4) & 3;
    if ((threadIdx.x & 31) == 0) g_O[cta * 9 * 512 + (((w >> 6) & 7) * 16 + (w & 15)) * 4 + (v < 8 ? (2 * hp + (v >> 2)) * 512 + (v & 3) : 8 * 512 + hp)] = pack(a * l, b * l);
  }
}

__device__ __forceinline__ uint32_t bad_heads(uint32_t bad_addr, int wr) {
  uint32_t bad;
  __syncwarp();
  asm volatile("ld.volatile.shared.u32 %0, [%1];" : "=r"(bad) : "r"(bad_addr) : "memory");
  return __shfl_sync(0xffffffffu, (bad >> (4 * wr)) & 15, 0);
}
__device__ __forceinline__ void repair_rows(int cta, int wr, uint32_t bad, int last_head, bool final) {
#pragma unroll 1
  for (uint32_t w = wr * 64; w < wr * 64 + 64; w++) {
    if (!((bad >> ((w >> 4) & 3)) & 1)) continue;
    if (final && ((w >> 4) & 3) != last_head) w |= 8u << 9;
    attn_slow_row(cta, w);
    w &= 511;
  }
  __syncwarp();
}
__device__ __forceinline__ void o_normalise(const float* o, uint32_t* w, uint32_t& x0, uint32_t& x1, int hp, int lane, uint32_t bad_addr, int wr) {
  const int src = (lane & ~3) | ((hp + 1) & 3);
  float l0 = __shfl_sync(0xffffffffu, o[0], src), l1 = __shfl_sync(0xffffffffu, o[2], src);
  float sa = 0.f;
#pragma unroll
  for (int i = 0; i < 12; i++) sa += fabsf(o[i]);
  bool ok = (l0 <= 1.329228e36f) && (l1 <= 1.329228e36f) && (l0 > 0.f) && (l1 > 0.f) && (sa <= 3.0e38f);
  float i0 = 2.f * rcp_fast(l0), i1 = 2.f * rcp_fast(l1);
  w[0] = pack(o[4] * i0, o[5] * i0);
  w[1] = pack(o[6] * i1, o[7] * i1);
  w[2] = pack(o[8] * i0, o[9] * i0);
  w[3] = pack(o[10] * i1, o[11] * i1);
  if ((lane & 3) == ((hp + 2) & 3)) { x0 = pack(o[0] * i0, o[1] * i0); x1 = pack(o[2] * i1, o[3] * i1); }
  if (!ok) asm volatile("red.shared.or.b32 [%0], %1;" ::"r"(bad_addr), "r"(1u << (4 * wr + hp)) : "memory");
}

__device__ __forceinline__ void issue_pv(Att& a, uint32_t kdesc) {
  const uint32_t vdesc = kdesc + 192 + (LO_V - LO_K);
#pragma unroll
  for (int k = 0; k < 4; k++) wg_rs_n24<HI_V>(a.o, a.p[4 * k], a.p[4 * k + 1], a.p[4 * k + 2], a.p[4 * k + 3], vdesc + k * 48);
}
__device__ __forceinline__ void issue_att(Att& a, uint32_t kdesc) {
  issue_pv(a, kdesc);
  wg_rs_z_n64<HI_K>(a.s, a.q[0], a.q[1], a.q[2], a.q[3], kdesc);
  wg_rs_n64<HI_K>(a.s, a.q[4], a.q[5], a.q[6], a.q[7], kdesc + 16);
}
__device__ __forceinline__ void softmax_a(Att& a) {
#pragma unroll
  for (int i = 0; i < 9; i++) a.p[i] = pack(ex2(a.s[2 * i]), ex2(a.s[2 * i + 1]));
  a.s[18] = ex2(a.s[18]); a.s[19] = ex2(a.s[19]);
  pin<9>(a.p); pin<2>(a.s + 18);
}
__device__ __forceinline__ void softmax_b(Att& a) {
  a.p[9] = pack(a.s[18], a.s[19]);
#pragma unroll
  for (int i = 10; i < 16; i++) a.p[i] = pack(ex2(a.s[2 * i]), ex2(a.s[2 * i + 1]));
  pin<7>(a.p + 9);
}
__device__ __forceinline__ void first_tile(Att& a, int hp, int lane) {
  float m0 = fmaxf(a.s[0], a.s[1]), m1 = fmaxf(a.s[2], a.s[3]);
#pragma unroll
  for (int i = 4; i < 32; i += 4) { m0 = fmaxf(m0, fmaxf(a.s[i], a.s[i + 1])); m1 = fmaxf(m1, fmaxf(a.s[i + 2], a.s[i + 3])); }
  m0 = fmaxf(m0, __shfl_xor_sync(0xffffffffu, m0, 1)); m1 = fmaxf(m1, __shfl_xor_sync(0xffffffffu, m1, 1));
  m0 = fmaxf(m0, __shfl_xor_sync(0xffffffffu, m0, 2)); m1 = fmaxf(m1, __shfl_xor_sync(0xffffffffu, m1, 2));
  float n0 = -(m0 + MOFF), n1 = -(m1 + MOFF);
  float h0 = bf_round(n0), h1 = bf_round(n1);
  uint32_t e0 = pack(h0, n0 - h0), e1 = pack(h1, n1 - h1);
  n0 = h0 + bf_hi(e0); n1 = h1 + bf_hi(e1);
  if ((lane & 3) == ((hp + 1) & 3)) { a.q[4] = e0; a.q[5] = e1; }
#pragma unroll
  for (int i = 0; i < 32; i += 4) { a.s[i] += n0; a.s[i + 1] += n0; a.s[i + 2] += n1; a.s[i + 3] += n1; }
#pragma unroll
  for (int i = 0; i < 12; i++) a.o[i] = 0.f;
  pin<12>(a.o); pin<8>(a.q);
}
__device__ __forceinline__ void fetch_q(uint32_t* q, int cta, int hp, int tid) {
  const uint4* src = reinterpret_cast<const uint4*>(g_Q) + (cta * 4 + hp) * 512 + tid;
  const uint4 u = __ldcg(src);
  const uint2 v = __ldcg(reinterpret_cast<const uint2*>(src + 256));
  q[0] = u.x; q[1] = u.y; q[2] = u.z; q[3] = u.w; q[4] = v.x; q[5] = v.y;
}
__device__ __forceinline__ void h_epilogue(const float* acc, uint32_t* dst) {
#pragma unroll
  for (int b = 0; b < 4; b++) {
    uint32_t w[2][2];
#pragma unroll
    for (int i = 0; i < 2; i++) {
      float h[4];
#pragma unroll
      for (int e = 0; e < 4; e++) {
        const float g = acc[(2 * b + i) * 4 + e], u = acc[32 + (2 * b + i) * 4 + e];
        h[e] = fmaf(tanh_fast(0.5f * g), u, u);
      }
      w[0][i] = pack(h[0], h[1]); w[1][i] = pack(h[2], h[3]);
    }
    if (!EXP_NOST || w[0][0] == 0x12345678) {
    *reinterpret_cast<uint2*>(dst + 1024 * b) = make_uint2(w[0][0], w[0][1]);
    *reinterpret_cast<uint2*>(dst + 1024 * b + 32) = make_uint2(w[1][0], w[1][1]);
    }
  }
}
__device__ __forceinline__ void rotate9(uint32_t (&v)[9][2]) {
#pragma unroll
  for (int rh = 0; rh < 2; rh++) {
    const uint32_t r = v[8][rh];
#pragma unroll
    for (int i = 8; i > 0; i--) v[i][rh] = v[i - 1][rh];
    v[0][rh] = r;
  }
}
template <int HP> __device__ __forceinline__ void store_kv_head(uint32_t (&pk)[2][9][2], uint32_t* kvp, int lane) {
  const int t = lane & 3;
  const bool up = t < HP;
#pragma unroll
  for (int rh = 0; rh < 2; rh++) {
    uint32_t* d = kvp + HP * SEQ * 20 + rh * 160;
    d[0] = up ? pk[0][2 * HP + 1][rh] : pk[0][2 * HP][rh];
    d[32] = up ? pk[0][2 * HP + 2][rh] : pk[0][2 * HP + 1][rh];
    d[96 + ((t - HP) & 3) - t] = up ? pk[1][2 * HP + 1][rh] : pk[1][2 * HP][rh];
    d[128 + ((t - HP) & 3) - t] = up ? pk[1][2 * HP + 2][rh] : pk[1][2 * HP + 1][rh];
    const uint32_t v9 = __shfl_sync(0xffffffffu, pk[1][2 * HP + 2][rh], (lane & ~3) | HP);
    d[64] = t == HP ? pk[0][2 * HP + 2][rh] : t == ((HP + 1) & 3) ? 0x3f803f80u : t == ((HP + 2) & 3) ? v9 : 0u;
  }
}

template <int OFF> __device__ __forceinline__ void ld4(uint32_t* v, const void* p) {
  asm volatile("ld.relaxed.gpu.global.v4.b32 {%0,%1,%2,%3}, [%4 + %5];" : "=r"(v[0]), "=r"(v[1]), "=r"(v[2]), "=r"(v[3]) : "l"(p), "n"(OFF) : "memory");
}
template <int OFF> __device__ __forceinline__ void ld2(uint32_t* v, const void* p) {
  asm volatile("ld.relaxed.gpu.global.v2.b32 {%0,%1}, [%2 + %3];" : "=r"(v[0]), "=r"(v[1]) : "l"(p), "n"(OFF) : "memory");
}
__device__ __forceinline__ void stage_partials(const float* acc, uint32_t dst, int tid) {
  const int lane = tid & 31, row = (tid >> 5) * 16 + (lane & 15);
  const uint32_t r128 = dst + row * 128, r64 = dst + 49152 + row * 64;
#pragma unroll
  for (int i = 0; i < 12; i++) {
    const float* v = acc + 8 * i;
    stsm4(r128 + (i >> 2) * 16384 + (((2 * (i & 3) + (lane >> 4)) ^ (row & 7)) << 4), pack(v[0], v[1]), pack(v[2], v[3]), pack(v[4], v[5]), pack(v[6], v[7]));
  }
#pragma unroll
  for (int i = 0; i < 2; i++) {
    const float* v = acc + 128 + 8 * i;
    stsm4(r64 + (((2 * i + (lane >> 4)) ^ ((row >> 1) & 3)) << 4), pack(v[0], v[1]), pack(v[2], v[3]), pack(v[4], v[5]), pack(v[6], v[7]));
  }
}
__device__ __forceinline__ void final_epilogue(const float* acc, const Params& prm, int m, int hh, int q, int tid) {
  uint32_t r[18];
#pragma unroll
  for (int i = 0; i < 16; i++) r[i] = pack(acc[2 * i] * 0.5f, acc[2 * i + 1] * 0.5f);
#pragma unroll
  for (int i = 0; i < 2; i++) {
    const int o = 32 + 4 * i;
    const float a0 = (q & 2) ? acc[o + 2] : acc[o], a1 = (q & 2) ? acc[o + 10] : acc[o + 8];
    const float b0 = (q & 2) ? acc[o + 3] : acc[o + 1], b1 = (q & 2) ? acc[o + 11] : acc[o + 9];
    r[16 + i] = pack(((q & 1) ? a1 : a0) * 0.5f, ((q & 1) ? b1 : b0) * 0.5f);
  }
  const size_t off = (size_t)(128 * m + (tid >> 5) * 16 + ((tid & 31) >> 2)) * DM + 2 * (tid & 3);
  const bool odd = tid & 1;
  uint32_t* o1 = reinterpret_cast<uint32_t*>(prm.out + off + 320 * hh + 64 * q) + (odd ? 3 : 0);
  uint32_t* o2 = reinterpret_cast<uint32_t*>(prm.out + off + 256 + 32 * hh + 16 * (q & 1) + (q >> 1) * 8 * DM) + (odd ? 3 : 0);
#pragma unroll
  for (int i = 0; i < 9; i++) {
    const uint32_t A = i < 8 ? r[4 * (i >> 1) + (i & 1)] : r[16], B = i < 8 ? r[4 * (i >> 1) + 2 + (i & 1)] : r[17];
    const uint32_t y = __shfl_xor_sync(0xffffffffu, odd ? A : B, 1);
    *reinterpret_cast<uint2*>(i < 8 ? o1 + 8 * (i >> 1) + (i & 1) * 8 * (DM / 2) : o2) = odd ? make_uint2(y, B) : make_uint2(A, y);
  }
}

__global__ void __launch_bounds__(384, 1) fused_kernel(const __grid_constant__ Params prm) {
  extern __shared__ __align__(1024) uint8_t smem[];
  const uint32_t sb = (uint32_t)__cvta_generic_to_shared(smem);
  const uint32_t bar = sb + SM_BAR;
  const int m = blockIdx.x & 15, j = blockIdx.x >> 4;
  const int cta = m * 8 + j;
  const int wr = __shfl_sync(0xffffffffu, (int)(threadIdx.x >> 5), 0);
  const int wg = wr >> 2;
  const int lane = threadIdx.x & 31;
  STAMP(0);
  if (PF_X && threadIdx.x < 144) pf_line(prm.x + (size_t)cta * 16 * DM + threadIdx.x * 64);
  if (wg == 2 && lane == 0) {
    if (wr == 8) {
      asm volatile("prefetch.tensormap [%0];" ::"l"(&prm.xm) : "memory");
#pragma unroll
      for (int c = 0; c < 9; c++) mbar_init(bar + 8 * (B_X + c), 1);
#pragma unroll
      for (int c = 0; c < 9; c++) mbar_expect(bar + 8 * (B_X + c), 16384);
      asm volatile("fence.proxy.async.shared::cta;" ::: "memory");
#pragma unroll
      for (int c = 0; c < 3; c++) tma2d(sb + SM_XN + c * 16384, &prm.xm, bar + 8 * (B_X + c), 64 * c, 128 * m);
    } else {
      if (wr == 9) {
#pragma unroll
        for (int i = 0; i < 8; i++) mbar_init(bar + 8 * (B_F + i), 1);
#pragma unroll
        for (int i = 0; i < 3; i++) mbar_init(bar + 8 * (B_QF + i), 1);
      } else if (wr == 10) {
#pragma unroll
        for (int i = 0; i < 8; i++) mbar_init(bar + 8 * (B_E + i), 8);
#pragma unroll
        for (int i = 0; i < 3; i++) mbar_init(bar + 8 * (B_QE + i), 8);
      } else {
#pragma unroll
        for (int i = B_SK1; i <= B_SP; i++) mbar_init(bar + 8 * i, 8);
        mbar_init(bar + 8 * B_OL, 1); mbar_init(bar + 8 * B_RX, 1);
        mbar_init(bar + 8 * B_NR, 4); mbar_init(bar + 8 * (B_NR + 1), 4);
        asm volatile("st.shared.u32 [%0], 0;" ::"r"(sb + SM_BAD) : "memory");
        if (sb & 1023) asm volatile("trap;");
      }
      asm volatile("fence.proxy.async.shared::cta;" ::: "memory");
    }
  }
  if (wr == 0) {
    const uint32_t one = (lane >> 3) == (lane & 3) ? ((lane & 4) ? 0x3f800000u : 0x00003f80u) : 0u;
    asm volatile("st.shared.v4.b32 [%0], {%1,%2,%2,%1};" ::"r"(sb + SM_ID + lane * 16), "r"(one), "r"(0) : "memory");
  }
  __syncthreads();

  if (wg == 2) {
    asm volatile("setmaxnreg.dec.sync.aligned.u32 24;");
    const int pw = wr & 3;
    const uint32_t epoch = *(volatile uint32_t*)FLAG_EPOCH(cta);
    const int hh = j & 1;
#define ACOL(A) (320 * hh + 64 * (((j >> 1) + 1 + (A)) & 3))
    if (pw == 0) {
      if (lane == 0) {
#pragma unroll
        for (int c = 3; c < 9; c++) tma2d(sb + SM_XN + c * 16384, &prm.xm, bar + 8 * (B_X + c), 64 * c, 128 * m);
        uint64_t pol;
        asm volatile("createpolicy.fractional.L2::evict_first.b64 %0, 1.0;" : "=l"(pol));
#pragma unroll 1
        for (int kb = 0; kb < 9; kb++) {
          const int s = kb % 3;
          if (kb >= 3) mbar_wait(bar + 8 * (B_QE + s), (kb / 3 - 1) & 1);
          const uint32_t fb = bar + 8 * (B_QF + s), dst = sb + SM_RING + s * QST;
          mbar_expect(fb, QST);
#pragma unroll
          for (int p = 0; p < 3; p++) {
            tma2d(dst + p * 8192, &prm.wqkv64, fb, 576 * p + 72 * j + 8 * hh, 64 * kb);
            tma2d(dst + 24576 + p * 1024, &prm.wqkv8, fb, 576 * p + 72 * j + 64 - 64 * hh, 64 * kb);
          }
        }
        asm volatile("st.shared.u32 [%0], %1;" ::"r"(sb + SM_TAG), "r"((epoch + 1) & 1) : "memory");
        const int hx = hh * 3;
        int col = 576 * j, kr = 0, u = 0, kslot = 0, vrow = 0;
        uint32_t seen = 0;
#pragma unroll 1
        for (int n = 0; n <= 141; n++) {
          if (n >= 4) mbar_wait(bar + 8 * (B_E + ((n - 3) & 7)), ((n - 3) >> 3) & 1);
          else if (n != 2) mbar_wait(bar + 8 * (B_QE + (n == 3 ? 2 : n)), 0);
          const uint32_t fb = bar + 8 * (B_F + (n & 7));
          const bool att = n >= N_G2 || (n >= NG0 && kr != 0);
          mbar_expect(fb, (n < N_G2 ? BST : 0) + (att ? (n < 141 ? KVST : KVST / 2) : 0));
          if (n < N_G2) {
            const uint32_t dst = sb + SM_RING + (n & 3) * BST;
            tma2d_h(dst, &prm.wg, fb, col, kr, pol);
            tma2d_h(dst + 8192, &prm.wu, fb, col, kr, pol);
            if ((kr += 64) == 576) { kr = 0; col += 64; }
          }
          if (att) {
            if (u == 0 || u == 16) { flag_wait(FLAG_KV(u >> 4, j), 16 * epoch + 16); fence_async(); if (u == 0) STAMPW(18); }
            const uint32_t dst = sb + SM_KV + kslot * KVST;
            const int krow = (4 * j + ((u >> 5) ^ hx)) * 256 + ((u + 2 * m) & 31) * 8;
            if (u == 0) vrow = krow;
            if (u < 128) tma2d(dst, &prm.kv, fb, 0, krow);
            tma2d(dst + 3072, &prm.kv, fb, 128, vrow);
            vrow = krow; u++;
            if (++kslot == 3) kslot = 0;
          }
          if (n >= N_G2 - 2 && n < N_AO - 2 && (n & 1)) {
            const int b = (n - (N_G2 - 2)) >> 1;
            const uint32_t gb = bar + 8 * (B_F + ((n + 2) & 7)), dst = sb + (b & 3) * G2ST;
            if (b == 0) STAMPW(16);
            mbar_expect_only(gb, G2ST);
            if (b < 24) {
              const int own = b < 10 || b == 20 || b == 21, jj = own ? j : (j ^ 1), lb = b < 10 ? b : b < 20 ? b - 10 : 10 + (b & 1), need = (3 * lb + 6) >> 2;
              if (b == 10 || b == 20 || b == 22) seen = 0;
              if (seen < need) { seen = flag_wait_v(FLAG_H(m * 8 + jj), 9 * epoch + need) - 9 * epoch; fence_async(); }
              bulk_g2s(dst, g_H + (m * 576 + 72 * jj + 6 * lb) * 512, 12288, gb);
#pragma unroll
              for (int a = 0; a < 4; a++) tma5d(dst + 12288 + a * 6144, &prm.wd[0], gb, ACOL(a), 36 * jj + 3 * lb);
              tma5d(dst + 36864, &prm.wd[1 + hh], gb, 0, 36 * jj + 3 * lb);
            } else {
              const int r = b - 24;
              flag_wait(FLAG_O((cta & ~1) + r), epoch + 1);
              fence_async();
              bulk_g2s(dst, g_O + ((cta & ~1) + r) * 9 * 512 + r * 1024, 12288, gb);
#pragma unroll
              for (int a = 0; a < 4; a++) tma3d(dst + 12288 + a * 6144, &prm.wo3[0], gb, ACOL(a), 4 * (j & 6) + 5 * r);
              tma3d(dst + 36864, &prm.wo3[1 + hh], gb, 0, 4 * (j & 6) + 5 * r);
            }
            if (b == 0) STAMPW(17);
          }
        }
      }
    } else if (pw == 1) {
      if (lane == 0) {
        mbar_wait(bar + 8 * B_SP, 0);
        mbar_expect(bar + 8 * B_OL, 49152 + 32768);
        tma2d(sb + SM_RES, &prm.xm, bar + 8 * B_OL, ACOL(3), 128 * m);
        __nanosleep(200);
        tma2d(sb + SM_RES + 16384, &prm.xm, bar + 8 * B_OL, 256 + 32 * hh, 128 * m);
#pragma unroll 1
        for (int i = 0; i < 4; i++) {
          __nanosleep(200);
          tma3d(sb + SM_LB + i * 4096, &prm.wo2[0], bar + 8 * B_OL, ACOL(3), 8 * i + 3);
          tma3d(sb + SM_LB + 24576 + i * 4096, &prm.wo2[1 + hh], bar + 8 * B_OL, 0, 8 * i + 3);
          tma3d(sb + SM_LB + 16384 + i * 2048, &prm.wo16[0], bar + 8 * B_OL, ACOL(3), 8 * i);
          tma3d(sb + SM_LB + 40960 + i * 2048, &prm.wo16[1 + hh], bar + 8 * B_OL, 0, 8 * i);
        }
      }
    } else if (pw == 2) {
      if (lane == 0) {
#pragma unroll 1
        for (int i = 1; i < 18; i++) asm volatile("prefetch.tensormap [%0];" ::"l"(&prm.xm + i) : "memory");
        mbar_wait(bar + 8 * B_SK1, 0);
        STAMPW(22);
        fence_gpu(); flag_add(FLAG_KV(0, j));
        STAMPW(20);
        mbar_wait(bar + 8 * B_SK2, 0);
        fence_gpu(); flag_add(FLAG_KV(1, j));
#pragma unroll 1
        for (int t = 0; t < 9; t++) { mbar_wait(bar + 8 * B_SH, t & 1); if (EXP_DELAY) __nanosleep(EXP_DELAY); fence_gpu(); flag_add(FLAG_H(cta)); }
        mbar_wait(bar + 8 * B_SO1, 0);
        fence_gpu(); flag_add(FLAG_O(cta));
      }
    } else {
      mbar_wait(bar + 8 * (B_X + PF_Q), 0);
#pragma unroll 1
      for (int i = lane; i < 122; i += 32) pf_line(prm.pwqkv + (size_t)min(i * 128 + cta, 15551) * 64);
      mbar_wait(bar + 8 * (B_QE + PF_G1), 0);
#pragma unroll 1
      for (int t = -3; t < 9; t++) {
        if (t >= 0) { mbar_wait(bar + 8 * B_SH, t & 1); if (EXP_PFD) __nanosleep(EXP_PFD); }
        if (t < 6) {
#pragma unroll 1
          for (int i = lane; i < 72; i += 32) pf_line((i >= 36 ? prm.pwu : prm.pwg) + (size_t)(36 * m + (i >= 36 ? i - 36 : i)) * FF + 576 * j + 64 * (t + 3));
        }
        if (t >= 5) {
#pragma unroll 1
          for (int i = lane; i < 81; i += 32) {
            const int l = (2 * m + hh) * 81 + i, r = l / 9;
            pf_line(prm.pwd + (size_t)(1152 * (j >> 1) + 576 * (r / 144) + 144 * (t - 5) + r % 144) * DM + 64 * (l % 9));
          }
        }
      }
      if (cta * 41 + lane < 5184) pf_line(prm.pwo + (size_t)(cta * 41 + lane) * 64);
      if (lane < 9 && cta * 41 + 32 + lane < 5184) pf_line(prm.pwo + (size_t)(cta * 41 + 32 + lane) * 64);
      if (lane == 0) {
      mbar_wait(bar + 8 * B_SP, 0);
      const int q = j >> 1;
#pragma unroll 1
      for (int i = 0; i < 14; i++) {
        bulk_s2g(g_P + cta * 3584 + i * 256, sb + SM_SEND + i * 4096, 4096);
        asm volatile("cp.async.bulk.commit_group;\ncp.async.bulk.wait_group.read %0;" ::"n"(SEND_DEPTH) : "memory");
      }
      asm volatile("cp.async.bulk.wait_group 0;" ::: "memory");
      fence_gpu();
      flag_add(FLAG_P(cta));
      STAMPW(15);
      mbar_expect(bar + 8 * B_RX, 73728);
#pragma unroll 1
      for (int a = 0; a < 3; a++) {
        const int src = m * 8 + 2 * ((q + 3 - a) & 3) + hh;
        flag_wait(FLAG_P(src), epoch + 1);
        fence_async();
        bulk_g2s(sb + SM_RECV + a * 24576, g_P + src * 3584 + a * 1024, 16384, bar + 8 * B_RX);
        bulk_g2s(sb + SM_RECV + a * 24576 + 16384, g_P + src * 3584 + 3072, 8192, bar + 8 * B_RX);
        if (RX_SLEEP) __nanosleep(RX_SLEEP);
      }
      STAMPW(25);
      *FLAG_EPOCH(cta) = epoch + 1;
      }
    }
  } else {
    const int tid = threadIdx.x;
    const int t = lane & 3;
    const uint32_t l0 = lane == 0;
    const uint32_t adesc = (((sb + SM_XN + wg * 8192) & 0x3FFFF) >> 4) | LO_A;
    const uint32_t bdesc = (((sb + SM_RING) & 0x3FFFF) >> 4) | LO_B;
    const uint32_t kdesc0 = (((sb + SM_KV) & 0x3FFFF) >> 4) | LO_K;
    const int hx = (j & 1) * 3;
    float accA[64], accB[64];
    Att a;
    uint32_t gs = 0, s8 = 0;
#define G1_ISSUE(ACC, AD, BD) _Pragma("unroll") for (int k = 0; k < 4; k++) wg_ss_n128<HI_SW128, HI_SW128>(ACC, (AD) + k * 2, (BD) + k * 128);
#define G1_ISSUE_Z(ACC, BD)                                                                                    \
  wg_ss_z_n128<HI_SW128, HI_SW128>(ACC, adesc, BD);                                                            \
  _Pragma("unroll") for (int k = 1; k < 4; k++) wg_ss_n128<HI_SW128, HI_SW128>(ACC, adesc + k * 2, (BD) + k * 128);
#define F_BAR (bar + 8 * B_F + 8 * s8)
#define F_PH ((gs >> 3) & 1)
#define RELEASE() mbar_arrive_if(bar + 8 * B_E + 8 * s8, l0);
#define NEXT_SLOT() { gs++; s8 = s8 == 7 ? 0 : s8 + 1; }
#define G1_ONLY() { mbar_wait(F_BAR, F_PH); wg_fence(); G1_ISSUE(accA, adesc + gs * 1024, bdesc + (gs & 3) * 1024) wg_commit(); wg_wait<1>(); RELEASE() NEXT_SLOT() }
    {
      const int lr = wr * 16 + (lane & 15);
      uint32_t ra[4];
#pragma unroll
      for (int k = 0; k < 4; k++) ra[k] = sb + SM_XN + lr * 128 + (((2 * k + (lane >> 4)) ^ (lr & 7)) << 4);
      STAMP(26);
      float cs[2][4] = {}, q0 = 0.f, q1 = 0.f, q2 = 0.f, q3 = 0.f;
#pragma unroll 1
      for (int c = 0; c < 9; c++) {
        mbar_wait(bar + 8 * (B_X + c), 0);
        if (c == 0) STAMP(27);
        if (c == 8) STAMP(28);
        uint32_t v[4][4];
#pragma unroll
        for (int k = 0; k < 4; k++) ldsm4(v[k], ra[k] + c * 16384);
#pragma unroll
        for (int k = 0; k < 4; k++) {
          mma_ones(cs[k & 1], v[k]);
#pragma unroll
          for (int e = 0; e < 4; e += 2) {
            const float x0 = bf_lo(v[k][e]), x1 = bf_hi(v[k][e]), y0 = bf_lo(v[k][e + 1]), y1 = bf_hi(v[k][e + 1]);
            q0 = fmaf(x0, x0, q0); q1 = fmaf(x1, x1, q1); q2 = fmaf(y0, y0, q2); q3 = fmaf(y1, y1, q3);
          }
        }
      }
      STAMP(11);
      asm volatile("setmaxnreg.inc.sync.aligned.u32 240;");
      const float mean0 = (cs[0][0] + cs[1][0]) * (1.f / 576.f), mean1 = (cs[0][2] + cs[1][2]) * (1.f / 576.f);
      q0 += q1; q2 += q3;
      q0 += __shfl_xor_sync(0xffffffffu, q0, 1); q2 += __shfl_xor_sync(0xffffffffu, q2, 1);
      q0 += __shfl_xor_sync(0xffffffffu, q0, 2); q2 += __shfl_xor_sync(0xffffffffu, q2, 2);
      float var0 = fmaf(q0, 1.f / 576.f, -mean0 * mean0), var1 = fmaf(q2, 1.f / 576.f, -mean1 * mean1);
      if (__any_sync(0xffffffffu, !(mean0 * mean0 <= 8.f * var0) || !(mean1 * mean1 <= 8.f * var1))) {
        q0 = q2 = 0.f;
#pragma unroll 1
        for (int i = 0; i < 36; i++) {
          uint32_t v[4];
          ldsm4(v, ((ra[0] + (i >> 2) * 16384) ^ ((i & 3) << 5)));
#pragma unroll
          for (int e = 0; e < 4; e += 2) {
            const float x0 = bf_lo(v[e]) - mean0, x1 = bf_hi(v[e]) - mean0, y0 = bf_lo(v[e + 1]) - mean1, y1 = bf_hi(v[e + 1]) - mean1;
            q0 = fmaf(x0, x0, fmaf(x1, x1, q0)); q2 = fmaf(y0, y0, fmaf(y1, y1, q2));
          }
        }
        q0 += __shfl_xor_sync(0xffffffffu, q0, 1); q2 += __shfl_xor_sync(0xffffffffu, q2, 1);
        q0 += __shfl_xor_sync(0xffffffffu, q0, 2); q2 += __shfl_xor_sync(0xffffffffu, q2, 2);
        var0 = q0 * (1.f / 576.f); var1 = q2 * (1.f / 576.f);
      }
      const float inv0 = rcp_fast(bf_round(sqrt_fast(bf_round(bf_round(var0) + 1e-5f)))), inv1 = rcp_fast(bf_round(sqrt_fast(bf_round(bf_round(var1) + 1e-5f))));
      const uint32_t mb0 = pack(mean0, mean0), mb1 = pack(mean1, mean1);
      const uint32_t h0 = pack(inv0, inv0), h1 = pack(inv1, inv1);
      const uint32_t e0 = pack(inv0 - bf_lo(h0), inv0 - bf_lo(h0)), e1 = pack(inv1 - bf_lo(h1), inv1 - bf_lo(h1));
#define NORM_STORE(C)                                                                                          \
  {                                                                                                            \
    _Pragma("unroll") for (int k = 0; k < 4; k++)                                                              \
      stsm4(ra[k] + (C) * 16384, bscale2(bsub2(v[k][0], mb0), h0, e0), bscale2(bsub2(v[k][1], mb1), h1, e1),   \
            bscale2(bsub2(v[k][2], mb0), h0, e0), bscale2(bsub2(v[k][3], mb1), h1, e1));                       \
    asm volatile("fence.proxy.async.shared::cta;" ::: "memory");                                               \
    __syncwarp();                                                                                              \
    mbar_arrive_if(bar + 8 * B_NR + 8 * wg, l0);                                                               \
  }
      float aq[96], ar[12];
      {
        uint32_t v[4][4];
#pragma unroll
        for (int k = 0; k < 4; k++) ldsm4(v[k], ra[k]);
        NORM_STORE(0)
      }
#pragma unroll
      for (int i = 0; i < 96; i++) aq[i] = 0.f;
#pragma unroll
      for (int i = 0; i < 12; i++) ar[i] = 0.f;
      pin<96>(aq); pin<12>(ar);
      STAMP(1);
      const uint32_t rdesc = (((sb + SM_RING + 24576) & 0x3FFFF) >> 4) | LO_R;
      uint32_t s = 0, ph = 0;
#pragma unroll 1
      for (int kb = 0; kb < 9; kb++) {
        uint32_t v[4][4];
        const int cn = kb < 8 ? kb + 1 : 8;
#pragma unroll
        for (int k = 0; k < 4; k++) ldsm4(v[k], ra[k] + cn * 16384);
        mbar_wait(bar + 8 * B_QF + 8 * s, ph);
        mbar_wait(bar + 8 * B_NR + 8 * wg, kb & 1);
        wg_fence();
#pragma unroll
        for (int k = 0; k < 4; k++) {
          wg_ss_n192<HI_SW128, HI_SW128>(aq, adesc + kb * 1024 + k * 2, bdesc + s * (QST >> 4) + k * 128);
          wg_ss_n24<HI_SW128, HI_R>(ar, adesc + kb * 1024 + k * 2, rdesc + s * (QST >> 4) + k * 16);
        }
        wg_commit();
        if (kb < 8) NORM_STORE(cn)
        wg_wait<1>();
        mbar_arrive_if(bar + 8 * B_QE + (s == 0 ? 16 : 8 * s - 8), l0 & (kb > 0));
        if (++s == 3) { s = 0; ph ^= 1; }
      }
      wg_wait<0>();
      pin<96>(aq); pin<12>(ar);
      mbar_arrive_if(bar + 8 * (B_QE + 2), l0);
      STAMP(2);
      uint32_t* kvp = g_KV + (size_t)(4 * j) * SEQ * 20 + (16 * m + 2 * wr) * 160 + lane;
      uint32_t pk[2][9][2];
#pragma unroll
      for (int p = 0; p < 2; p++)
#pragma unroll
        for (int i = 0; i < 9; i++) {
          const float* src = i < 8 ? &aq[(8 * (p + 1) + i) * 4] : &ar[4 * (p + 1)];
          pk[p][i][0] = pack(src[0], src[1]); pk[p][i][1] = pack(src[2], src[3]);
        }
      if (hx) {
#pragma unroll
        for (int p = 0; p < 2; p++) { rotate9(pk[p]); }
        store_kv_head<3>(pk, kvp, lane);
      } else store_kv_head<0>(pk, kvp, lane);
      __syncwarp();
      mbar_arrive_if(bar + 8 * B_SK1, l0);
      STAMP(3);
      mbar_wait(bar + 8 * B_F, 0);
      wg_fence();
      G1_ISSUE_Z(accA, bdesc)
      wg_commit();
      RELEASE()
      NEXT_SLOT()
      uint32_t pq[9][2];
#pragma unroll
      for (int i = 0; i < 9; i++) {
        const float* src = i < 8 ? &aq[i * 4] : &ar[0];
        pq[i][0] = pack(bf_round(src[0]) * QSCALE, bf_round(src[1]) * QSCALE); pq[i][1] = pack(bf_round(src[2]) * QSCALE, bf_round(src[3]) * QSCALE);
      }
      if (hx) rotate9(pq);
      pin<18>(&pq[0][0]);
#pragma unroll 1
      while (gs < 3) G1_ONLY()
      if (hx) store_kv_head<0>(pk, kvp, lane); else store_kv_head<3>(pk, kvp, lane);
      store_kv_head<1>(pk, kvp, lane);
      store_kv_head<2>(pk, kvp, lane);
      __syncwarp();
      mbar_arrive_if(bar + 8 * B_SK2, l0);
      G1_ONLY()
      uint4* qp = reinterpret_cast<uint4*>(g_Q) + cta * 4 * 512 + tid;
#pragma unroll
      for (int hp = 0; hp < 4; hp++) {
        const bool up = t < hp;
        const uint4 u = make_uint4(up ? pq[2 * hp + 1][0] : pq[2 * hp][0], up ? pq[2 * hp + 1][1] : pq[2 * hp][1],
                                   up ? pq[2 * hp + 2][0] : pq[2 * hp + 1][0], up ? pq[2 * hp + 2][1] : pq[2 * hp + 1][1]);
        const uint4 v = make_uint4(t == hp ? pq[2 * hp + 2][0] : 0u, t == hp ? pq[2 * hp + 2][1] : 0u, 0u, 0u);
        qp[hp * 512] = u; qp[hp * 512 + 256] = v;
        if (hp == 0 || (hp == 3 && hx)) { a.q[0] = u.x; a.q[1] = u.y; a.q[2] = u.z; a.q[3] = u.w; a.q[4] = v.x; a.q[5] = v.y; }
      }
      a.q[6] = __shfl_sync(0xffffffffu, lane, 0); a.q[7] = __shfl_sync(0xffffffffu, lane >> 1, 1);
#pragma unroll
      for (int i = 0; i < 16; i++) a.p[i] = 0;
#pragma unroll
      for (int i = 0; i < 12; i++) a.o[i] = 0.f;
      pin<16>(a.p); pin<12>(a.o); pin<8>(a.q);
    }
    static_assert(NG0 == 5, "slot / item alignment below assumes NG0 == 5");
    G1_ONLY()
    STAMP(4);
    mbar_wait(F_BAR, F_PH);
    STAMP(23);
    uint32_t kd = kdesc0;
    uint32_t it = 0;
    uint32_t ox0 = 0, ox1 = 0;
    bool special = true;
    uint32_t qn[6] = {0, 0, 0, 0, 0, 0};
    uint32_t* hdst = g_H + ((m * 576 + 72 * j + (t >> 1)) * 128 + 16 * wr + (lane >> 2)) * 4 + 2 * (t & 1);
    uint32_t ad = adesc + NG0 * 1024, bd = bdesc + (gs & 3) * 1024;

#define ITEM_FIRST()                                                                                           \
  {                                                                                                            \
    pin<12>(a.o);                                                                                              \
    if (it != 0) {                                                                                             \
      uint32_t w[4];                                                                                           \
      o_normalise(a.o, w, ox0, ox1, ((it >> 5) - 1) ^ hx, lane, sb + SM_BAD, wr);                              \
      uint32_t* d = g_O + cta * 9 * 512 + (((it >> 5) - 1) ^ hx) * 1024 + wr * 64 + lane;                      \
      d[0] = w[0]; d[32] = w[1]; d[512] = w[2]; d[544] = w[3];                                                 \
    }                                                                                                          \
    if (it == 96) mbar_arrive_if(bar + 8 * B_SO1, l0 & (bad_heads(sb + SM_BAD, wr) == 0));                     \
    first_tile(a, (it >> 5) ^ hx, lane);                                                                       \
  }
#define ITEM_NEXTQ() { if (it & 2) { _Pragma("unroll") for (int i = 0; i < 6; i++) a.q[i] = qn[i]; } else fetch_q(qn, cta, ((it >> 5) + 1) ^ hx, tid); }
#define KV_ADVANCE() { kd = kd == kdesc0 + 768 ? kdesc0 : kd + 384; }
#define WAIT_UNLESS(OK) if (__builtin_expect(!(OK), 0)) mbar_wait(F_BAR, F_PH);
#define SOFTMAX_NEXT() { const uint32_t ok = mbar_test(F_BAR, F_PH); softmax_a(a); WAIT_UNLESS(ok) softmax_b(a); }
#define EPI_STEP(ACCN, ACCO)                                                                                   \
  {                                                                                                            \
    wg_fence();                                                                                                \
    G1_ISSUE_Z(ACCN, bd)                                                                                       \
    wg_commit();                                                                                               \
    wg_wait<1>();                                                                                              \
    pin<64>(ACCO);                                                                                             \
    RELEASE()                                                                                                  \
    NEXT_SLOT()                                                                                                \
    ad = adesc + 1024; bd = bdesc + (gs & 3) * 1024;                                                           \
    const uint32_t ok = mbar_test(F_BAR, F_PH);                                                                \
    h_epilogue(ACCO, hdst);                                                                                    \
    hdst += 4096;                                                                                              \
    __syncwarp();                                                                                              \
    mbar_arrive_if(bar + 8 * B_SH, l0);                                                                        \
    WAIT_UNLESS(ok)                                                                                            \
  }
#define ATT_LOOP1(ACC, ITEMS)                                                                                  \
  do {                                                                                                         \
    wg_fence();                                                                                                \
    issue_att(a, kd);                                                                                          \
    wg_commit();                                                                                               \
    G1_ISSUE(ACC, ad, bd)                                                                                      \
    wg_commit();                                                                                               \
    wg_wait<1>();                                                                                              \
    pin<32>(a.s);                                                                                              \
    RELEASE()                                                                                                  \
    TRACE()                                                                                                    \
    if (ITEMS) { if (__builtin_expect(special, 0)) { if (it & 1) ITEM_NEXTQ() else if (!(it & 2)) { if (it == 64) fetch_q(qn, cta, 3 ^ hx, tid); ITEM_FIRST() } } } \
    NEXT_SLOT() it++;                                                                                                \
    if (ITEMS) special = ((it + 3) & 31) < 4;                                                                  \
    KV_ADVANCE()                                                                                               \
    ad += 1024; bd = bdesc + (gs & 3) * 1024;                                                                  \
    SOFTMAX_NEXT()                                                                                             \
    pin<8>(a.q);                                                                                               \
  } while (ad != adesc + 9 * 1024);
#pragma unroll 1
    for (int pr = 0;; pr++) {
      ATT_LOOP1(accA, true)
      if (pr == 4) break;
      if (pr == 2) STAMP(29);
      EPI_STEP(accB, accA)
      if (pr == 2) STAMP(30);
      ATT_LOOP1(accB, false)
      if (pr == 2) STAMP(31);
      EPI_STEP(accA, accB)
      special = false;
      if (pr == 2) STAMP(21);
      if (pr == 3) STAMP(14);
    }
    STAMP(5);
    wg_wait<0>();
    pin<64>(accA);
    h_epilogue(accA, hdst);
    __syncwarp();
    mbar_arrive_if(bar + 8 * B_SH, l0);
    mbar_wait(bar + 8 * B_E, 0);
    asm volatile("st.shared.v4.b32 [%0], {%1,%2,%3,%4};\nst.shared.v2.b32 [%5], {%6,%7};" ::"r"(sb + SM_QS + tid * 16), "r"(qn[0]), "r"(qn[1]), "r"(qn[2]), "r"(qn[3]),
                 "r"(sb + SM_QS + 4096 + tid * 8), "r"(qn[4]), "r"(qn[5]) : "memory");
    STAMP(6);
    STAMP(12);

    float acc2[144];
    const uint32_t a2desc = (((sb + wg * 1024) & 0x3FFFF) >> 4) | LO_O;
    const uint32_t b2desc = (((sb + 12288) & 0x3FFFF) >> 4) | LO_B48;
    ad = a2desc; bd = b2desc;
#define G2_LO(K) wg_ss_n128<HI_O, HI_SW128>(acc2, ad + (K) * 256, bd + (K) * 128);
#define G2_HI(K) wg_ss_n160<HI_O, HI_SW128>(acc2 + 64, ad + (K) * 256, bd + (K) * 128 + 768);
#define ATT_PAIR(ZERO)                                                                                         \
  {                                                                                                            \
    wg_fence();                                                                                                \
    issue_att(a, kd);                                                                                          \
    wg_commit();                                                                                               \
    if (ZERO) { wg_ss_z_n128<HI_O, HI_SW128>(acc2, ad, bd); wg_ss_z_n160<HI_O, HI_SW128>(acc2 + 64, ad, bd + 768); } \
    else { G2_LO(0) G2_HI(0) }                                                                                 \
    G2_LO(1)                                                                                                   \
    wg_commit();                                                                                               \
    wg_wait<1>();                                                                                              \
    pin<32>(a.s);                                                                                              \
    RELEASE()                                                                                                  \
    TRACE()                                                                                                    \
    if (!(ZERO)) { if (__builtin_expect(gs == N_G2 + 28, 0)) ITEM_FIRST() }                                    \
    NEXT_SLOT() it++;                                                                                                \
    KV_ADVANCE()                                                                                               \
    SOFTMAX_NEXT()                                                                                             \
    pin<8>(a.q);                                                                                               \
    wg_fence();                                                                                                \
    issue_att(a, kd);                                                                                          \
    wg_commit();                                                                                               \
    G2_HI(1) G2_LO(2) G2_HI(2)                                                                                 \
    wg_commit();                                                                                               \
    wg_wait<1>();                                                                                              \
    pin<32>(a.s);                                                                                              \
    RELEASE()                                                                                                  \
    TRACE()                                                                                                    \
    if (!(ZERO) && __builtin_expect(gs == N_G2 + 27, 0)) {                                                     \
      const int ft = fresh_tid();                                                                              \
      asm volatile("ld.shared.v4.b32 {%0,%1,%2,%3}, [%6];\nld.shared.v2.b32 {%4,%5}, [%7];" : "=r"(a.q[0]), "=r"(a.q[1]), "=r"(a.q[2]), "=r"(a.q[3]), \
                   "=r"(a.q[4]), "=r"(a.q[5]) : "r"(sb + SM_QS + ft * 16), "r"(sb + SM_QS + 4096 + ft * 8) : "memory"); \
    }                                                                                                          \
    NEXT_SLOT() it++;                                                                                                \
    KV_ADVANCE()                                                                                               \
    ad = a2desc + (((gs - N_G2) >> 1) & 3) * 2688; bd = ad + (b2desc - a2desc);                                \
    SOFTMAX_NEXT()                                                                                             \
    pin<8>(a.q);                                                                                               \
  }
    ATT_PAIR(true)
#pragma unroll 1
    for (int half = 0; half < 2; half++) {
      const uint32_t stop = half ? N_AO : N_G2 + 46;
      do ATT_PAIR(false) while (gs != stop);
      if (!half) {
        const uint32_t bad = bad_heads(sb + SM_BAD, wr);
        if (bad) { repair_rows(cta, wr, bad, 3 ^ hx, false); mbar_arrive_if(bar + 8 * B_SO1, l0); }
      }
    }
    STAMP(13);
    wg_wait<0>();
    pin<144>(acc2);
    mbar_wait(bar + 8 * (B_E + 1), 0);
    stage_partials(acc2, sb + SM_SEND, fresh_tid());
    asm volatile("fence.proxy.async.shared::cta;" ::: "memory");
    __syncwarp();
    mbar_arrive_if(bar + 8 * B_SP, l0);
    do {
      wg_fence();
      issue_att(a, kd);
      wg_commit();
      wg_wait<0>();
      pin<32>(a.s);
      RELEASE()
      TRACE()
      NEXT_SLOT() it++;
      KV_ADVANCE()
      SOFTMAX_NEXT()
    } while (gs != 141);
    STAMP(7);
    wg_fence();
    issue_pv(a, kd);
    wg_commit();
    int tid2, bid2;
    asm volatile("mov.u32 %0, %%tid.x;" : "=r"(tid2));
    asm volatile("mov.u32 %0, %%ctaid.x;" : "=r"(bid2));
    const int m2 = bid2 & 15, j2 = bid2 >> 4;
    uint32_t tag;
    asm volatile("ld.shared.u32 %0, [%1];" : "=r"(tag) : "r"(sb + SM_TAG) : "memory");
    wg_wait<0>();
    pin<12>(a.o);
    {
      uint32_t w[4];
      o_normalise(a.o, w, ox0, ox1, 3 ^ hx, lane, sb + SM_BAD, wr);
      ox0 = __shfl_xor_sync(0xffffffffu, ox0, 2); ox1 = __shfl_xor_sync(0xffffffffu, ox1, 2);
      const uint32_t bad = bad_heads(sb + SM_BAD, wr);
      if (bad) {
        uint32_t* d = g_O + cta * 9 * 512 + wr * 64 + lane;
        uint32_t* h = d + (3 ^ hx) * 1024;
        h[0] = w[0]; h[32] = w[1]; h[512] = w[2]; h[544] = w[3]; d[4096] = ox0; d[4128] = ox1;
        __syncwarp();
        repair_rows(cta, wr, bad, 3 ^ hx, true);
        w[0] = __ldcg(h); w[1] = __ldcg(h + 32); w[2] = __ldcg(h + 512); w[3] = __ldcg(h + 544); ox0 = __ldcg(d + 4096); ox1 = __ldcg(d + 4128);
      }
      asm volatile("st.relaxed.gpu.global.v4.b32 [%0], {%1,%2,%3,%4};" ::"l"(g_L + (m2 * 8 + j2) * 384 + tid2), "r"((w[0] & ~1u) | tag), "r"((w[1] & ~1u) | tag),
                   "r"((w[2] & ~1u) | tag), "r"((w[3] & ~1u) | tag) : "memory");
      asm volatile("st.relaxed.gpu.global.v2.b32 [%0], {%1,%2};" ::"l"(reinterpret_cast<uint2*>(g_L + (m2 * 8 + j2) * 384 + 256) + tid2), "r"((ox0 & ~1u) | tag),
                   "r"((ox1 & ~1u) | tag) : "memory");
    }
    STAMP(8);
    uint32_t la[48];
    const uint4* p4 = g_L + m2 * 8 * 384 + tid2;
    const uint2* p2 = reinterpret_cast<const uint2*>(g_L + m2 * 8 * 384 + 256) + tid2;
#define LOAD_LA2() { ld2<0>(la + 32, p2); ld2<6144>(la + 34, p2); ld2<12288>(la + 36, p2); ld2<18432>(la + 38, p2); \
                     ld2<24576>(la + 40, p2); ld2<30720>(la + 42, p2); ld2<36864>(la + 44, p2); ld2<43008>(la + 46, p2); }
#define LOAD_LA4() { ld4<0>(la, p4); ld4<6144>(la + 4, p4); ld4<12288>(la + 8, p4); ld4<18432>(la + 12, p4); \
                     ld4<24576>(la + 16, p4); ld4<30720>(la + 20, p4); ld4<36864>(la + 24, p4); ld4<43008>(la + 28, p4); }
    LOAD_LA4()
    LOAD_LA2()
    float fin[48];
    uint32_t id[4][4];
    {
      uint32_t id2[4][4];
#pragma unroll
      for (int k = 0; k < 4; k++) {
        asm volatile("ld.volatile.shared.v4.b32 {%0,%1,%2,%3}, [%4];" : "=r"(id[k][0]), "=r"(id[k][1]), "=r"(id[k][2]), "=r"(id[k][3])
                     : "r"(sb + SM_ID + ((wr & 3) == k ? lane : 1) * 16) : "memory");
#pragma unroll
        for (int e = 0; e < 4; e++) id2[k][e] = id[k][e] + (id[k][e] & 0x00800080u);
      }
      pin<16>(&id[0][0]); pin<16>(&id2[0][0]);
      const uint32_t xdesc = (((sb + SM_RES + wg * 8192) & 0x3FFFF) >> 4) | LO_B;
      mbar_wait(bar + 8 * B_OL, 0);
      wg_fence();
      wg_rsb_z_n64<HI_SW128>(fin, id2[0][0], id2[0][1], id2[0][2], id2[0][3], xdesc);
      wg_rs_z_n32<HI_SW128>(fin + 32, id2[0][0], id2[0][1], id2[0][2], id2[0][3], xdesc + 1024);
#pragma unroll
      for (int k = 1; k < 4; k++) {
        wg_rsb_n64<HI_SW128>(fin, id2[k][0], id2[k][1], id2[k][2], id2[k][3], xdesc + k * 128);
        wg_rs_n32<HI_SW128>(fin + 32, id2[k][0], id2[k][1], id2[k][2], id2[k][3], xdesc + 1024 + k * 128);
      }
      wg_commit();
      wg_wait<0>();
      pin<48>(fin);
#pragma unroll
      for (int i = 0; i < 48; i++) fin[i] += acc2[96 + i];
      pin<48>(fin);
    }
    for (uint32_t tries = 0; tries < 0x400000u; tries++) {
      uint32_t bad = 0;
#pragma unroll
      for (int i = 0; i < 48; i++) bad |= la[i] ^ tag;
      if (__all_sync(0xffffffffu, !(bad & 1))) break;
      LOAD_LA4()
      LOAD_LA2()
    }
#pragma unroll
    for (int i = 0; i < 48; i++) la[i] ^= tag;
    pin<48>(la);
    STAMP(19);
    const uint32_t ldesc = (((sb + SM_LB) & 0x3FFFF) >> 4) | LO_B;
    wg_fence();
#pragma unroll
    for (int k = 0; k < 12; k++) {
      wg_rsb_n64<HI_SW128>(fin, la[4 * k], la[4 * k + 1], la[4 * k + 2], la[4 * k + 3], ldesc + k * 128);
      wg_rs_n32<HI_SW128>(fin + 32, la[4 * k], la[4 * k + 1], la[4 * k + 2], la[4 * k + 3], ldesc + 1536 + k * 128);
    }
    wg_commit();
    const uint32_t pdesc = (((sb + SM_RECV + wg * 8192) & 0x3FFFF) >> 4) | LO_B, hdesc = (((sb + SM_RECV + 16384 + wg * 4096) & 0x3FFFF) >> 4) | LO_B;
    mbar_wait(bar + 8 * B_RX, 0);
    STAMP(24);
    wg_fence();
#pragma unroll
    for (int a3 = 0; a3 < 3; a3++)
#pragma unroll
      for (int k = 0; k < 4; k++) {
        wg_rsb_n64<HI_SW128>(fin, id[k][0], id[k][1], id[k][2], id[k][3], pdesc + a3 * 1536 + k * 128);
        wg_rs_n32<HI_SW64>(fin + 32, id[k][0], id[k][1], id[k][2], id[k][3], hdesc + a3 * 1536 + k * 64);
      }
    wg_commit();
    wg_wait<0>();
    pin<48>(fin);
    STAMP(9);
    final_epilogue(fin, prm, m2, j2 & 1, j2 >> 1, tid2);
    STAMP(10);
  }
}

typedef CUresult (*EncodeFn)(CUtensorMap*, CUtensorMapDataType, cuuint32_t, void*, const cuuint64_t*, const cuuint64_t*, const cuuint32_t*, const cuuint32_t*,
                             CUtensorMapInterleave, CUtensorMapSwizzle, CUtensorMapL2promotion, CUtensorMapFloatOOBfill);

void enc2d(EncodeFn enc, CUtensorMap* tm, const void* base, uint64_t w, uint64_t h, uint64_t pitch_elems, uint32_t bw, uint32_t bh, CUtensorMapSwizzle sw) {
  cuuint64_t dims[2] = {w, h}, str[1] = {pitch_elems * 2};
  cuuint32_t box[2] = {bw, bh}, es[2] = {1, 1};
  enc(tm, CU_TENSOR_MAP_DATA_TYPE_BFLOAT16, 2, const_cast<void*>(base), dims, str, box, es, CU_TENSOR_MAP_INTERLEAVE_NONE, sw,
      CU_TENSOR_MAP_L2_PROMOTION_L2_128B, CU_TENSOR_MAP_FLOAT_OOB_FILL_NONE);
}

}

extern "C" void kernel_launch(void* const* d_in, const int* in_sizes, int n_in, void* d_out, int out_size) {
  (void)in_sizes; (void)n_in; (void)out_size;
  const __nv_bfloat16* x = (const __nv_bfloat16*)d_in[0];
  const __nv_bfloat16* wqkv = (const __nv_bfloat16*)d_in[1];
  const __nv_bfloat16* wo = (const __nv_bfloat16*)d_in[2];
  const __nv_bfloat16* wg = (const __nv_bfloat16*)d_in[4];
  const __nv_bfloat16* wu = (const __nv_bfloat16*)d_in[5];
  const __nv_bfloat16* wd = (const __nv_bfloat16*)d_in[6];
  void* fn = nullptr;
  cudaDriverEntryPointQueryResult qr;
  cudaGetDriverEntryPoint("cuTensorMapEncodeTiled", &fn, cudaEnableDefault, &qr);
  EncodeFn enc = (EncodeFn)fn;
  void* kvp = nullptr;
  cudaGetSymbolAddress(&kvp, g_KV);
  Params p;
  enc2d(enc, &p.xm, x, DM, SEQ, DM, 64, 128, CU_TENSOR_MAP_SWIZZLE_128B);
  enc2d(enc, &p.kv, kvp, 320, 32 * 256, 320, 192, 8, CU_TENSOR_MAP_SWIZZLE_NONE);
  enc2d(enc, &p.wqkv64, wqkv, 3 * DM, DM, 3 * DM, 64, 64, CU_TENSOR_MAP_SWIZZLE_128B);
  enc2d(enc, &p.wqkv8, wqkv, 3 * DM, DM, 3 * DM, 8, 64, CU_TENSOR_MAP_SWIZZLE_NONE);
  enc2d(enc, &p.wg, wg, FF, DM, FF, 64, 64, CU_TENSOR_MAP_SWIZZLE_128B);
  enc2d(enc, &p.wu, wu, FF, DM, FF, 64, 64, CU_TENSOR_MAP_SWIZZLE_128B);
  for (int v = 0; v < 3; v++) {
    const cuuint64_t wdt = v ? 32 : DM;
    const int c0 = v ? 256 + 32 * (v - 1) : 0;
    for (int e = 0; e < 3; e++) {
      cuuint64_t d3[3] = {wdt, e == 2 ? 2u : 16u, 32}, s3[2] = {DM * 2, 18 * DM * 2};
      cuuint32_t b3[3] = {64, e == 2 ? 2u : 16u, e == 0 ? 3u : e == 1 ? 2u : 8u}, e3[3] = {1, 1, 1};
      enc(e == 0 ? &p.wo3[v] : e == 1 ? &p.wo2[v] : &p.wo16[v], CU_TENSOR_MAP_DATA_TYPE_BFLOAT16, 3, (void*)(wo + c0 + (e == 2 ? 16 * DM : 0)), d3, s3, b3, e3,
          CU_TENSOR_MAP_INTERLEAVE_NONE, CU_TENSOR_MAP_SWIZZLE_128B, CU_TENSOR_MAP_L2_PROMOTION_L2_128B, CU_TENSOR_MAP_FLOAT_OOB_FILL_NONE);
    }
    cuuint64_t dims[5] = {wdt, 2, 2, 4, FF / 16}, str[4] = {DM * 2, 8 * DM * 2, 2 * DM * 2, 16 * DM * 2};
    cuuint32_t box[5] = {64, 2, 2, 4, 3}, es[5] = {1, 1, 1, 1, 1};
    enc(&p.wd[v], CU_TENSOR_MAP_DATA_TYPE_BFLOAT16, 5, (void*)(wd + c0), dims, str, box, es, CU_TENSOR_MAP_INTERLEAVE_NONE,
        CU_TENSOR_MAP_SWIZZLE_128B, CU_TENSOR_MAP_L2_PROMOTION_L2_128B, CU_TENSOR_MAP_FLOAT_OOB_FILL_NONE);
  }
  p.x = x; p.pwqkv = wqkv; p.pwo = wo; p.pwg = wg; p.pwu = wu; p.pwd = wd;
  p.out = (__nv_bfloat16*)d_out;
  cudaFuncSetAttribute(fused_kernel, cudaFuncAttributeMaxDynamicSharedMemorySize, SM_TOTAL);
  fused_kernel<<<NCTA, 384, SM_TOTAL, cudaStreamPerThread>>>(p);
}
```

```cpp
#include <cuda_runtime.h>
#include <cuda.h>
#include <cuda_bf16.h>
#include <stdint.h>

namespace {

constexpr int SEQ = 2048, DM = 576, FF = 4608;
constexpr int NCTA = 128;

constexpr uint32_t SM_XN = 0;
constexpr uint32_t SM_RING = 147456;
constexpr uint32_t SM_KV = 212992;
constexpr uint32_t QST = 27648, BST = 16384, KVST = 6144;
constexpr uint32_t G2ST = 43008;
constexpr uint32_t SM_LB = 0, SM_RES = 49152, SM_SEND = 86016, SM_RECV = SM_SEND;
constexpr uint32_t SM_QS = 204800;
constexpr uint32_t SM_ID = 231424;
constexpr uint32_t SM_BAR = 231936;
constexpr uint32_t SM_TAG = 232436;
constexpr uint32_t SM_BAD = 232432;
constexpr uint32_t SM_TOTAL = 232448;
enum { B_F = 0, B_E = 8, B_QF = 16, B_QE = 19, B_SK1 = 22, B_SK2 = 23, B_SH = 24, B_SO1 = 25, B_SP = 26, B_OL = 27, B_RX = 28, B_NR = 29, B_X = 31, B_N = 40 };
constexpr int N_G2 = 81, N_AO = 133;
#define EXP_DELAY 1000
#define EXP_PFD 1500
#define EXP_NOST 0
#define SEND_DEPTH 2
#define RX_SLEEP 0
#define EXP_NOKV 0
#define EXP_NOB 0
#define VOTE 0
#define LATE_TEST 1
#define SM_A 7
#define SM_B 11
#define PF_X 0
#define PF_Q 6
constexpr int PF_G1 = 1;
constexpr int NG0 = 5;

constexpr uint32_t HI_SW128 = 0x40000040u;
constexpr uint32_t LO_A = 1u << 16;
constexpr uint32_t LO_B = 512u << 16;
constexpr uint32_t HI_R = 64u, LO_R = 8u << 16;
constexpr uint32_t HI_K = 24u, LO_K = 8u << 16;
constexpr uint32_t HI_V = 8u, LO_V = 24u << 16;
constexpr uint32_t LO_B48 = 384u << 16;
constexpr uint32_t HI_O = 8u, LO_O = 128u << 16;
constexpr uint32_t HI_SW64 = 0x80000020u;

constexpr float QSCALE = 0.23570226039551584f * 1.4426950408889634f;
constexpr float MOFF = 90.f;

struct __align__(64) Params {
  CUtensorMap xm, wqkv64, wqkv8, wg, wu, kv, wd[3], wo3[3], wo2[3], wo16[3];
  const __nv_bfloat16 *x, *pwqkv, *pwo, *pwg, *pwu, *pwd;
  __nv_bfloat16* out;
};

__device__ __align__(1024) uint32_t g_H[16 * 576 * 512];
__device__ __align__(1024) uint32_t g_O[NCTA * 9 * 512];
__device__ __align__(1024) uint32_t g_KV[32 * SEQ * 20];
__device__ __align__(1024) uint32_t g_Q[NCTA * 4 * 256 * 8];
__device__ __align__(1024) uint4 g_P[NCTA * 3584];
__device__ __align__(1024) uint4 g_L[NCTA * 384];
__device__ float g_S[NCTA * 8 * SEQ];
__device__ uint32_t g_flags[16 * 32 + NCTA * 32 * 4];
#define FLAG_KV(l, j) (&g_flags[((l) * 8 + (j)) * 32])
#define FLAG_H(c) (&g_flags[16 * 32 + (c) * 32])
#define FLAG_O(c) (&g_flags[16 * 32 + NCTA * 32 + (c) * 32])
#define FLAG_P(c) (&g_flags[16 * 32 + NCTA * 64 + (c) * 32])
#define FLAG_EPOCH(c) (&g_flags[16 * 32 + NCTA * 96 + (c) * 32])
#define STAMP(i)
#define STAMPW(i)
#define TRACE()

template<uint32_t AHI, uint32_t BHI> __device__ __forceinline__ void wg_ss_n192(float* d, uint32_t a, uint32_t b) {
  asm volatile("{\n.reg .pred p;\n.reg .b64 da, db;\nsetp.ne.b32 p, 1, 0;\nmov.b64 da, {%96, %98};\nmov.b64 db, {%97, %99};\n"
    "wgmma.mma_async.sync.aligned.m64n192k16.f32.bf16.bf16 {%0, %1, %2, %3, %4, %5, %6, %7, %8, %9, %10, %11, %12, %13, %14, %15, %16, %17, %18, %19, %20, %21, %22, %23, %24, %25, %26, %27, %28, %29, %30, %31, %32, %33, %34, %35, %36, %37, %38, %39, %40, %41, %42, %43, %44, %45, %46, %47, %48, %49, %50, %51, %52, %53, %54, %55, %56, %57, %58, %59, %60, %61, %62, %63, %64, %65, %66, %67, %68, %69, %70, %71, %72, %73, %74, %75, %76, %77, %78, %79, %80, %81, %82, %83, %84, %85, %86, %87, %88, %89, %90, %91, %92, %93, %94, %95}, da, db, p, 1, 1, 0, 1;\n}\n"
    : "+f"(d[0]), "+f"(d[1]), "+f"(d[2]), "+f"(d[3]), "+f"(d[4]), "+f"(d[5]), "+f"(d[6]), "+f"(d[7]), "+f"(d[8]), "+f"(d[9]), "+f"(d[10]), "+f"(d[11]), "+f"(d[12]), "+f"(d[13]), "+f"(d[14]), "+f"(d[15]), "+f"(d[16]), "+f"(d[17]), "+f"(d[18]), "+f"(d[19]), "+f"(d[20]), "+f"(d[21]), "+f"(d[22]), "+f"(d[23]), "+f"(d[24]), "+f"(d[25]), "+f"(d[26]), "+f"(d[27]), "+f"(d[28]), "+f"(d[29]), "+f"(d[30]), "+f"(d[31]), "+f"(d[32]), "+f"(d[33]), "+f"(d[34]), "+f"(d[35]), "+f"(d[36]), "+f"(d[37]), "+f"(d[38]), "+f"(d[39]), "+f"(d[40]), "+f"(d[41]), "+f"(d[42]), "+f"(d[43]), "+f"(d[44]), "+f"(d[45]), "+f"(d[46]), "+f"(d[47]), "+f"(d[48]), "+f"(d[49]), "+f"(d[50]), "+f"(d[51]), "+f"(d[52]), "+f"(d[53]), "+f"(d[54]), "+f"(d[55]), "+f"(d[56]), "+f"(d[57]), "+f"(d[58]), "+f"(d[59]), "+f"(d[60]), "+f"(d[61]), "+f"(d[62]), "+f"(d[63]), "+f"(d[64]), "+f"(d[65]), "+f"(d[66]), "+f"(d[67]), "+f"(d[68]), "+f"(d[69]), "+f"(d[70]), "+f"(d[71]), "+f"(d[72]), "+f"(d[73]), "+f"(d[74]), "+f"(d[75]), "+f"(d[76]), "+f"(d[77]), "+f"(d[78]), "+f"(d[79]), "+f"(d[80]), "+f"(d[81]), "+f"(d[82]), "+f"(d[83]), "+f"(d[84]), "+f"(d[85]), "+f"(d[86]), "+f"(d[87]), "+f"(d[88]), "+f"(d[89]), "+f"(d[90]), "+f"(d[91]), "+f"(d[92]), "+f"(d[93]), "+f"(d[94]), "+f"(d[95])
    : "r"(a), "r"(b), "n"(AHI), "n"(BHI));
}
template<uint32_t AHI, uint32_t BHI> __device__ __forceinline__ void wg_ss_z_n192(float* d, uint32_t a, uint32_t b) {
  asm volatile("{\n.reg .pred p;\n.reg .b64 da, db;\nsetp.ne.b32 p, 0, 0;\nmov.b64 da, {%96, %98};\nmov.b64 db, {%97, %99};\n"
    "wgmma.mma_async.sync.aligned.m64n192k16.f32.bf16.bf16 {%0, %1, %2, %3, %4, %5, %6, %7, %8, %9, %10, %11, %12, %13, %14, %15, %16, %17, %18, %19, %20, %21, %22, %23, %24, %25, %26, %27, %28, %29, %30, %31, %32, %33, %34, %35, %36, %37, %38, %39, %40, %41, %42, %43, %44, %45, %46, %47, %48, %49, %50, %51, %52, %53, %54, %55, %56, %57, %58, %59, %60, %61, %62, %63, %64, %65, %66, %67, %68, %69, %70, %71, %72, %73, %74, %75, %76, %77, %78, %79, %80, %81, %82, %83, %84, %85, %86, %87, %88, %89, %90, %91, %92, %93, %94, %95}, da, db, p, 1, 1, 0, 1;\n}\n"
    : "=f"(d[0]), "=f"(d[1]), "=f"(d[2]), "=f"(d[3]), "=f"(d[4]), "=f"(d[5]), "=f"(d[6]), "=f"(d[7]), "=f"(d[8]), "=f"(d[9]), "=f"(d[10]), "=f"(d[11]), "=f"(d[12]), "=f"(d[13]), "=f"(d[14]), "=f"(d[15]), "=f"(d[16]), "=f"(d[17]), "=f"(d[18]), "=f"(d[19]), "=f"(d[20]), "=f"(d[21]), "=f"(d[22]), "=f"(d[23]), "=f"(d[24]), "=f"(d[25]), "=f"(d[26]), "=f"(d[27]), "=f"(d[28]), "=f"(d[29]), "=f"(d[30]), "=f"(d[31]), "=f"(d[32]), "=f"(d[33]), "=f"(d[34]), "=f"(d[35]), "=f"(d[36]), "=f"(d[37]), "=f"(d[38]), "=f"(d[39]), "=f"(d[40]), "=f"(d[41]), "=f"(d[42]), "=f"(d[43]), "=f"(d[44]), "=f"(d[45]), "=f"(d[46]), "=f"(d[47]), "=f"(d[48]), "=f"(d[49]), "=f"(d[50]), "=f"(d[51]), "=f"(d[52]), "=f"(d[53]), "=f"(d[54]), "=f"(d[55]), "=f"(d[56]), "=f"(d[57]), "=f"(d[58]), "=f"(d[59]), "=f"(d[60]), "=f"(d[61]), "=f"(d[62]), "=f"(d[63]), "=f"(d[64]), "=f"(d[65]), "=f"(d[66]), "=f"(d[67]), "=f"(d[68]), "=f"(d[69]), "=f"(d[70]), "=f"(d[71]), "=f"(d[72]), "=f"(d[73]), "=f"(d[74]), "=f"(d[75]), "=f"(d[76]), "=f"(d[77]), "=f"(d[78]), "=f"(d[79]), "=f"(d[80]), "=f"(d[81]), "=f"(d[82]), "=f"(d[83]), "=f"(d[84]), "=f"(d[85]), "=f"(d[86]), "=f"(d[87]), "=f"(d[88]), "=f"(d[89]), "=f"(d[90]), "=f"(d[91]), "=f"(d[92]), "=f"(d[93]), "=f"(d[94]), "=f"(d[95])
    : "r"(a), "r"(b), "n"(AHI), "n"(BHI));
}
template<uint32_t AHI, uint32_t BHI> __device__ __forceinline__ void wg_ss_n24(float* d, uint32_t a, uint32_t b) {
  asm volatile("{\n.reg .pred p;\n.reg .b64 da, db;\nsetp.ne.b32 p, 1, 0;\nmov.b64 da, {%12, %14};\nmov.b64 db, {%13, %15};\n"
    "wgmma.mma_async.sync.aligned.m64n24k16.f32.bf16.bf16 {%0, %1, %2, %3, %4, %5, %6, %7, %8, %9, %10, %11}, da, db, p, 1, 1, 0, 1;\n}\n"
    : "+f"(d[0]), "+f"(d[1]), "+f"(d[2]), "+f"(d[3]), "+f"(d[4]), "+f"(d[5]), "+f"(d[6]), "+f"(d[7]), "+f"(d[8]), "+f"(d[9]), "+f"(d[10]), "+f"(d[11])
    : "r"(a), "r"(b), "n"(AHI), "n"(BHI));
}
template<uint32_t AHI, uint32_t BHI> __device__ __forceinline__ void wg_ss_z_n24(float* d, uint32_t a, uint32_t b) {
  asm volatile("{\n.reg .pred p;\n.reg .b64 da, db;\nsetp.ne.b32 p, 0, 0;\nmov.b64 da, {%12, %14};\nmov.b64 db, {%13, %15};\n"
    "wgmma.mma_async.sync.aligned.m64n24k16.f32.bf16.bf16 {%0, %1, %2, %3, %4, %5, %6, %7, %8, %9, %10, %11}, da, db, p, 1, 1, 0, 1;\n}\n"
    : "=f"(d[0]), "=f"(d[1]), "=f"(d[2]), "=f"(d[3]), "=f"(d[4]), "=f"(d[5]), "=f"(d[6]), "=f"(d[7]), "=f"(d[8]), "=f"(d[9]), "=f"(d[10]), "=f"(d[11])
    : "r"(a), "r"(b), "n"(AHI), "n"(BHI));
}
template<uint32_t AHI, uint32_t BHI> __device__ __forceinline__ void wg_ss_n128(float* d, uint32_t a, uint32_t b) {
  asm volatile("{\n.reg .pred p;\n.reg .b64 da, db;\nsetp.ne.b32 p, 1, 0;\nmov.b64 da, {%64, %66};\nmov.b64 db, {%65, %67};\n"
    "wgmma.mma_async.sync.aligned.m64n128k16.f32.bf16.bf16 {%0, %1, %2, %3, %4, %5, %6, %7, %8, %9, %10, %11, %12, %13, %14, %15, %16, %17, %18, %19, %20, %21, %22, %23, %24, %25, %26, %27, %28, %29, %30, %31, %32, %33, %34, %35, %36, %37, %38, %39, %40, %41, %42, %43, %44, %45, %46, %47, %48, %49, %50, %51, %52, %53, %54, %55, %56, %57, %58, %59, %60, %61, %62, %63}, da, db, p, 1, 1, 0, 1;\n}\n"
    : "+f"(d[0]), "+f"(d[1]), "+f"(d[2]), "+f"(d[3]), "+f"(d[4]), "+f"(d[5]), "+f"(d[6]), "+f"(d[7]), "+f"(d[8]), "+f"(d[9]), "+f"(d[10]), "+f"(d[11]), "+f"(d[12]), "+f"(d[13]), "+f"(d[14]), "+f"(d[15]), "+f"(d[16]), "+f"(d[17]), "+f"(d[18]), "+f"(d[19]), "+f"(d[20]), "+f"(d[21]), "+f"(d[22]), "+f"(d[23]), "+f"(d[24]), "+f"(d[25]), "+f"(d[26]), "+f"(d[27]), "+f"(d[28]), "+f"(d[29]), "+f"(d[30]), "+f"(d[31]), "+f"(d[32]), "+f"(d[33]), "+f"(d[34]), "+f"(d[35]), "+f"(d[36]), "+f"(d[37]), "+f"(d[38]), "+f"(d[39]), "+f"(d[40]), "+f"(d[41]), "+f"(d[42]), "+f"(d[43]), "+f"(d[44]), "+f"(d[45]), "+f"(d[46]), "+f"(d[47]), "+f"(d[48]), "+f"(d[49]), "+f"(d[50]), "+f"(d[51]), "+f"(d[52]), "+f"(d[53]), "+f"(d[54]), "+f"(d[55]), "+f"(d[56]), "+f"(d[57]), "+f"(d[58]), "+f"(d[59]), "+f"(d[60]), "+f"(d[61]), "+f"(d[62]), "+f"(d[63])
    : "r"(a), "r"(b), "n"(AHI), "n"(BHI));
}
template<uint32_t AHI, uint32_t BHI> __device__ __forceinline__ void wg_ss_z_n128(float* d, uint32_t a, uint32_t b) {
  asm volatile("{\n.reg .pred p;\n.reg .b64 da, db;\nsetp.ne.b32 p, 0, 0;\nmov.b64 da, {%64, %66};\nmov.b64 db, {%65, %67};\n"
    "wgmma.mma_async.sync.aligned.m64n128k16.f32.bf16.bf16 {%0, %1, %2, %3, %4, %5, %6, %7, %8, %9, %10, %11, %12, %13, %14, %15, %16, %17, %18, %19, %20, %21, %22, %23, %24, %25, %26, %27, %28, %29, %30, %31, %32, %33, %34, %35, %36, %37, %38, %39, %40, %41, %42, %43, %44, %45, %46, %47, %48, %49, %50, %51, %52, %53, %54, %55, %56, %57, %58, %59, %60, %61, %62, %63}, da, db, p, 1, 1, 0, 1;\n}\n"
    : "=f"(d[0]), "=f"(d[1]), "=f"(d[2]), "=f"(d[3]), "=f"(d[4]), "=f"(d[5]), "=f"(d[6]), "=f"(d[7]), "=f"(d[8]), "=f"(d[9]), "=f"(d[10]), "=f"(d[11]), "=f"(d[12]), "=f"(d[13]), "=f"(d[14]), "=f"(d[15]), "=f"(d[16]), "=f"(d[17]), "=f"(d[18]), "=f"(d[19]), "=f"(d[20]), "=f"(d[21]), "=f"(d[22]), "=f"(d[23]), "=f"(d[24]), "=f"(d[25]), "=f"(d[26]), "=f"(d[27]), "=f"(d[28]), "=f"(d[29]), "=f"(d[30]), "=f"(d[31]), "=f"(d[32]), "=f"(d[33]), "=f"(d[34]), "=f"(d[35]), "=f"(d[36]), "=f"(d[37]), "=f"(d[38]), "=f"(d[39]), "=f"(d[40]), "=f"(d[41]), "=f"(d[42]), "=f"(d[43]), "=f"(d[44]), "=f"(d[45]), "=f"(d[46]), "=f"(d[47]), "=f"(d[48]), "=f"(d[49]), "=f"(d[50]), "=f"(d[51]), "=f"(d[52]), "=f"(d[53]), "=f"(d[54]), "=f"(d[55]), "=f"(d[56]), "=f"(d[57]), "=f"(d[58]), "=f"(d[59]), "=f"(d[60]), "=f"(d[61]), "=f"(d[62]), "=f"(d[63])
    : "r"(a), "r"(b), "n"(AHI), "n"(BHI));
}
template<uint32_t AHI, uint32_t BHI> __device__ __forceinline__ void wg_ss_n160(float* d, uint32_t a, uint32_t b) {
  asm volatile("{\n.reg .pred p;\n.reg .b64 da, db;\nsetp.ne.b32 p, 1, 0;\nmov.b64 da, {%80, %82};\nmov.b64 db, {%81, %83};\n"
    "wgmma.mma_async.sync.aligned.m64n160k16.f32.bf16.bf16 {%0, %1, %2, %3, %4, %5, %6, %7, %8, %9, %10, %11, %12, %13, %14, %15, %16, %17, %18, %19, %20, %21, %22, %23, %24, %25, %26, %27, %28, %29, %30, %31, %32, %33, %34, %35, %36, %37, %38, %39, %40, %41, %42, %43, %44, %45, %46, %47, %48, %49, %50, %51, %52, %53, %54, %55, %56, %57, %58, %59, %60, %61, %62, %63, %64, %65, %66, %67, %68, %69, %70, %71, %72, %73, %74, %75, %76, %77, %78, %79}, da, db, p, 1, 1, 0, 1;\n}\n"
    : "+f"(d[0]), "+f"(d[1]), "+f"(d[2]), "+f"(d[3]), "+f"(d[4]), "+f"(d[5]), "+f"(d[6]), "+f"(d[7]), "+f"(d[8]), "+f"(d[9]), "+f"(d[10]), "+f"(d[11]), "+f"(d[12]), "+f"(d[13]), "+f"(d[14]), "+f"(d[15]), "+f"(d[16]), "+f"(d[17]), "+f"(d[18]), "+f"(d[19]), "+f"(d[20]), "+f"(d[21]), "+f"(d[22]), "+f"(d[23]), "+f"(d[24]), "+f"(d[25]), "+f"(d[26]), "+f"(d[27]), "+f"(d[28]), "+f"(d[29]), "+f"(d[30]), "+f"(d[31]), "+f"(d[32]), "+f"(d[33]), "+f"(d[34]), "+f"(d[35]), "+f"(d[36]), "+f"(d[37]), "+f"(d[38]), "+f"(d[39]), "+f"(d[40]), "+f"(d[41]), "+f"(d[42]), "+f"(d[43]), "+f"(d[44]), "+f"(d[45]), "+f"(d[46]), "+f"(d[47]), "+f"(d[48]), "+f"(d[49]), "+f"(d[50]), "+f"(d[51]), "+f"(d[52]), "+f"(d[53]), "+f"(d[54]), "+f"(d[55]), "+f"(d[56]), "+f"(d[57]), "+f"(d[58]), "+f"(d[59]), "+f"(d[60]), "+f"(d[61]), "+f"(d[62]), "+f"(d[63]), "+f"(d[64]), "+f"(d[65]), "+f"(d[66]), "+f"(d[67]), "+f"(d[68]), "+f"(d[69]), "+f"(d[70]), "+f"(d[71]), "+f"(d[72]), "+f"(d[73]), "+f"(d[74]), "+f"(d[75]), "+f"(d[76]), "+f"(d[77]), "+f"(d[78]), "+f"(d[79])
    : "r"(a), "r"(b), "n"(AHI), "n"(BHI));
}
template<uint32_t AHI, uint32_t BHI> __device__ __forceinline__ void wg_ss_z_n160(float* d, uint32_t a, uint32_t b) {
  asm volatile("{\n.reg .pred p;\n.reg .b64 da, db;\nsetp.ne.b32 p, 0, 0;\nmov.b64 da, {%80, %82};\nmov.b64 db, {%81, %83};\n"
    "wgmma.mma_async.sync.aligned.m64n160k16.f32.bf16.bf16 {%0, %1, %2, %3, %4, %5, %6, %7, %8, %9, %10, %11, %12, %13, %14, %15, %16, %17, %18, %19, %20, %21, %22, %23, %24, %25, %26, %27, %28, %29, %30, %31, %32, %33, %34, %35, %36, %37, %38, %39, %40, %41, %42, %43, %44, %45, %46, %47, %48, %49, %50, %51, %52, %53, %54, %55, %56, %57, %58, %59, %60, %61, %62, %63, %64, %65, %66, %67, %68, %69, %70, %71, %72, %73, %74, %75, %76, %77, %78, %79}, da, db, p, 1, 1, 0, 1;\n}\n"
    : "=f"(d[0]), "=f"(d[1]), "=f"(d[2]), "=f"(d[3]), "=f"(d[4]), "=f"(d[5]), "=f"(d[6]), "=f"(d[7]), "=f"(d[8]), "=f"(d[9]), "=f"(d[10]), "=f"(d[11]), "=f"(d[12]), "=f"(d[13]), "=f"(d[14]), "=f"(d[15]), "=f"(d[16]), "=f"(d[17]), "=f"(d[18]), "=f"(d[19]), "=f"(d[20]), "=f"(d[21]), "=f"(d[22]), "=f"(d[23]), "=f"(d[24]), "=f"(d[25]), "=f"(d[26]), "=f"(d[27]), "=f"(d[28]), "=f"(d[29]), "=f"(d[30]), "=f"(d[31]), "=f"(d[32]), "=f"(d[33]), "=f"(d[34]), "=f"(d[35]), "=f"(d[36]), "=f"(d[37]), "=f"(d[38]), "=f"(d[39]), "=f"(d[40]), "=f"(d[41]), "=f"(d[42]), "=f"(d[43]), "=f"(d[44]), "=f"(d[45]), "=f"(d[46]), "=f"(d[47]), "=f"(d[48]), "=f"(d[49]), "=f"(d[50]), "=f"(d[51]), "=f"(d[52]), "=f"(d[53]), "=f"(d[54]), "=f"(d[55]), "=f"(d[56]), "=f"(d[57]), "=f"(d[58]), "=f"(d[59]), "=f"(d[60]), "=f"(d[61]), "=f"(d[62]), "=f"(d[63]), "=f"(d[64]), "=f"(d[65]), "=f"(d[66]), "=f"(d[67]), "=f"(d[68]), "=f"(d[69]), "=f"(d[70]), "=f"(d[71]), "=f"(d[72]), "=f"(d[73]), "=f"(d[74]), "=f"(d[75]), "=f"(d[76]), "=f"(d[77]), "=f"(d[78]), "=f"(d[79])
    : "r"(a), "r"(b), "n"(AHI), "n"(BHI));
}
template<uint32_t BHI> __device__ __forceinline__ void wg_rs_n32(float* d, uint32_t a0, uint32_t a1, uint32_t a2, uint32_t a3, uint32_t b) {
  asm volatile("{\n.reg .pred p;\n.reg .b64 db;\nsetp.ne.b32 p, 1, 0;\nmov.b64 db, {%20, %21};\n"
    "wgmma.mma_async.sync.aligned.m64n32k16.f32.bf16.bf16 {%0, %1, %2, %3, %4, %5, %6, %7, %8, %9, %10, %11, %12, %13, %14, %15}, {%16, %17, %18, %19}, db, p, 1, 1, 1;\n}\n"
    : "+f"(d[0]), "+f"(d[1]), "+f"(d[2]), "+f"(d[3]), "+f"(d[4]), "+f"(d[5]), "+f"(d[6]), "+f"(d[7]), "+f"(d[8]), "+f"(d[9]), "+f"(d[10]), "+f"(d[11]), "+f"(d[12]), "+f"(d[13]), "+f"(d[14]), "+f"(d[15])
    : "r"(a0), "r"(a1), "r"(a2), "r"(a3), "r"(b), "n"(BHI));
}
template<uint32_t BHI> __device__ __forceinline__ void wg_rs_z_n32(float* d, uint32_t a0, uint32_t a1, uint32_t a2, uint32_t a3, uint32_t b) {
  asm volatile("{\n.reg .pred p;\n.reg .b64 db;\nsetp.ne.b32 p, 0, 0;\nmov.b64 db, {%20, %21};\n"
    "wgmma.mma_async.sync.aligned.m64n32k16.f32.bf16.bf16 {%0, %1, %2, %3, %4, %5, %6, %7, %8, %9, %10, %11, %12, %13, %14, %15}, {%16, %17, %18, %19}, db, p, 1, 1, 1;\n}\n"
    : "=f"(d[0]), "=f"(d[1]), "=f"(d[2]), "=f"(d[3]), "=f"(d[4]), "=f"(d[5]), "=f"(d[6]), "=f"(d[7]), "=f"(d[8]), "=f"(d[9]), "=f"(d[10]), "=f"(d[11]), "=f"(d[12]), "=f"(d[13]), "=f"(d[14]), "=f"(d[15])
    : "r"(a0), "r"(a1), "r"(a2), "r"(a3), "r"(b), "n"(BHI));
}
template<uint32_t BHI> __device__ __forceinline__ void wg_rs_n64(float* d, uint32_t a0, uint32_t a1, uint32_t a2, uint32_t a3, uint32_t b) {
  asm volatile("{\n.reg .pred p;\n.reg .b64 db;\nsetp.ne.b32 p, 1, 0;\nmov.b64 db, {%36, %37};\n"
    "wgmma.mma_async.sync.aligned.m64n64k16.f32.bf16.bf16 {%0, %1, %2, %3, %4, %5, %6, %7, %8, %9, %10, %11, %12, %13, %14, %15, %16, %17, %18, %19, %20, %21, %22, %23, %24, %25, %26, %27, %28, %29, %30, %31}, {%32, %33, %34, %35}, db, p, 1, 1, 0;\n}\n"
    : "+f"(d[0]), "+f"(d[1]), "+f"(d[2]), "+f"(d[3]), "+f"(d[4]), "+f"(d[5]), "+f"(d[6]), "+f"(d[7]), "+f"(d[8]), "+f"(d[9]), "+f"(d[10]), "+f"(d[11]), "+f"(d[12]), "+f"(d[13]), "+f"(d[14]), "+f"(d[15]), "+f"(d[16]), "+f"(d[17]), "+f"(d[18]), "+f"(d[19]), "+f"(d[20]), "+f"(d[21]), "+f"(d[22]), "+f"(d[23]), "+f"(d[24]), "+f"(d[25]), "+f"(d[26]), "+f"(d[27]), "+f"(d[28]), "+f"(d[29]), "+f"(d[30]), "+f"(d[31])
    : "r"(a0), "r"(a1), "r"(a2), "r"(a3), "r"(b), "n"(BHI));
}
template<uint32_t BHI> __device__ __forceinline__ void wg_rs_z_n64(float* d, uint32_t a0, uint32_t a1, uint32_t a2, uint32_t a3, uint32_t b) {
  asm volatile("{\n.reg .pred p;\n.reg .b64 db;\nsetp.ne.b32 p, 0, 0;\nmov.b64 db, {%36, %37};\n"
    "wgmma.mma_async.sync.aligned.m64n64k16.f32.bf16.bf16 {%0, %1, %2, %3, %4, %5, %6, %7, %8, %9, %10, %11, %12, %13, %14, %15, %16, %17, %18, %19, %20, %21, %22, %23, %24, %25, %26, %27, %28, %29, %30, %31}, {%32, %33, %34, %35}, db, p, 1, 1, 0;\n}\n"
    : "=f"(d[0]), "=f"(d[1]), "=f"(d[2]), "=f"(d[3]), "=f"(d[4]), "=f"(d[5]), "=f"(d[6]), "=f"(d[7]), "=f"(d[8]), "=f"(d[9]), "=f"(d[10]), "=f"(d[11]), "=f"(d[12]), "=f"(d[13]), "=f"(d[14]), "=f"(d[15]), "=f"(d[16]), "=f"(d[17]), "=f"(d[18]), "=f"(d[19]), "=f"(d[20]), "=f"(d[21]), "=f"(d[22]), "=f"(d[23]), "=f"(d[24]), "=f"(d[25]), "=f"(d[26]), "=f"(d[27]), "=f"(d[28]), "=f"(d[29]), "=f"(d[30]), "=f"(d[31])
    : "r"(a0), "r"(a1), "r"(a2), "r"(a3), "r"(b), "n"(BHI));
}
template<uint32_t BHI> __device__ __forceinline__ void wg_rs_n24(float* d, uint32_t a0, uint32_t a1, uint32_t a2, uint32_t a3, uint32_t b) {
  asm volatile("{\n.reg .pred p;\n.reg .b64 db;\nsetp.ne.b32 p, 1, 0;\nmov.b64 db, {%16, %17};\n"
    "wgmma.mma_async.sync.aligned.m64n24k16.f32.bf16.bf16 {%0, %1, %2, %3, %4, %5, %6, %7, %8, %9, %10, %11}, {%12, %13, %14, %15}, db, p, 1, 1, 1;\n}\n"
    : "+f"(d[0]), "+f"(d[1]), "+f"(d[2]), "+f"(d[3]), "+f"(d[4]), "+f"(d[5]), "+f"(d[6]), "+f"(d[7]), "+f"(d[8]), "+f"(d[9]), "+f"(d[10]), "+f"(d[11])
    : "r"(a0), "r"(a1), "r"(a2), "r"(a3), "r"(b), "n"(BHI));
}
template<uint32_t BHI> __device__ __forceinline__ void wg_rs_z_n24(float* d, uint32_t a0, uint32_t a1, uint32_t a2, uint32_t a3, uint32_t b) {
  asm volatile("{\n.reg .pred p;\n.reg .b64 db;\nsetp.ne.b32 p, 0, 0;\nmov.b64 db, {%16, %17};\n"
    "wgmma.mma_async.sync.aligned.m64n24k16.f32.bf16.bf16 {%0, %1, %2, %3, %4, %5, %6, %7, %8, %9, %10, %11}, {%12, %13, %14, %15}, db, p, 1, 1, 1;\n}\n"
    : "=f"(d[0]), "=f"(d[1]), "=f"(d[2]), "=f"(d[3]), "=f"(d[4]), "=f"(d[5]), "=f"(d[6]), "=f"(d[7]), "=f"(d[8]), "=f"(d[9]), "=f"(d[10]), "=f"(d[11])
    : "r"(a0), "r"(a1), "r"(a2), "r"(a3), "r"(b), "n"(BHI));
}
template<uint32_t BHI> __device__ __forceinline__ void wg_rsb_n64(float* d, uint32_t a0, uint32_t a1, uint32_t a2, uint32_t a3, uint32_t b) {
  asm volatile("{\n.reg .pred p;\n.reg .b64 db;\nsetp.ne.b32 p, 1, 0;\nmov.b64 db, {%36, %37};\n"
    "wgmma.mma_async.sync.aligned.m64n64k16.f32.bf16.bf16 {%0, %1, %2, %3, %4, %5, %6, %7, %8, %9, %10, %11, %12, %13, %14, %15, %16, %17, %18, %19, %20, %21, %22, %23, %24, %25, %26, %27, %28, %29, %30, %31}, {%32, %33, %34, %35}, db, p, 1, 1, 1;\n}\n"
    : "+f"(d[0]), "+f"(d[1]), "+f"(d[2]), "+f"(d[3]), "+f"(d[4]), "+f"(d[5]), "+f"(d[6]), "+f"(d[7]), "+f"(d[8]), "+f"(d[9]), "+f"(d[10]), "+f"(d[11]), "+f"(d[12]), "+f"(d[13]), "+f"(d[14]), "+f"(d[15]), "+f"(d[16]), "+f"(d[17]), "+f"(d[18]), "+f"(d[19]), "+f"(d[20]), "+f"(d[21]), "+f"(d[22]), "+f"(d[23]), "+f"(d[24]), "+f"(d[25]), "+f"(d[26]), "+f"(d[27]), "+f"(d[28]), "+f"(d[29]), "+f"(d[30]), "+f"(d[31])
    : "r"(a0), "r"(a1), "r"(a2), "r"(a3), "r"(b), "n"(BHI));
}
template<uint32_t BHI> __device__ __forceinline__ void wg_rsb_z_n64(float* d, uint32_t a0, uint32_t a1, uint32_t a2, uint32_t a3, uint32_t b) {
  asm volatile("{\n.reg .pred p;\n.reg .b64 db;\nsetp.ne.b32 p, 0, 0;\nmov.b64 db, {%36, %37};\n"
    "wgmma.mma_async.sync.aligned.m64n64k16.f32.bf16.bf16 {%0, %1, %2, %3, %4, %5, %6, %7, %8, %9, %10, %11, %12, %13, %14, %15, %16, %17, %18, %19, %20, %21, %22, %23, %24, %25, %26, %27, %28, %29, %30, %31}, {%32, %33, %34, %35}, db, p, 1, 1, 1;\n}\n"
    : "=f"(d[0]), "=f"(d[1]), "=f"(d[2]), "=f"(d[3]), "=f"(d[4]), "=f"(d[5]), "=f"(d[6]), "=f"(d[7]), "=f"(d[8]), "=f"(d[9]), "=f"(d[10]), "=f"(d[11]), "=f"(d[12]), "=f"(d[13]), "=f"(d[14]), "=f"(d[15]), "=f"(d[16]), "=f"(d[17]), "=f"(d[18]), "=f"(d[19]), "=f"(d[20]), "=f"(d[21]), "=f"(d[22]), "=f"(d[23]), "=f"(d[24]), "=f"(d[25]), "=f"(d[26]), "=f"(d[27]), "=f"(d[28]), "=f"(d[29]), "=f"(d[30]), "=f"(d[31])
    : "r"(a0), "r"(a1), "r"(a2), "r"(a3), "r"(b), "n"(BHI));
}

__device__ __forceinline__ void wg_fence() { asm volatile("wgmma.fence.sync.aligned;" ::: "memory"); }
__device__ __forceinline__ void wg_commit() { asm volatile("wgmma.commit_group.sync.aligned;" ::: "memory"); }
template <int N> __device__ __forceinline__ void wg_wait() { asm volatile("wgmma.wait_group.sync.aligned %0;" ::"n"(N) : "memory"); }
template <int R> __device__ __forceinline__ void pin(float* d) {
#pragma unroll
  for (int i = 0; i < R; i++) asm volatile("" : "+f"(d[i])::"memory");
}
template <int R> __device__ __forceinline__ void pin(uint32_t* d) {
#pragma unroll
  for (int i = 0; i < R; i++) asm volatile("" : "+r"(d[i])::"memory");
}
__device__ __forceinline__ float ex2(float x) { float y; asm("ex2.approx.ftz.f32 %0, %1;" : "=f"(y) : "f"(x)); return y; }
__device__ __forceinline__ float tanh_fast(float x) { float y; asm("tanh.approx.f32 %0, %1;" : "=f"(y) : "f"(x)); return y; }
__device__ __forceinline__ uint32_t pack(float lo, float hi) { uint32_t r; asm("cvt.rn.bf16x2.f32 %0, %1, %2;" : "=r"(r) : "f"(hi), "f"(lo)); return r; }
__device__ __forceinline__ float bf_lo(uint32_t v) { return __uint_as_float(v << 16); }
__device__ __forceinline__ float bf_hi(uint32_t v) { return __uint_as_float(v & 0xffff0000u); }
__device__ __forceinline__ float bf_round(float x) { return bf_lo(pack(x, 0.f)); }

__device__ __forceinline__ void mbar_init(uint32_t bar, uint32_t cnt) { asm volatile("mbarrier.init.shared::cta.b64 [%0], %1;" ::"r"(bar), "r"(cnt) : "memory"); }
__device__ __forceinline__ void mbar_expect(uint32_t bar, uint32_t bytes) { asm volatile("mbarrier.arrive.expect_tx.shared::cta.b64 _, [%0], %1;" ::"r"(bar), "r"(bytes) : "memory"); }
__device__ __forceinline__ void mbar_wait(uint32_t bar, uint32_t parity) {
  asm volatile(
      "{\n.reg .pred p;\n.reg .u32 c;\n"
      "mbarrier.try_wait.parity.shared::cta.b64 p, [%0], %1;\n"
      "@p bra.uni DONE;\n"
      "mov.u32 c, 0;\n"
      "LOOP:\n"
      "mbarrier.try_wait.parity.shared::cta.b64 p, [%0], %1;\n"
      "@p bra.uni DONE;\n"
      "add.u32 c, c, 1;\n"
      "setp.lt.u32 p, c, 0x4000000;\n"
      "@p bra.uni LOOP;\n"
      "trap;\n"
      "DONE:\n}\n" ::"r"(bar), "r"(parity) : "memory");
}
__device__ __forceinline__ uint32_t mbar_test(uint32_t bar, uint32_t parity) {
  uint32_t ok;
  asm volatile("{\n.reg .pred p;\nmbarrier.test_wait.parity.shared::cta.b64 p, [%1], %2;\nselp.u32 %0, 1, 0, p;\n}\n" : "=r"(ok) : "r"(bar), "r"(parity) : "memory");
  return ok;
}
__device__ __forceinline__ void mbar_arrive_if(uint32_t bar, uint32_t cond) {
  asm volatile("{\n.reg .pred p;\nsetp.ne.u32 p, %1, 0;\n@p mbarrier.arrive.shared::cta.b64 _, [%0];\n}\n" ::"r"(bar), "r"(cond) : "memory");
}
__device__ __forceinline__ uint32_t bsub2(uint32_t a, uint32_t b) { uint32_t d; asm("sub.rn.bf16x2 %0, %1, %2;" : "=r"(d) : "r"(a), "r"(b)); return d; }
__device__ __forceinline__ uint32_t bscale2(uint32_t d, uint32_t hi, uint32_t lo) {
  uint32_t t, r;
  asm("mul.rn.bf16x2 %0, %1, %2;" : "=r"(t) : "r"(d), "r"(lo));
  asm("fma.rn.bf16x2 %0, %1, %2, %3;" : "=r"(r) : "r"(d), "r"(hi), "r"(t));
  return r;
}
__device__ __forceinline__ void flag_wait(const uint32_t* f, uint32_t target) {
  asm volatile(
      "{\n.reg .pred p;\n.reg .u32 c, v;\n"
      "mov.u32 c, 0;\n"
      "LOOP:\n"
      "ld.acquire.gpu.global.u32 v, [%0];\n"
      "sub.u32 v, v, %1;\n"
      "setp.ge.s32 p, v, 0;\n"
      "@p bra DONE;\n"
      "add.u32 c, c, 1;\n"
      "setp.lt.u32 p, c, 0x1000000;\n"
      "@p bra LOOP;\n"
      "trap;\n"
      "DONE:\n}\n" ::"l"(f), "r"(target) : "memory");
}
__device__ __forceinline__ uint32_t flag_wait_v(const uint32_t* f, uint32_t target) {
  uint32_t v;
  asm volatile(
      "{\n.reg .pred p;\n.reg .u32 c, d;\n"
      "mov.u32 c, 0;\n"
      "LOOP:\n"
      "ld.acquire.gpu.global.u32 %0, [%1];\n"
      "sub.u32 d, %0, %2;\n"
      "setp.ge.s32 p, d, 0;\n"
      "@p bra DONE;\n"
      "add.u32 c, c, 1;\n"
      "setp.lt.u32 p, c, 0x1000000;\n"
      "@p bra LOOP;\n"
      "trap;\n"
      "DONE:\n}\n" : "=&r"(v) : "l"(f), "r"(target) : "memory");
  return v;
}
__device__ __forceinline__ float sqrt_fast(float x) { float y; asm("sqrt.approx.f32 %0, %1;" : "=f"(y) : "f"(x)); return y; }
__device__ __forceinline__ float rcp_fast(float x) { float y; asm("rcp.approx.ftz.f32 %0, %1;" : "=f"(y) : "f"(x)); return y; }
__device__ __forceinline__ void ldsm4(uint32_t* v, uint32_t addr) {
  asm volatile("ldmatrix.sync.aligned.m8n8.x4.shared.b16 {%0,%1,%2,%3}, [%4];" : "=r"(v[0]), "=r"(v[1]), "=r"(v[2]), "=r"(v[3]) : "r"(addr) : "memory");
}
__device__ __forceinline__ void stsm4(uint32_t addr, uint32_t a, uint32_t b, uint32_t c, uint32_t d) {
  asm volatile("stmatrix.sync.aligned.m8n8.x4.shared.b16 [%0], {%1,%2,%3,%4};" ::"r"(addr), "r"(a), "r"(b), "r"(c), "r"(d) : "memory");
}
__device__ __forceinline__ void flag_add(uint32_t* f) { asm volatile("red.relaxed.gpu.global.add.u32 [%0], 1;" ::"l"(f) : "memory"); }
__device__ __forceinline__ void fence_gpu() { asm volatile("fence.acq_rel.gpu;" ::: "memory"); }
#define FENCE_G 1
__device__ __forceinline__ void fence_async() { if (FENCE_G) asm volatile("fence.proxy.async.global;" ::: "memory"); else asm volatile("fence.proxy.async;" ::: "memory"); }
__device__ __forceinline__ void tma2d(uint32_t dst, const CUtensorMap* tm, uint32_t bar, int c0, int c1) {
  asm volatile("cp.async.bulk.tensor.2d.shared::cluster.global.mbarrier::complete_tx::bytes [%0], [%1, {%3, %4}], [%2];" ::"r"(dst), "l"(tm), "r"(bar), "r"(c0), "r"(c1) : "memory");
}
__device__ __forceinline__ void tma2d_h(uint32_t dst, const CUtensorMap* tm, uint32_t bar, int c0, int c1, uint64_t pol) {
  asm volatile("cp.async.bulk.tensor.2d.shared::cluster.global.mbarrier::complete_tx::bytes.L2::cache_hint [%0], [%1, {%3, %4}], [%2], %5;" ::"r"(dst), "l"(tm), "r"(bar), "r"(c0), "r"(c1), "l"(pol) : "memory");
}
__device__ __forceinline__ void bulk_s2g(void* dst, uint32_t src, uint32_t bytes) {
  asm volatile("cp.async.bulk.global.shared::cta.bulk_group [%0], [%1], %2;" ::"l"(dst), "r"(src), "r"(bytes) : "memory");
}
__device__ __forceinline__ void mma_ones(float* c, const uint32_t* a) {
  asm("mma.sync.aligned.m16n8k16.row.col.f32.bf16.bf16.f32 {%0,%1,%2,%3}, {%4,%5,%6,%7}, {%8,%8}, {%0,%1,%2,%3};"
      : "+f"(c[0]), "+f"(c[1]), "+f"(c[2]), "+f"(c[3]) : "r"(a[0]), "r"(a[1]), "r"(a[2]), "r"(a[3]), "r"(0x3f803f80u));
}
__device__ __forceinline__ void tma5d(uint32_t dst, const CUtensorMap* tm, uint32_t bar, int c0, int c4) {
  asm volatile("cp.async.bulk.tensor.5d.shared::cluster.global.mbarrier::complete_tx::bytes [%0], [%1, {%3, %5, %5, %5, %4}], [%2];" ::"r"(dst), "l"(tm), "r"(bar), "r"(c0), "r"(c4), "r"(0) : "memory");
}
__device__ __forceinline__ void tma3d(uint32_t dst, const CUtensorMap* tm, uint32_t bar, int c0, int c2) {
  asm volatile("cp.async.bulk.tensor.3d.shared::cluster.global.mbarrier::complete_tx::bytes [%0], [%1, {%3, %5, %4}], [%2];" ::"r"(dst), "l"(tm), "r"(bar), "r"(c0), "r"(c2), "r"(0) : "memory");
}
__device__ __forceinline__ void bulk_g2s(uint32_t dst, const void* src, uint32_t bytes, uint32_t bar) {
  asm volatile("cp.async.bulk.shared::cluster.global.mbarrier::complete_tx::bytes [%0], [%1], %2, [%3];" ::"r"(dst), "l"(src), "r"(bytes), "r"(bar) : "memory");
}
__device__ __forceinline__ void pf_line(const void* p) { asm volatile("prefetch.global.L2 [%0];" ::"l"(p) : "memory"); }
__device__ __forceinline__ int fresh_tid() { int v; asm volatile("mov.u32 %0, %%tid.x;" : "=r"(v)); return v; }
struct Att {
  float s[32];
  float o[12];
  uint32_t p[16];
  uint32_t q[8];
};

__device__ __forceinline__ float warp_sum(float v) {
#pragma unroll 1
  for (int d = 16; d; d >>= 1) v += __shfl_xor_sync(0xffffffffu, v, d);
  return v;
}
#define OPAQUE(x) asm volatile("" : "+r"(x))
__device__ __forceinline__ void attn_slow_row(int cta, uint32_t& w) {
  float mx = -INFINITY;
#pragma unroll 1
  for (uint32_t key = threadIdx.x & 31; key < SEQ; key += 32) {
    float s = 0.f;
#pragma unroll 1
    for (uint32_t v = 0; v < 9; v++) {
      OPAQUE(w); OPAQUE(key);
      const uint32_t hp = (w >> 4) & 3, pos = (v + hp) & 3;
      const uint32_t q = g_Q[(((cta * 4 + hp) * 2 + (v >> 3)) * 256 + ((w >> 6) & 7) * 32 + (w & 7) * 4 + pos) * 4 + 2 * ((v >> 2) & 1) + ((w >> 3) & 1)];
      const uint32_t u = g_KV[(4 * (cta & 7) + hp) * SEQ * 20 + (key >> 3) * 160 + (key & 7) * 4 + (v >> 2) * 32 + pos];
      s = fmaf(bf_lo(q), bf_lo(u), fmaf(bf_hi(q), bf_hi(u), s));
    }
    g_S[(cta * 8 + ((w >> 6) & 7)) * SEQ + key] = s;
    mx = fmaxf(mx, s);
  }
#pragma unroll 1
  for (int d = 16; d; d >>= 1) mx = fmaxf(mx, __shfl_xor_sync(0xffffffffu, mx, d));
  float l = 0.f;
#pragma unroll 1
  for (uint32_t key = threadIdx.x & 31; key < SEQ; key += 32) l += ex2(g_S[(cta * 8 + ((w >> 6) & 7)) * SEQ + key] - mx);
  l = 2.f * rcp_fast(warp_sum(l));
#pragma unroll 1
  for (uint32_t v = w >> 9; v < 9; v++) {
    float a = 0.f, b = 0.f;
#pragma unroll 1
    for (uint32_t key = threadIdx.x & 31; key < SEQ; key += 32) {
      OPAQUE(w); OPAQUE(v);
      const uint32_t hp = (w >> 4) & 3;
      const uint32_t u = g_KV[(4 * (cta & 7) + hp) * SEQ * 20 + (key >> 3) * 160 + (key & 7) * 4 + (v < 8 ? (3 + (v >> 2)) * 32 + (v & 3) : 64 + ((hp + 2) & 3))];
      const float p = ex2(g_S[(cta * 8 + ((w >> 6) & 7)) * SEQ + key] - mx);
      a = fmaf(p, bf_lo(u), a); b = fmaf(p, bf_hi(u), b);
    }
    a = warp_sum(a); b = warp_sum(b);
    OPAQUE(w);
    const uint32_t hp = (w >> 4) & 3;
    if ((threadIdx.x & 31) == 0) g_O[cta * 9 * 512 + (((w >> 6) & 7) * 16 + (w & 15)) * 4 + (v < 8 ? (2 * hp + (v >> 2)) * 512 + (v & 3) : 8 * 512 + hp)] = pack(a * l, b * l);
  }
}

__device__ __forceinline__ uint32_t bad_heads(uint32_t bad_addr, int wr) {
  uint32_t bad;
  __syncwarp();
  asm volatile("ld.volatile.shared.u32 %0, [%1];" : "=r"(bad) : "r"(bad_addr) : "memory");
  return __shfl_sync(0xffffffffu, (bad >> (4 * wr)) & 15, 0);
}
__device__ __forceinline__ void repair_rows(int cta, int wr, uint32_t bad, int last_head, bool final) {
#pragma unroll 1
  for (uint32_t w = wr * 64; w < wr * 64 + 64; w++) {
    if (!((bad >> ((w >> 4) & 3)) & 1)) continue;
    if (final && ((w >> 4) & 3) != last_head) w |= 8u << 9;
    attn_slow_row(cta, w);
    w &= 511;
  }
  __syncwarp();
}
__device__ __forceinline__ void o_normalise(const float* o, uint32_t* w, uint32_t& x0, uint32_t& x1, int hp, int lane, uint32_t bad_addr, int wr) {
  const int src = (lane & ~3) | ((hp + 1) & 3);
  float l0 = __shfl_sync(0xffffffffu, o[0], src), l1 = __shfl_sync(0xffffffffu, o[2], src);
  float sa = 0.f;
#pragma unroll
  for (int i = 0; i < 12; i++) sa += fabsf(o[i]);
  bool ok = (l0 <= 1.329228e36f) && (l1 <= 1.329228e36f) && (l0 > 0.f) && (l1 > 0.f) && (sa <= 3.0e38f);
  float i0 = 2.f * rcp_fast(l0), i1 = 2.f * rcp_fast(l1);
  w[0] = pack(o[4] * i0, o[5] * i0);
  w[1] = pack(o[6] * i1, o[7] * i1);
  w[2] = pack(o[8] * i0, o[9] * i0);
  w[3] = pack(o[10] * i1, o[11] * i1);
  if ((lane & 3) == ((hp + 2) & 3)) { x0 = pack(o[0] * i0, o[1] * i0); x1 = pack(o[2] * i1, o[3] * i1); }
  if (!ok) asm volatile("red.shared.or.b32 [%0], %1;" ::"r"(bad_addr), "r"(1u << (4 * wr + hp)) : "memory");
}

__device__ __forceinline__ void issue_pv(Att& a, uint32_t kdesc) {
  const uint32_t vdesc = kdesc + 192 + (LO_V - LO_K);
#pragma unroll
  for (int k = 0; k < 4; k++) wg_rs_n24<HI_V>(a.o, a.p[4 * k], a.p[4 * k + 1], a.p[4 * k + 2], a.p[4 * k + 3], vdesc + k * 48);
}
__device__ __forceinline__ void issue_att(Att& a, uint32_t kdesc) {
  issue_pv(a, kdesc);
  wg_rs_z_n64<HI_K>(a.s, a.q[0], a.q[1], a.q[2], a.q[3], kdesc);
  wg_rs_n64<HI_K>(a.s, a.q[4], a.q[5], a.q[6], a.q[7], kdesc + 16);
}
__device__ __forceinline__ void softmax_a(Att& a) {
#pragma unroll
  for (int i = 0; i < SM_A; i++) a.p[i] = pack(ex2(a.s[2 * i]), ex2(a.s[2 * i + 1]));
  pin<SM_A>(a.p);
}
__device__ __forceinline__ void softmax_b(Att& a) {
#pragma unroll
  for (int i = SM_A; i < SM_B; i++) a.p[i] = pack(ex2(a.s[2 * i]), ex2(a.s[2 * i + 1]));
  a.s[2 * SM_B] = ex2(a.s[2 * SM_B]); a.s[2 * SM_B + 1] = ex2(a.s[2 * SM_B + 1]);
  pin<SM_B - SM_A>(a.p + SM_A); pin<2>(a.s + 2 * SM_B);
}
__device__ __forceinline__ void softmax_c(Att& a) {
  a.p[SM_B] = pack(a.s[2 * SM_B], a.s[2 * SM_B + 1]);
#pragma unroll
  for (int i = SM_B + 1; i < 16; i++) a.p[i] = pack(ex2(a.s[2 * i]), ex2(a.s[2 * i + 1]));
  pin<16 - SM_B>(a.p + SM_B);
}
__device__ __forceinline__ void first_tile(Att& a, int hp, int lane) {
  float m0 = fmaxf(a.s[0], a.s[1]), m1 = fmaxf(a.s[2], a.s[3]);
#pragma unroll
  for (int i = 4; i < 32; i += 4) { m0 = fmaxf(m0, fmaxf(a.s[i], a.s[i + 1])); m1 = fmaxf(m1, fmaxf(a.s[i + 2], a.s[i + 3])); }
  m0 = fmaxf(m0, __shfl_xor_sync(0xffffffffu, m0, 1)); m1 = fmaxf(m1, __shfl_xor_sync(0xffffffffu, m1, 1));
  m0 = fmaxf(m0, __shfl_xor_sync(0xffffffffu, m0, 2)); m1 = fmaxf(m1, __shfl_xor_sync(0xffffffffu, m1, 2));
  float n0 = -(m0 + MOFF), n1 = -(m1 + MOFF);
  float h0 = bf_round(n0), h1 = bf_round(n1);
  uint32_t e0 = pack(h0, n0 - h0), e1 = pack(h1, n1 - h1);
  n0 = h0 + bf_hi(e0); n1 = h1 + bf_hi(e1);
  if ((lane & 3) == ((hp + 1) & 3)) { a.q[4] = e0; a.q[5] = e1; }
#pragma unroll
  for (int i = 0; i < 32; i += 4) { a.s[i] += n0; a.s[i + 1] += n0; a.s[i + 2] += n1; a.s[i + 3] += n1; }
#pragma unroll
  for (int i = 0; i < 12; i++) a.o[i] = 0.f;
  pin<12>(a.o); pin<8>(a.q);
}
__device__ __forceinline__ void fetch_q(uint32_t* q, int cta, int hp, int tid) {
  const uint4* src = reinterpret_cast<const uint4*>(g_Q) + (cta * 4 + hp) * 512 + tid;
  const uint4 u = __ldcg(src);
  const uint2 v = __ldcg(reinterpret_cast<const uint2*>(src + 256));
  q[0] = u.x; q[1] = u.y; q[2] = u.z; q[3] = u.w; q[4] = v.x; q[5] = v.y;
}
__device__ __forceinline__ void h_epilogue(const float* acc, uint32_t* dst) {
#pragma unroll
  for (int b = 0; b < 4; b++) {
    uint32_t w[2][2];
#pragma unroll
    for (int i = 0; i < 2; i++) {
      float h[4];
#pragma unroll
      for (int e = 0; e < 4; e++) {
        const float g = acc[(2 * b + i) * 4 + e], u = acc[32 + (2 * b + i) * 4 + e];
        h[e] = fmaf(tanh_fast(0.5f * g), u, u);
      }
      w[0][i] = pack(h[0], h[1]); w[1][i] = pack(h[2], h[3]);
    }
    if (!EXP_NOST || w[0][0] == 0x12345678) {
    *reinterpret_cast<uint2*>(dst + 1024 * b) = make_uint2(w[0][0], w[0][1]);
    *reinterpret_cast<uint2*>(dst + 1024 * b + 32) = make_uint2(w[1][0], w[1][1]);
    }
  }
}
__device__ __forceinline__ void rotate9(uint32_t (&v)[9][2]) {
#pragma unroll
  for (int rh = 0; rh < 2; rh++) {
    const uint32_t r = v[8][rh];
#pragma unroll
    for (int i = 8; i > 0; i--) v[i][rh] = v[i - 1][rh];
    v[0][rh] = r;
  }
}
template <int HP> __device__ __forceinline__ void store_kv_head(uint32_t (&pk)[2][9][2], uint32_t* kvp, int lane) {
  const int t = lane & 3;
  const bool up = t < HP;
#pragma unroll
  for (int rh = 0; rh < 2; rh++) {
    uint32_t* d = kvp + HP * SEQ * 20 + rh * 160;
    d[0] = up ? pk[0][2 * HP + 1][rh] : pk[0][2 * HP][rh];
    d[32] = up ? pk[0][2 * HP + 2][rh] : pk[0][2 * HP + 1][rh];
    d[96 + ((t - HP) & 3) - t] = up ? pk[1][2 * HP + 1][rh] : pk[1][2 * HP][rh];
    d[128 + ((t - HP) & 3) - t] = up ? pk[1][2 * HP + 2][rh] : pk[1][2 * HP + 1][rh];
    const uint32_t v9 = __shfl_sync(0xffffffffu, pk[1][2 * HP + 2][rh], (lane & ~3) | HP);
    d[64] = t == HP ? pk[0][2 * HP + 2][rh] : t == ((HP + 1) & 3) ? 0x3f803f80u : t == ((HP + 2) & 3) ? v9 : 0u;
  }
}

template <int OFF> __device__ __forceinline__ void ld4(uint32_t* v, const void* p) {
  asm volatile("ld.relaxed.gpu.global.v4.b32 {%0,%1,%2,%3}, [%4 + %5];" : "=r"(v[0]), "=r"(v[1]), "=r"(v[2]), "=r"(v[3]) : "l"(p), "n"(OFF) : "memory");
}
template <int OFF> __device__ __forceinline__ void ld2(uint32_t* v, const void* p) {
  asm volatile("ld.relaxed.gpu.global.v2.b32 {%0,%1}, [%2 + %3];" : "=r"(v[0]), "=r"(v[1]) : "l"(p), "n"(OFF) : "memory");
}
__device__ __forceinline__ void stage_partials(const float* acc, uint32_t dst, int tid) {
  const int lane = tid & 31, row = (tid >> 5) * 16 + (lane & 15);
  const uint32_t r128 = dst + row * 128, r64 = dst + 49152 + row * 64;
#pragma unroll
  for (int i = 0; i < 12; i++) {
    const float* v = acc + 8 * i;
    stsm4(r128 + (i >> 2) * 16384 + (((2 * (i & 3) + (lane >> 4)) ^ (row & 7)) << 4), pack(v[0], v[1]), pack(v[2], v[3]), pack(v[4], v[5]), pack(v[6], v[7]));
  }
#pragma unroll
  for (int i = 0; i < 2; i++) {
    const float* v = acc + 128 + 8 * i;
    stsm4(r64 + (((2 * i + (lane >> 4)) ^ ((row >> 1) & 3)) << 4), pack(v[0], v[1]), pack(v[2], v[3]), pack(v[4], v[5]), pack(v[6], v[7]));
  }
}
__device__ __forceinline__ void final_epilogue(const float* acc, const Params& prm, int m, int hh, int q, int tid) {
  uint32_t r[18];
#pragma unroll
  for (int i = 0; i < 16; i++) r[i] = pack(acc[2 * i] * 0.5f, acc[2 * i + 1] * 0.5f);
#pragma unroll
  for (int i = 0; i < 2; i++) {
    const int o = 32 + 4 * i;
    const float a0 = (q & 2) ? acc[o + 2] : acc[o], a1 = (q & 2) ? acc[o + 10] : acc[o + 8];
    const float b0 = (q & 2) ? acc[o + 3] : acc[o + 1], b1 = (q & 2) ? acc[o + 11] : acc[o + 9];
    r[16 + i] = pack(((q & 1) ? a1 : a0) * 0.5f, ((q & 1) ? b1 : b0) * 0.5f);
  }
  const size_t off = (size_t)(128 * m + (tid >> 5) * 16 + ((tid & 31) >> 2)) * DM + 2 * (tid & 3);
  const bool odd = tid & 1;
  uint32_t* o1 = reinterpret_cast<uint32_t*>(prm.out + off + 320 * hh + 64 * q) + (odd ? 3 : 0);
  uint32_t* o2 = reinterpret_cast<uint32_t*>(prm.out + off + 256 + 32 * hh + 16 * (q & 1) + (q >> 1) * 8 * DM) + (odd ? 3 : 0);
#pragma unroll
  for (int i = 0; i < 9; i++) {
    const uint32_t A = i < 8 ? r[4 * (i >> 1) + (i & 1)] : r[16], B = i < 8 ? r[4 * (i >> 1) + 2 + (i & 1)] : r[17];
    const uint32_t y = __shfl_xor_sync(0xffffffffu, odd ? A : B, 1);
    *reinterpret_cast<uint2*>(i < 8 ? o1 + 8 * (i >> 1) + (i & 1) * 8 * (DM / 2) : o2) = odd ? make_uint2(y, B) : make_uint2(A, y);
  }
}

__global__ void __launch_bounds__(384, 1) fused_kernel(const __grid_constant__ Params prm) {
  extern __shared__ __align__(1024) uint8_t smem[];
  const uint32_t sb = (uint32_t)__cvta_generic_to_shared(smem);
  const uint32_t bar = sb + SM_BAR;
  const int m = blockIdx.x & 15, j = blockIdx.x >> 4;
  const int cta = m * 8 + j;
  const int wr = __shfl_sync(0xffffffffu, (int)(threadIdx.x >> 5), 0);
  const int wg = wr >> 2;
  const int lane = threadIdx.x & 31;
  STAMP(0);
  if (PF_X && threadIdx.x < 144) pf_line(prm.x + (size_t)cta * 16 * DM + threadIdx.x * 64);
  if (wg == 2 && lane == 0) {
    if (wr == 8) {
      asm volatile("prefetch.tensormap [%0];" ::"l"(&prm.xm) : "memory");
#pragma unroll
      for (int c = 0; c < 9; c++) mbar_init(bar + 8 * (B_X + c), 1);
#pragma unroll
      for (int c = 0; c < 9; c++) mbar_expect(bar + 8 * (B_X + c), 16384);
      asm volatile("fence.proxy.async.shared::cta;" ::: "memory");
#pragma unroll
      for (int c = 0; c < 3; c++) tma2d(sb + SM_XN + c * 16384, &prm.xm, bar + 8 * (B_X + c), 64 * c, 128 * m);
    } else {
      if (wr == 9) {
#pragma unroll
        for (int i = 0; i < 8; i++) mbar_init(bar + 8 * (B_F + i), 2);
#pragma unroll
        for (int i = 0; i < 3; i++) mbar_init(bar + 8 * (B_QF + i), 1);
      } else if (wr == 10) {
#pragma unroll
        for (int i = 0; i < 8; i++) mbar_init(bar + 8 * (B_E + i), 8);
#pragma unroll
        for (int i = 0; i < 3; i++) mbar_init(bar + 8 * (B_QE + i), 8);
      } else {
#pragma unroll
        for (int i = B_SK1; i <= B_SP; i++) mbar_init(bar + 8 * i, 8);
        mbar_init(bar + 8 * B_OL, 1); mbar_init(bar + 8 * B_RX, 1);
        mbar_init(bar + 8 * B_NR, 4); mbar_init(bar + 8 * (B_NR + 1), 4);
        asm volatile("st.shared.u32 [%0], 0;" ::"r"(sb + SM_BAD) : "memory");
        if (sb & 1023) asm volatile("trap;");
      }
      asm volatile("fence.proxy.async.shared::cta;" ::: "memory");
    }
  }
  if (wr == 0) {
    const uint32_t one = (lane >> 3) == (lane & 3) ? ((lane & 4) ? 0x3f800000u : 0x00003f80u) : 0u;
    asm volatile("st.shared.v4.b32 [%0], {%1,%2,%2,%1};" ::"r"(sb + SM_ID + lane * 16), "r"(one), "r"(0) : "memory");
  }
  __syncthreads();

  if (wg == 2) {
    asm volatile("setmaxnreg.dec.sync.aligned.u32 24;");
    const int pw = wr & 3;
    const uint32_t epoch = *(volatile uint32_t*)FLAG_EPOCH(cta);
    const int hh = j & 1;
#define ACOL(A) (320 * hh + 64 * (((j >> 1) + 1 + (A)) & 3))
    if (pw == 0) {
      if (lane == 0) {
#pragma unroll
        for (int c = 3; c < 9; c++) tma2d(sb + SM_XN + c * 16384, &prm.xm, bar + 8 * (B_X + c), 64 * c, 128 * m);
        uint64_t pol;
        asm volatile("createpolicy.fractional.L2::evict_first.b64 %0, 1.0;" : "=l"(pol));
#pragma unroll 1
        for (int kb = 0; kb < 9; kb++) {
          const int s = kb % 3;
          if (kb >= 3) mbar_wait(bar + 8 * (B_QE + s), (kb / 3 - 1) & 1);
          const uint32_t fb = bar + 8 * (B_QF + s), dst = sb + SM_RING + s * QST;
          mbar_expect(fb, QST);
#pragma unroll
          for (int p = 0; p < 3; p++) {
            tma2d(dst + p * 8192, &prm.wqkv64, fb, 576 * p + 72 * j + 8 * hh, 64 * kb);
            tma2d(dst + 24576 + p * 1024, &prm.wqkv8, fb, 576 * p + 72 * j + 64 - 64 * hh, 64 * kb);
          }
        }
        asm volatile("st.shared.u32 [%0], %1;" ::"r"(sb + SM_TAG), "r"((epoch + 1) & 1) : "memory");
        int col = 576 * j, kr = 0;
#pragma unroll 1
        for (int n = 0; n < N_G2; n++) {
          const uint32_t fb = bar + 8 * (B_F + (n & 7)), dst = sb + SM_RING + (n & 3) * BST;
          mbar_expect(fb, BST);
          if (n >= 4) mbar_wait(bar + 8 * (B_E + ((n - 3) & 7)), ((n - 3) >> 3) & 1);
          else if (n != 2) mbar_wait(bar + 8 * (B_QE + (n == 3 ? 2 : n)), 0);
          tma2d_h(dst, &prm.wg, fb, col, kr, pol);
          tma2d_h(dst + 8192, &prm.wu, fb, col, kr, pol);
          if ((kr += 64) == 576) { kr = 0; col += 64; }
        }
        uint32_t seen = 0;
#pragma unroll 1
        for (int b = 0; b < 26; b++) {
          const int n = N_G2 + 2 * b;
          const uint32_t fb = bar + 8 * (B_F + (n & 7)), dst = sb + (b & 3) * G2ST;
          const int own = b < 10 || b == 20 || b == 21, jj = own ? j : (j ^ 1), lb = b < 10 ? b : b < 20 ? b - 10 : 10 + (b & 1), need = (3 * lb + 6) >> 2;
          if (b < 24) {
            if (b == 10 || b == 20 || b == 22) seen = 0;
            if (seen < need) { seen = flag_wait_v(FLAG_H(m * 8 + jj), 9 * epoch + need) - 9 * epoch; fence_async(); }
          } else {
            flag_wait(FLAG_O((cta & ~1) + b - 24), epoch + 1);
            fence_async();
          }
          mbar_wait(bar + 8 * (B_E + ((n - 5) & 7)), ((n - 5) >> 3) & 1);
          if (b == 0) STAMPW(16);
          mbar_expect(fb, G2ST);
          if (b < 24) {
            bulk_g2s(dst, g_H + (m * 576 + 72 * jj + 6 * lb) * 512, 12288, fb);
#pragma unroll
            for (int a = 0; a < 4; a++) tma5d(dst + 12288 + a * 6144, &prm.wd[0], fb, ACOL(a), 36 * jj + 3 * lb);
            tma5d(dst + 36864, &prm.wd[1 + hh], fb, 0, 36 * jj + 3 * lb);
          } else {
            const int r = b - 24;
            bulk_g2s(dst, g_O + ((cta & ~1) + r) * 9 * 512 + r * 1024, 12288, fb);
#pragma unroll
            for (int a = 0; a < 4; a++) tma3d(dst + 12288 + a * 6144, &prm.wo3[0], fb, ACOL(a), 4 * (j & 6) + 5 * r);
            tma3d(dst + 36864, &prm.wo3[1 + hh], fb, 0, 4 * (j & 6) + 5 * r);
          }
          if (b == 0) STAMPW(17);
        }
        mbar_wait(bar + 8 * B_SP, 0);
        mbar_expect(bar + 8 * B_OL, 49152 + 32768);
        tma2d(sb + SM_RES, &prm.xm, bar + 8 * B_OL, ACOL(3), 128 * m);
        __nanosleep(200);
        tma2d(sb + SM_RES + 16384, &prm.xm, bar + 8 * B_OL, 256 + 32 * hh, 128 * m);
#pragma unroll 1
        for (int i = 0; i < 4; i++) {
          __nanosleep(200);
          tma3d(sb + SM_LB + i * 4096, &prm.wo2[0], bar + 8 * B_OL, ACOL(3), 8 * i + 3);
          tma3d(sb + SM_LB + 24576 + i * 4096, &prm.wo2[1 + hh], bar + 8 * B_OL, 0, 8 * i + 3);
          tma3d(sb + SM_LB + 16384 + i * 2048, &prm.wo16[0], bar + 8 * B_OL, ACOL(3), 8 * i);
          tma3d(sb + SM_LB + 40960 + i * 2048, &prm.wo16[1 + hh], bar + 8 * B_OL, 0, 8 * i);
        }
      }
    } else if (pw == 1) {
      if (lane == 0) {
        const int hx = hh * 3;
        int u = 0, kslot = 0, vrow = 0, kb = 0;
#pragma unroll 1
        for (int n = 0; n <= 141; n++) {
          const uint32_t fb = bar + 8 * (B_F + (n & 7)), dst = sb + SM_KV + kslot * KVST;
          const bool att = n >= N_G2 || (n >= NG0 && kb != 0);
          if (++kb == 9) kb = 0;
          mbar_expect(fb, att ? (n < 141 ? KVST : KVST / 2) : 0);
          if (n >= N_AO || (n > N_G2 && !(n & 1))) mbar_expect(fb, 0);
          if (u == 0 && att) { flag_wait(FLAG_KV(0, j), 16 * epoch + 16); fence_async(); STAMPW(18); }
          if (n >= 4) mbar_wait(bar + 8 * (B_E + ((n - 3) & 7)), ((n - 3) >> 3) & 1);
          if (att) {
            const int krow = (4 * j + ((u >> 5) ^ hx)) * 256 + ((u + 2 * m) & 31) * 8;
            if (u == 0) vrow = krow;
            if (u < 128) tma2d(dst, &prm.kv, fb, 0, krow);
            tma2d(dst + 3072, &prm.kv, fb, 128, vrow);
            vrow = krow; u++;
            if (++kslot == 3) kslot = 0;
            if (u == 16) { flag_wait(FLAG_KV(1, j), 16 * epoch + 16); fence_async(); }
          }
        }
      }
    } else if (pw == 2) {
      if (lane == 0) {
#pragma unroll 1
        for (int i = 1; i < 18; i++) asm volatile("prefetch.tensormap [%0];" ::"l"(&prm.xm + i) : "memory");
        mbar_wait(bar + 8 * B_SK1, 0);
        STAMPW(22);
        fence_gpu(); flag_add(FLAG_KV(0, j));
        STAMPW(20);
        mbar_wait(bar + 8 * B_SK2, 0);
        fence_gpu(); flag_add(FLAG_KV(1, j));
#pragma unroll 1
        for (int t = 0; t < 9; t++) { mbar_wait(bar + 8 * B_SH, t & 1); if (EXP_DELAY) __nanosleep(EXP_DELAY); fence_gpu(); flag_add(FLAG_H(cta)); }
        mbar_wait(bar + 8 * B_SO1, 0);
        fence_gpu(); flag_add(FLAG_O(cta));
      }
    } else {
      mbar_wait(bar + 8 * (B_X + PF_Q), 0);
#pragma unroll 1
      for (int i = lane; i < 122; i += 32) pf_line(prm.pwqkv + (size_t)min(i * 128 + cta, 15551) * 64);
      mbar_wait(bar + 8 * (B_QE + PF_G1), 0);
#pragma unroll 1
      for (int t = -3; t < 9; t++) {
        if (t >= 0) { mbar_wait(bar + 8 * B_SH, t & 1); if (EXP_PFD) __nanosleep(EXP_PFD); }
        if (t < 6) {
#pragma unroll 1
          for (int i = lane; i < 72; i += 32) pf_line((i >= 36 ? prm.pwu : prm.pwg) + (size_t)(36 * m + (i >= 36 ? i - 36 : i)) * FF + 576 * j + 64 * (t + 3));
        }
        if (t >= 5) {
#pragma unroll 1
          for (int i = lane; i < 81; i += 32) {
            const int l = (2 * m + hh) * 81 + i, r = l / 9;
            pf_line(prm.pwd + (size_t)(1152 * (j >> 1) + 576 * (r / 144) + 144 * (t - 5) + r % 144) * DM + 64 * (l % 9));
          }
        }
      }
      if (cta * 41 + lane < 5184) pf_line(prm.pwo + (size_t)(cta * 41 + lane) * 64);
      if (lane < 9 && cta * 41 + 32 + lane < 5184) pf_line(prm.pwo + (size_t)(cta * 41 + 32 + lane) * 64);
      if (lane == 0) {
      mbar_wait(bar + 8 * B_SP, 0);
      const int q = j >> 1;
#pragma unroll 1
      for (int i = 0; i < 14; i++) {
        bulk_s2g(g_P + cta * 3584 + i * 256, sb + SM_SEND + i * 4096, 4096);
        asm volatile("cp.async.bulk.commit_group;\ncp.async.bulk.wait_group.read %0;" ::"n"(SEND_DEPTH) : "memory");
      }
      asm volatile("cp.async.bulk.wait_group 0;" ::: "memory");
      fence_gpu();
      flag_add(FLAG_P(cta));
      STAMPW(15);
      mbar_expect(bar + 8 * B_RX, 73728);
#pragma unroll 1
      for (int a = 0; a < 3; a++) {
        const int src = m * 8 + 2 * ((q + 3 - a) & 3) + hh;
        flag_wait(FLAG_P(src), epoch + 1);
        fence_async();
        bulk_g2s(sb + SM_RECV + a * 24576, g_P + src * 3584 + a * 1024, 16384, bar + 8 * B_RX);
        bulk_g2s(sb + SM_RECV + a * 24576 + 16384, g_P + src * 3584 + 3072, 8192, bar + 8 * B_RX);
        if (RX_SLEEP) __nanosleep(RX_SLEEP);
      }
      STAMPW(25);
      *FLAG_EPOCH(cta) = epoch + 1;
      }
    }
  } else {
    const int tid = threadIdx.x;
    const int t = lane & 3;
    const uint32_t l0 = lane == 0;
    const uint32_t adesc = (((sb + SM_XN + wg * 8192) & 0x3FFFF) >> 4) | LO_A;
    const uint32_t bdesc = (((sb + SM_RING) & 0x3FFFF) >> 4) | LO_B;
    const uint32_t kdesc0 = (((sb + SM_KV) & 0x3FFFF) >> 4) | LO_K;
    const int hx = (j & 1) * 3;
    float accA[64], accB[64];
    Att a;
    uint32_t gs = 0, s8 = 0;
#define G1_ISSUE(ACC, AD, BD) _Pragma("unroll") for (int k = 0; k < 4; k++) wg_ss_n128<HI_SW128, HI_SW128>(ACC, (AD) + k * 2, (BD) + k * 128);
#define G1_ISSUE_Z(ACC, BD)                                                                                    \
  wg_ss_z_n128<HI_SW128, HI_SW128>(ACC, adesc, BD);                                                            \
  _Pragma("unroll") for (int k = 1; k < 4; k++) wg_ss_n128<HI_SW128, HI_SW128>(ACC, adesc + k * 2, (BD) + k * 128);
#define F_BAR (bar + 8 * B_F + 8 * s8)
#define F_PH ((gs >> 3) & 1)
#define RELEASE() mbar_arrive_if(bar + 8 * B_E + 8 * s8, l0);
#define NEXT_SLOT() { gs++; s8 = s8 == 7 ? 0 : s8 + 1; }
#define G1_ONLY() { mbar_wait(F_BAR, F_PH); wg_fence(); G1_ISSUE(accA, adesc + gs * 1024, bdesc + (gs & 3) * 1024) wg_commit(); wg_wait<1>(); RELEASE() NEXT_SLOT() }
    {
      const int lr = wr * 16 + (lane & 15);
      uint32_t ra[4];
#pragma unroll
      for (int k = 0; k < 4; k++) ra[k] = sb + SM_XN + lr * 128 + (((2 * k + (lane >> 4)) ^ (lr & 7)) << 4);
      STAMP(26);
      float cs[2][4] = {}, q0 = 0.f, q1 = 0.f, q2 = 0.f, q3 = 0.f;
#pragma unroll 1
      for (int c = 0; c < 9; c++) {
        mbar_wait(bar + 8 * (B_X + c), 0);
        if (c == 0) STAMP(27);
        if (c == 8) STAMP(28);
        uint32_t v[4][4];
#pragma unroll
        for (int k = 0; k < 4; k++) ldsm4(v[k], ra[k] + c * 16384);
#pragma unroll
        for (int k = 0; k < 4; k++) {
          mma_ones(cs[k & 1], v[k]);
#pragma unroll
          for (int e = 0; e < 4; e += 2) {
            const float x0 = bf_lo(v[k][e]), x1 = bf_hi(v[k][e]), y0 = bf_lo(v[k][e + 1]), y1 = bf_hi(v[k][e + 1]);
            q0 = fmaf(x0, x0, q0); q1 = fmaf(x1, x1, q1); q2 = fmaf(y0, y0, q2); q3 = fmaf(y1, y1, q3);
          }
        }
      }
      STAMP(11);
      asm volatile("setmaxnreg.inc.sync.aligned.u32 240;");
      const float mean0 = (cs[0][0] + cs[1][0]) * (1.f / 576.f), mean1 = (cs[0][2] + cs[1][2]) * (1.f / 576.f);
      q0 += q1; q2 += q3;
      q0 += __shfl_xor_sync(0xffffffffu, q0, 1); q2 += __shfl_xor_sync(0xffffffffu, q2, 1);
      q0 += __shfl_xor_sync(0xffffffffu, q0, 2); q2 += __shfl_xor_sync(0xffffffffu, q2, 2);
      float var0 = fmaf(q0, 1.f / 576.f, -mean0 * mean0), var1 = fmaf(q2, 1.f / 576.f, -mean1 * mean1);
      if (__any_sync(0xffffffffu, !(mean0 * mean0 <= 8.f * var0) || !(mean1 * mean1 <= 8.f * var1))) {
        q0 = q2 = 0.f;
#pragma unroll 1
        for (int i = 0; i < 36; i++) {
          uint32_t v[4];
          ldsm4(v, ((ra[0] + (i >> 2) * 16384) ^ ((i & 3) << 5)));
#pragma unroll
          for (int e = 0; e < 4; e += 2) {
            const float x0 = bf_lo(v[e]) - mean0, x1 = bf_hi(v[e]) - mean0, y0 = bf_lo(v[e + 1]) - mean1, y1 = bf_hi(v[e + 1]) - mean1;
            q0 = fmaf(x0, x0, fmaf(x1, x1, q0)); q2 = fmaf(y0, y0, fmaf(y1, y1, q2));
          }
        }
        q0 += __shfl_xor_sync(0xffffffffu, q0, 1); q2 += __shfl_xor_sync(0xffffffffu, q2, 1);
        q0 += __shfl_xor_sync(0xffffffffu, q0, 2); q2 += __shfl_xor_sync(0xffffffffu, q2, 2);
        var0 = q0 * (1.f / 576.f); var1 = q2 * (1.f / 576.f);
      }
      const float inv0 = rcp_fast(bf_round(sqrt_fast(bf_round(bf_round(var0) + 1e-5f)))), inv1 = rcp_fast(bf_round(sqrt_fast(bf_round(bf_round(var1) + 1e-5f))));
      const uint32_t mb0 = pack(mean0, mean0), mb1 = pack(mean1, mean1);
      const uint32_t h0 = pack(inv0, inv0), h1 = pack(inv1, inv1);
      const uint32_t e0 = pack(inv0 - bf_lo(h0), inv0 - bf_lo(h0)), e1 = pack(inv1 - bf_lo(h1), inv1 - bf_lo(h1));
#define NORM_STORE(C)                                                                                          \
  {                                                                                                            \
    _Pragma("unroll") for (int k = 0; k < 4; k++)                                                              \
      stsm4(ra[k] + (C) * 16384, bscale2(bsub2(v[k][0], mb0), h0, e0), bscale2(bsub2(v[k][1], mb1), h1, e1),   \
            bscale2(bsub2(v[k][2], mb0), h0, e0), bscale2(bsub2(v[k][3], mb1), h1, e1));                       \
    asm volatile("fence.proxy.async.shared::cta;" ::: "memory");                                               \
    __syncwarp();                                                                                              \
    mbar_arrive_if(bar + 8 * B_NR + 8 * wg, l0);                                                               \
  }
      float aq[96], ar[12];
      {
        uint32_t v[4][4];
#pragma unroll
        for (int k = 0; k < 4; k++) ldsm4(v[k], ra[k]);
        NORM_STORE(0)
      }
#pragma unroll
      for (int i = 0; i < 96; i++) aq[i] = 0.f;
#pragma unroll
      for (int i = 0; i < 12; i++) ar[i] = 0.f;
      pin<96>(aq); pin<12>(ar);
      STAMP(1);
      const uint32_t rdesc = (((sb + SM_RING + 24576) & 0x3FFFF) >> 4) | LO_R;
      uint32_t s = 0, ph = 0;
#pragma unroll 1
      for (int kb = 0; kb < 9; kb++) {
        uint32_t v[4][4];
        const int cn = kb < 8 ? kb + 1 : 8;
#pragma unroll
        for (int k = 0; k < 4; k++) ldsm4(v[k], ra[k] + cn * 16384);
        mbar_wait(bar + 8 * B_QF + 8 * s, ph);
        mbar_wait(bar + 8 * B_NR + 8 * wg, kb & 1);
        wg_fence();
#pragma unroll
        for (int k = 0; k < 4; k++) {
          wg_ss_n192<HI_SW128, HI_SW128>(aq, adesc + kb * 1024 + k * 2, bdesc + s * (QST >> 4) + k * 128);
          wg_ss_n24<HI_SW128, HI_R>(ar, adesc + kb * 1024 + k * 2, rdesc + s * (QST >> 4) + k * 16);
        }
        wg_commit();
        if (kb < 8) NORM_STORE(cn)
        wg_wait<1>();
        mbar_arrive_if(bar + 8 * B_QE + (s == 0 ? 16 : 8 * s - 8), l0 & (kb > 0));
        if (++s == 3) { s = 0; ph ^= 1; }
      }
      wg_wait<0>();
      pin<96>(aq); pin<12>(ar);
      mbar_arrive_if(bar + 8 * (B_QE + 2), l0);
      STAMP(2);
      uint32_t* kvp = g_KV + (size_t)(4 * j) * SEQ * 20 + (16 * m + 2 * wr) * 160 + lane;
      uint32_t pk[2][9][2];
#pragma unroll
      for (int p = 0; p < 2; p++)
#pragma unroll
        for (int i = 0; i < 9; i++) {
          const float* src = i < 8 ? &aq[(8 * (p + 1) + i) * 4] : &ar[4 * (p + 1)];
          pk[p][i][0] = pack(src[0], src[1]); pk[p][i][1] = pack(src[2], src[3]);
        }
      if (hx) {
#pragma unroll
        for (int p = 0; p < 2; p++) { rotate9(pk[p]); }
        store_kv_head<3>(pk, kvp, lane);
      } else store_kv_head<0>(pk, kvp, lane);
      __syncwarp();
      mbar_arrive_if(bar + 8 * B_SK1, l0);
      STAMP(3);
      mbar_wait(bar + 8 * B_F, 0);
      wg_fence();
      G1_ISSUE_Z(accA, bdesc)
      wg_commit();
      RELEASE()
      NEXT_SLOT()
      uint32_t pq[9][2];
#pragma unroll
      for (int i = 0; i < 9; i++) {
        const float* src = i < 8 ? &aq[i * 4] : &ar[0];
        pq[i][0] = pack(bf_round(src[0]) * QSCALE, bf_round(src[1]) * QSCALE); pq[i][1] = pack(bf_round(src[2]) * QSCALE, bf_round(src[3]) * QSCALE);
      }
      if (hx) rotate9(pq);
      pin<18>(&pq[0][0]);
#pragma unroll 1
      while (gs < 3) G1_ONLY()
      if (hx) store_kv_head<0>(pk, kvp, lane); else store_kv_head<3>(pk, kvp, lane);
      store_kv_head<1>(pk, kvp, lane);
      store_kv_head<2>(pk, kvp, lane);
      __syncwarp();
      mbar_arrive_if(bar + 8 * B_SK2, l0);
      G1_ONLY()
      uint4* qp = reinterpret_cast<uint4*>(g_Q) + cta * 4 * 512 + tid;
#pragma unroll
      for (int hp = 0; hp < 4; hp++) {
        const bool up = t < hp;
        const uint4 u = make_uint4(up ? pq[2 * hp + 1][0] : pq[2 * hp][0], up ? pq[2 * hp + 1][1] : pq[2 * hp][1],
                                   up ? pq[2 * hp + 2][0] : pq[2 * hp + 1][0], up ? pq[2 * hp + 2][1] : pq[2 * hp + 1][1]);
        const uint4 v = make_uint4(t == hp ? pq[2 * hp + 2][0] : 0u, t == hp ? pq[2 * hp + 2][1] : 0u, 0u, 0u);
        qp[hp * 512] = u; qp[hp * 512 + 256] = v;
        if (hp == 0 || (hp == 3 && hx)) { a.q[0] = u.x; a.q[1] = u.y; a.q[2] = u.z; a.q[3] = u.w; a.q[4] = v.x; a.q[5] = v.y; }
      }
      a.q[6] = __shfl_sync(0xffffffffu, lane, 0); a.q[7] = __shfl_sync(0xffffffffu, lane >> 1, 1);
#pragma unroll
      for (int i = 0; i < 16; i++) a.p[i] = 0;
#pragma unroll
      for (int i = 0; i < 12; i++) a.o[i] = 0.f;
      pin<16>(a.p); pin<12>(a.o); pin<8>(a.q);
    }
    static_assert(NG0 == 5, "slot / item alignment below assumes NG0 == 5");
    G1_ONLY()
    STAMP(4);
    mbar_wait(F_BAR, F_PH);
    STAMP(23);
    uint32_t kd = kdesc0;
    uint32_t it = 0;
    uint32_t ox0 = 0, ox1 = 0;
    bool special = true;
    uint32_t qn[6] = {0, 0, 0, 0, 0, 0};
    uint32_t* hdst = g_H + ((m * 576 + 72 * j + (t >> 1)) * 128 + 16 * wr + (lane >> 2)) * 4 + 2 * (t & 1);
    uint32_t ad = adesc + NG0 * 1024, bd = bdesc + (gs & 3) * 1024;

#define ITEM_FIRST()                                                                                           \
  {                                                                                                            \
    pin<12>(a.o);                                                                                              \
    if (it != 0) {                                                                                             \
      uint32_t w[4];                                                                                           \
      o_normalise(a.o, w, ox0, ox1, ((it >> 5) - 1) ^ hx, lane, sb + SM_BAD, wr);                              \
      uint32_t* d = g_O + cta * 9 * 512 + (((it >> 5) - 1) ^ hx) * 1024 + wr * 64 + lane;                      \
      d[0] = w[0]; d[32] = w[1]; d[512] = w[2]; d[544] = w[3];                                                 \
    }                                                                                                          \
    if (it == 96) mbar_arrive_if(bar + 8 * B_SO1, l0 & (bad_heads(sb + SM_BAD, wr) == 0));                     \
    first_tile(a, (it >> 5) ^ hx, lane);                                                                       \
  }
#define ITEM_NEXTQ() { if (it & 2) { _Pragma("unroll") for (int i = 0; i < 6; i++) a.q[i] = qn[i]; } else fetch_q(qn, cta, ((it >> 5) + 1) ^ hx, tid); }
#define KV_ADVANCE() { kd = kd == kdesc0 + 768 ? kdesc0 : kd + 384; }
#define WAIT_UNLESS(OK) if (__builtin_expect(!(OK), 0)) mbar_wait(F_BAR, F_PH);
#define SOFTMAX_NEXT() { softmax_a(a); softmax_b(a); mbar_wait(F_BAR, F_PH); softmax_c(a); }
#define EPI_STEP(ACCN, ACCO)                                                                                   \
  {                                                                                                            \
    wg_fence();                                                                                                \
    G1_ISSUE_Z(ACCN, bd)                                                                                       \
    wg_commit();                                                                                               \
    wg_wait<1>();                                                                                              \
    pin<64>(ACCO);                                                                                             \
    RELEASE()                                                                                                  \
    NEXT_SLOT()                                                                                                \
    ad = adesc + 1024; bd = bdesc + (gs & 3) * 1024;                                                           \
    const uint32_t ok = mbar_test(F_BAR, F_PH);                                                                \
    h_epilogue(ACCO, hdst);                                                                                    \
    hdst += 4096;                                                                                              \
    __syncwarp();                                                                                              \
    mbar_arrive_if(bar + 8 * B_SH, l0);                                                                        \
    WAIT_UNLESS(ok)                                                                                            \
  }
#define ATT_LOOP1(ACC, ITEMS)                                                                                  \
  do {                                                                                                         \
    wg_fence();                                                                                                \
    issue_att(a, kd);                                                                                          \
    wg_commit();                                                                                               \
    G1_ISSUE(ACC, ad, bd)                                                                                      \
    wg_commit();                                                                                               \
    wg_wait<1>();                                                                                              \
    pin<32>(a.s);                                                                                              \
    RELEASE()                                                                                                  \
    TRACE()                                                                                                    \
    if (ITEMS) { if (__builtin_expect(special, 0)) { if (it & 1) ITEM_NEXTQ() else if (!(it & 2)) { if (it == 64) fetch_q(qn, cta, 3 ^ hx, tid); ITEM_FIRST() } } } \
    NEXT_SLOT() it++;                                                                                                \
    if (ITEMS) special = ((it + 3) & 31) < 4;                                                                  \
    KV_ADVANCE()                                                                                               \
    ad += 1024; bd = bdesc + (gs & 3) * 1024;                                                                  \
    SOFTMAX_NEXT()                                                                                             \
    pin<8>(a.q);                                                                                               \
  } while (ad != adesc + 9 * 1024);
#pragma unroll 1
    for (int pr = 0;; pr++) {
      ATT_LOOP1(accA, true)
      if (pr == 4) break;
      if (pr == 2) STAMP(29);
      EPI_STEP(accB, accA)
      if (pr == 2) STAMP(30);
      ATT_LOOP1(accB, false)
      if (pr == 2) STAMP(31);
      EPI_STEP(accA, accB)
      special = false;
      if (pr == 2) STAMP(21);
      if (pr == 3) STAMP(14);
    }
    STAMP(5);
    wg_wait<0>();
    pin<64>(accA);
    h_epilogue(accA, hdst);
    __syncwarp();
    mbar_arrive_if(bar + 8 * B_SH, l0);
    mbar_wait(bar + 8 * B_E, 0);
    asm volatile("st.shared.v4.b32 [%0], {%1,%2,%3,%4};\nst.shared.v2.b32 [%5], {%6,%7};" ::"r"(sb + SM_QS + tid * 16), "r"(qn[0]), "r"(qn[1]), "r"(qn[2]), "r"(qn[3]),
                 "r"(sb + SM_QS + 4096 + tid * 8), "r"(qn[4]), "r"(qn[5]) : "memory");
    STAMP(6);
    STAMP(12);

    float acc2[144];
    const uint32_t a2desc = (((sb + wg * 1024) & 0x3FFFF) >> 4) | LO_O;
    const uint32_t b2desc = (((sb + 12288) & 0x3FFFF) >> 4) | LO_B48;
    ad = a2desc; bd = b2desc;
#define G2_LO(K) wg_ss_n128<HI_O, HI_SW128>(acc2, ad + (K) * 256, bd + (K) * 128);
#define G2_HI(K) wg_ss_n160<HI_O, HI_SW128>(acc2 + 64, ad + (K) * 256, bd + (K) * 128 + 768);
#define ATT_PAIR(ZERO)                                                                                         \
  {                                                                                                            \
    wg_fence();                                                                                                \
    issue_att(a, kd);                                                                                          \
    wg_commit();                                                                                               \
    if (ZERO) { wg_ss_z_n128<HI_O, HI_SW128>(acc2, ad, bd); wg_ss_z_n160<HI_O, HI_SW128>(acc2 + 64, ad, bd + 768); } \
    else { G2_LO(0) G2_HI(0) }                                                                                 \
    G2_LO(1)                                                                                                   \
    wg_commit();                                                                                               \
    wg_wait<1>();                                                                                              \
    pin<32>(a.s);                                                                                              \
    RELEASE()                                                                                                  \
    TRACE()                                                                                                    \
    if (!(ZERO)) { if (__builtin_expect(gs == N_G2 + 28, 0)) ITEM_FIRST() }                                    \
    NEXT_SLOT() it++;                                                                                                \
    KV_ADVANCE()                                                                                               \
    SOFTMAX_NEXT()                                                                                             \
    pin<8>(a.q);                                                                                               \
    wg_fence();                                                                                                \
    issue_att(a, kd);                                                                                          \
    wg_commit();                                                                                               \
    G2_HI(1) G2_LO(2) G2_HI(2)                                                                                 \
    wg_commit();                                                                                               \
    wg_wait<1>();                                                                                              \
    pin<32>(a.s);                                                                                              \
    RELEASE()                                                                                                  \
    TRACE()                                                                                                    \
    if (!(ZERO) && __builtin_expect(gs == N_G2 + 27, 0)) {                                                     \
      const int ft = fresh_tid();                                                                              \
      asm volatile("ld.shared.v4.b32 {%0,%1,%2,%3}, [%6];\nld.shared.v2.b32 {%4,%5}, [%7];" : "=r"(a.q[0]), "=r"(a.q[1]), "=r"(a.q[2]), "=r"(a.q[3]), \
                   "=r"(a.q[4]), "=r"(a.q[5]) : "r"(sb + SM_QS + ft * 16), "r"(sb + SM_QS + 4096 + ft * 8) : "memory"); \
    }                                                                                                          \
    NEXT_SLOT() it++;                                                                                                \
    KV_ADVANCE()                                                                                               \
    ad = a2desc + (((gs - N_G2) >> 1) & 3) * 2688; bd = ad + (b2desc - a2desc);                                \
    SOFTMAX_NEXT()                                                                                             \
    pin<8>(a.q);                                                                                               \
  }
    ATT_PAIR(true)
#pragma unroll 1
    for (int half = 0; half < 2; half++) {
      const uint32_t stop = half ? N_AO : N_G2 + 46;
      do ATT_PAIR(false) while (gs != stop);
      if (!half) {
        const uint32_t bad = bad_heads(sb + SM_BAD, wr);
        if (bad) { repair_rows(cta, wr, bad, 3 ^ hx, false); mbar_arrive_if(bar + 8 * B_SO1, l0); }
      }
    }
    STAMP(13);
    wg_wait<0>();
    pin<144>(acc2);
    mbar_wait(bar + 8 * (B_E + 1), 0);
    stage_partials(acc2, sb + SM_SEND, fresh_tid());
    asm volatile("fence.proxy.async.shared::cta;" ::: "memory");
    __syncwarp();
    mbar_arrive_if(bar + 8 * B_SP, l0);
    do {
      wg_fence();
      issue_att(a, kd);
      wg_commit();
      wg_wait<0>();
      pin<32>(a.s);
      RELEASE()
      TRACE()
      NEXT_SLOT() it++;
      KV_ADVANCE()
      SOFTMAX_NEXT()
    } while (gs != 141);
    STAMP(7);
    wg_fence();
    issue_pv(a, kd);
    wg_commit();
    int tid2, bid2;
    asm volatile("mov.u32 %0, %%tid.x;" : "=r"(tid2));
    asm volatile("mov.u32 %0, %%ctaid.x;" : "=r"(bid2));
    const int m2 = bid2 & 15, j2 = bid2 >> 4;
    uint32_t tag;
    asm volatile("ld.shared.u32 %0, [%1];" : "=r"(tag) : "r"(sb + SM_TAG) : "memory");
    wg_wait<0>();
    pin<12>(a.o);
    {
      uint32_t w[4];
      o_normalise(a.o, w, ox0, ox1, 3 ^ hx, lane, sb + SM_BAD, wr);
      ox0 = __shfl_xor_sync(0xffffffffu, ox0, 2); ox1 = __shfl_xor_sync(0xffffffffu, ox1, 2);
      const uint32_t bad = bad_heads(sb + SM_BAD, wr);
      if (bad) {
        uint32_t* d = g_O + cta * 9 * 512 + wr * 64 + lane;
        uint32_t* h = d + (3 ^ hx) * 1024;
        h[0] = w[0]; h[32] = w[1]; h[512] = w[2]; h[544] = w[3]; d[4096] = ox0; d[4128] = ox1;
        __syncwarp();
        repair_rows(cta, wr, bad, 3 ^ hx, true);
        w[0] = __ldcg(h); w[1] = __ldcg(h + 32); w[2] = __ldcg(h + 512); w[3] = __ldcg(h + 544); ox0 = __ldcg(d + 4096); ox1 = __ldcg(d + 4128);
      }
      asm volatile("st.relaxed.gpu.global.v4.b32 [%0], {%1,%2,%3,%4};" ::"l"(g_L + (m2 * 8 + j2) * 384 + tid2), "r"((w[0] & ~1u) | tag), "r"((w[1] & ~1u) | tag),
                   "r"((w[2] & ~1u) | tag), "r"((w[3] & ~1u) | tag) : "memory");
      asm volatile("st.relaxed.gpu.global.v2.b32 [%0], {%1,%2};" ::"l"(reinterpret_cast<uint2*>(g_L + (m2 * 8 + j2) * 384 + 256) + tid2), "r"((ox0 & ~1u) | tag),
                   "r"((ox1 & ~1u) | tag) : "memory");
    }
    STAMP(8);
    uint32_t la[48];
    const uint4* p4 = g_L + m2 * 8 * 384 + tid2;
    const uint2* p2 = reinterpret_cast<const uint2*>(g_L + m2 * 8 * 384 + 256) + tid2;
#define LOAD_LA2() { ld2<0>(la + 32, p2); ld2<6144>(la + 34, p2); ld2<12288>(la + 36, p2); ld2<18432>(la + 38, p2); \
                     ld2<24576>(la + 40, p2); ld2<30720>(la + 42, p2); ld2<36864>(la + 44, p2); ld2<43008>(la + 46, p2); }
#define LOAD_LA4() { ld4<0>(la, p4); ld4<6144>(la + 4, p4); ld4<12288>(la + 8, p4); ld4<18432>(la + 12, p4); \
                     ld4<24576>(la + 16, p4); ld4<30720>(la + 20, p4); ld4<36864>(la + 24, p4); ld4<43008>(la + 28, p4); }
    LOAD_LA4()
    LOAD_LA2()
    float fin[48];
    uint32_t id[4][4];
    {
      uint32_t id2[4][4];
#pragma unroll
      for (int k = 0; k < 4; k++) {
        asm volatile("ld.volatile.shared.v4.b32 {%0,%1,%2,%3}, [%4];" : "=r"(id[k][0]), "=r"(id[k][1]), "=r"(id[k][2]), "=r"(id[k][3])
                     : "r"(sb + SM_ID + ((wr & 3) == k ? lane : 1) * 16) : "memory");
#pragma unroll
        for (int e = 0; e < 4; e++) id2[k][e] = id[k][e] + (id[k][e] & 0x00800080u);
      }
      pin<16>(&id[0][0]); pin<16>(&id2[0][0]);
      const uint32_t xdesc = (((sb + SM_RES + wg * 8192) & 0x3FFFF) >> 4) | LO_B;
      mbar_wait(bar + 8 * B_OL, 0);
      wg_fence();
      wg_rsb_z_n64<HI_SW128>(fin, id2[0][0], id2[0][1], id2[0][2], id2[0][3], xdesc);
      wg_rs_z_n32<HI_SW128>(fin + 32, id2[0][0], id2[0][1], id2[0][2], id2[0][3], xdesc + 1024);
#pragma unroll
      for (int k = 1; k < 4; k++) {
        wg_rsb_n64<HI_SW128>(fin, id2[k][0], id2[k][1], id2[k][2], id2[k][3], xdesc + k * 128);
        wg_rs_n32<HI_SW128>(fin + 32, id2[k][0], id2[k][1], id2[k][2], id2[k][3], xdesc + 1024 + k * 128);
      }
      wg_commit();
      wg_wait<0>();
      pin<48>(fin);
#pragma unroll
      for (int i = 0; i < 48; i++) fin[i] += acc2[96 + i];
      pin<48>(fin);
    }
    for (uint32_t tries = 0; tries < 0x400000u; tries++) {
      uint32_t bad = 0;
#pragma unroll
      for (int i = 0; i < 48; i++) bad |= la[i] ^ tag;
      if (__all_sync(0xffffffffu, !(bad & 1))) break;
      LOAD_LA4()
      LOAD_LA2()
    }
#pragma unroll
    for (int i = 0; i < 48; i++) la[i] ^= tag;
    pin<48>(la);
    STAMP(19);
    const uint32_t ldesc = (((sb + SM_LB) & 0x3FFFF) >> 4) | LO_B;
    wg_fence();
#pragma unroll
    for (int k = 0; k < 12; k++) {
      wg_rsb_n64<HI_SW128>(fin, la[4 * k], la[4 * k + 1], la[4 * k + 2], la[4 * k + 3], ldesc + k * 128);
      wg_rs_n32<HI_SW128>(fin + 32, la[4 * k], la[4 * k + 1], la[4 * k + 2], la[4 * k + 3], ldesc + 1536 + k * 128);
    }
    wg_commit();
    const uint32_t pdesc = (((sb + SM_RECV + wg * 8192) & 0x3FFFF) >> 4) | LO_B, hdesc = (((sb + SM_RECV + 16384 + wg * 4096) & 0x3FFFF) >> 4) | LO_B;
    mbar_wait(bar + 8 * B_RX, 0);
    STAMP(24);
    wg_fence();
#pragma unroll
    for (int a3 = 0; a3 < 3; a3++)
#pragma unroll
      for (int k = 0; k < 4; k++) {
        wg_rsb_n64<HI_SW128>(fin, id[k][0], id[k][1], id[k][2], id[k][3], pdesc + a3 * 1536 + k * 128);
        wg_rs_n32<HI_SW64>(fin + 32, id[k][0], id[k][1], id[k][2], id[k][3], hdesc + a3 * 1536 + k * 64);
      }
    wg_commit();
    wg_wait<0>();
    pin<48>(fin);
    STAMP(9);
    final_epilogue(fin, prm, m2, j2 & 1, j2 >> 1, tid2);
    STAMP(10);
  }
}

typedef CUresult (*EncodeFn)(CUtensorMap*, CUtensorMapDataType, cuuint32_t, void*, const cuuint64_t*, const cuuint64_t*, const cuuint32_t*, const cuuint32_t*,
                             CUtensorMapInterleave, CUtensorMapSwizzle, CUtensorMapL2promotion, CUtensorMapFloatOOBfill);

void enc2d(EncodeFn enc, CUtensorMap* tm, const void* base, uint64_t w, uint64_t h, uint64_t pitch_elems, uint32_t bw, uint32_t bh, CUtensorMapSwizzle sw) {
  cuuint64_t dims[2] = {w, h}, str[1] = {pitch_elems * 2};
  cuuint32_t box[2] = {bw, bh}, es[2] = {1, 1};
  enc(tm, CU_TENSOR_MAP_DATA_TYPE_BFLOAT16, 2, const_cast<void*>(base), dims, str, box, es, CU_TENSOR_MAP_INTERLEAVE_NONE, sw,
      CU_TENSOR_MAP_L2_PROMOTION_L2_128B, CU_TENSOR_MAP_FLOAT_OOB_FILL_NONE);
}

}

extern "C" void kernel_launch(void* const* d_in, const int* in_sizes, int n_in, void* d_out, int out_size) {
  (void)in_sizes; (void)n_in; (void)out_size;
  const __nv_bfloat16* x = (const __nv_bfloat16*)d_in[0];
  const __nv_bfloat16* wqkv = (const __nv_bfloat16*)d_in[1];
  const __nv_bfloat16* wo = (const __nv_bfloat16*)d_in[2];
  const __nv_bfloat16* wg = (const __nv_bfloat16*)d_in[4];
  const __nv_bfloat16* wu = (const __nv_bfloat16*)d_in[5];
  const __nv_bfloat16* wd = (const __nv_bfloat16*)d_in[6];
  void* fn = nullptr;
  cudaDriverEntryPointQueryResult qr;
  cudaGetDriverEntryPoint("cuTensorMapEncodeTiled", &fn, cudaEnableDefault, &qr);
  EncodeFn enc = (EncodeFn)fn;
  void* kvp = nullptr;
  cudaGetSymbolAddress(&kvp, g_KV);
  Params p;
  enc2d(enc, &p.xm, x, DM, SEQ, DM, 64, 128, CU_TENSOR_MAP_SWIZZLE_128B);
  enc2d(enc, &p.kv, kvp, 320, 32 * 256, 320, 192, 8, CU_TENSOR_MAP_SWIZZLE_NONE);
  enc2d(enc, &p.wqkv64, wqkv, 3 * DM, DM, 3 * DM, 64, 64, CU_TENSOR_MAP_SWIZZLE_128B);
  enc2d(enc, &p.wqkv8, wqkv, 3 * DM, DM, 3 * DM, 8, 64, CU_TENSOR_MAP_SWIZZLE_NONE);
  enc2d(enc, &p.wg, wg, FF, DM, FF, 64, 64, CU_TENSOR_MAP_SWIZZLE_128B);
  enc2d(enc, &p.wu, wu, FF, DM, FF, 64, 64, CU_TENSOR_MAP_SWIZZLE_128B);
  for (int v = 0; v < 3; v++) {
    const cuuint64_t wdt = v ? 32 : DM;
    const int c0 = v ? 256 + 32 * (v - 1) : 0;
    for (int e = 0; e < 3; e++) {
      cuuint64_t d3[3] = {wdt, e == 2 ? 2u : 16u, 32}, s3[2] = {DM * 2, 18 * DM * 2};
      cuuint32_t b3[3] = {64, e == 2 ? 2u : 16u, e == 0 ? 3u : e == 1 ? 2u : 8u}, e3[3] = {1, 1, 1};
      enc(e == 0 ? &p.wo3[v] : e == 1 ? &p.wo2[v] : &p.wo16[v], CU_TENSOR_MAP_DATA_TYPE_BFLOAT16, 3, (void*)(wo + c0 + (e == 2 ? 16 * DM : 0)), d3, s3, b3, e3,
          CU_TENSOR_MAP_INTERLEAVE_NONE, CU_TENSOR_MAP_SWIZZLE_128B, CU_TENSOR_MAP_L2_PROMOTION_L2_128B, CU_TENSOR_MAP_FLOAT_OOB_FILL_NONE);
    }
    cuuint64_t dims[5] = {wdt, 2, 2, 4, FF / 16}, str[4] = {DM * 2, 8 * DM * 2, 2 * DM * 2, 16 * DM * 2};
    cuuint32_t box[5] = {64, 2, 2, 4, 3}, es[5] = {1, 1, 1, 1, 1};
    enc(&p.wd[v], CU_TENSOR_MAP_DATA_TYPE_BFLOAT16, 5, (void*)(wd + c0), dims, str, box, es, CU_TENSOR_MAP_INTERLEAVE_NONE,
        CU_TENSOR_MAP_SWIZZLE_128B, CU_TENSOR_MAP_L2_PROMOTION_L2_128B, CU_TENSOR_MAP_FLOAT_OOB_FILL_NONE);
  }
  p.x = x; p.pwqkv = wqkv; p.pwo = wo; p.pwg = wg; p.pwu = wu; p.pwd = wd;
  p.out = (__nv_bfloat16*)d_out;
  cudaFuncSetAttribute(fused_kernel, cudaFuncAttributeMaxDynamicSharedMemorySize, SM_TOTAL);
  fused_kernel<<<NCTA, 384, SM_TOTAL, cudaStreamPerThread>>>(p);
}
```

```cpp
#include <cuda_runtime.h>
#include <cuda.h>
#include <cuda_bf16.h>
#include <stdint.h>

namespace {

constexpr int SEQ = 2048, DM = 576, FF = 4608;
constexpr int NCTA = 128;

constexpr uint32_t SM_XN = 0;
constexpr uint32_t SM_RING = 147456;
constexpr uint32_t SM_KV = 212992;
constexpr uint32_t QST = 27648, BST = 16384, KVST = 6144;
constexpr uint32_t G2ST = 43008;
constexpr uint32_t SM_LB = 0, SM_RES = 49152, SM_SEND = 86016, SM_RECV = SM_SEND;
constexpr uint32_t SM_QS = 204800;
constexpr uint32_t SM_ID = 231424;
constexpr uint32_t SM_BAR = 231936;
constexpr uint32_t SM_TAG = 232436;
constexpr uint32_t SM_BAD = 232432;
constexpr uint32_t SM_TOTAL = 232448;
enum { B_F = 0, B_E = 8, B_QF = 16, B_QE = 19, B_SK1 = 22, B_SK2 = 23, B_SH = 24, B_SO1 = 25, B_LK = 26, B_SP = 27, B_OL = 28, B_RX = 29, B_NR = 30, B_X = 32, B_N = 41 };
constexpr int N_G2 = 81, N_AO = 133;
#define N_END (136 + NG0)
#define IT_G2 (73 - NG0)
#define EXP_DELAY 1000
#define EXP_PFD 1500
#define EXP_NOST 0
#define SEND_DEPTH 2
#define RX_SLEEP 0
#define EXP_NOKV 0
#define EXP_NOB 0
#define VOTE 0
#define LATE_TEST 1
#define SM_A 7
#define SM_B 11
#define RX_FIRST 0
#define CLUSTER 0
#define PF_X 0
#define PF_Q 6
constexpr int PF_G1 = 1;
#define NG0_ 5
constexpr int NG0 = NG0_;

constexpr uint32_t HI_SW128 = 0x40000040u;
constexpr uint32_t LO_A = 1u << 16;
constexpr uint32_t LO_B = 512u << 16;
constexpr uint32_t HI_R = 64u, LO_R = 8u << 16;
constexpr uint32_t HI_K = 24u, LO_K = 8u << 16;
constexpr uint32_t HI_V = 8u, LO_V = 24u << 16;
constexpr uint32_t LO_B48 = 384u << 16;
constexpr uint32_t HI_O = 8u, LO_O = 128u << 16;
constexpr uint32_t HI_SW64 = 0x80000020u;

constexpr float QSCALE = 0.23570226039551584f * 1.4426950408889634f;
constexpr float MOFF = 90.f;

struct __align__(64) Params {
  CUtensorMap xm, xh, wqkv64, wqkv8, wg, wu, kv, wd[3], wo3[3], wo2[3], wo16[3];
  const __nv_bfloat16 *x, *pwqkv, *pwo, *pwg, *pwu, *pwd;
  __nv_bfloat16* out;
};

__device__ __align__(1024) uint32_t g_H[16 * 576 * 512];
__device__ __align__(1024) uint32_t g_O[NCTA * 9 * 512];
__device__ __align__(1024) uint32_t g_KV[32 * SEQ * 20];
__device__ __align__(1024) uint32_t g_Q[NCTA * 4 * 256 * 8];
__device__ __align__(1024) uint4 g_P[NCTA * 3584];
__device__ __align__(1024) uint4 g_L[NCTA * 384];
__device__ float g_S[NCTA * 8 * SEQ];
__device__ uint32_t g_flags[16 * 32 + NCTA * 32 * 4];
#define FLAG_KV(l, j) (&g_flags[((l) * 8 + (j)) * 32])
#define FLAG_H(c) (&g_flags[16 * 32 + (c) * 32])
#define FLAG_O(c) (&g_flags[16 * 32 + NCTA * 32 + (c) * 32])
#define FLAG_P(c) (&g_flags[16 * 32 + NCTA * 64 + (c) * 32])
#define FLAG_EPOCH(c) (&g_flags[16 * 32 + NCTA * 96 + (c) * 32])
#define STAMP(i)
#define STAMPW(i)
#define TRACE()

template<uint32_t BHI> __device__ __forceinline__ void wg_rs_n192(float* d, uint32_t a0, uint32_t a1, uint32_t a2, uint32_t a3, uint32_t b) {
  asm volatile("{\n.reg .pred p;\n.reg .b64 db;\nsetp.ne.b32 p, 1, 0;\nmov.b64 db, {%100, %101};\n"
    "wgmma.mma_async.sync.aligned.m64n192k16.f32.bf16.bf16 {%0, %1, %2, %3, %4, %5, %6, %7, %8, %9, %10, %11, %12, %13, %14, %15, %16, %17, %18, %19, %20, %21, %22, %23, %24, %25, %26, %27, %28, %29, %30, %31, %32, %33, %34, %35, %36, %37, %38, %39, %40, %41, %42, %43, %44, %45, %46, %47, %48, %49, %50, %51, %52, %53, %54, %55, %56, %57, %58, %59, %60, %61, %62, %63, %64, %65, %66, %67, %68, %69, %70, %71, %72, %73, %74, %75, %76, %77, %78, %79, %80, %81, %82, %83, %84, %85, %86, %87, %88, %89, %90, %91, %92, %93, %94, %95}, {%96, %97, %98, %99}, db, p, 1, 1, 1;\n}\n"
    : "+f"(d[0]), "+f"(d[1]), "+f"(d[2]), "+f"(d[3]), "+f"(d[4]), "+f"(d[5]), "+f"(d[6]), "+f"(d[7]), "+f"(d[8]), "+f"(d[9]), "+f"(d[10]), "+f"(d[11]), "+f"(d[12]), "+f"(d[13]), "+f"(d[14]), "+f"(d[15]), "+f"(d[16]), "+f"(d[17]), "+f"(d[18]), "+f"(d[19]), "+f"(d[20]), "+f"(d[21]), "+f"(d[22]), "+f"(d[23]), "+f"(d[24]), "+f"(d[25]), "+f"(d[26]), "+f"(d[27]), "+f"(d[28]), "+f"(d[29]), "+f"(d[30]), "+f"(d[31]), "+f"(d[32]), "+f"(d[33]), "+f"(d[34]), "+f"(d[35]), "+f"(d[36]), "+f"(d[37]), "+f"(d[38]), "+f"(d[39]), "+f"(d[40]), "+f"(d[41]), "+f"(d[42]), "+f"(d[43]), "+f"(d[44]), "+f"(d[45]), "+f"(d[46]), "+f"(d[47]), "+f"(d[48]), "+f"(d[49]), "+f"(d[50]), "+f"(d[51]), "+f"(d[52]), "+f"(d[53]), "+f"(d[54]), "+f"(d[55]), "+f"(d[56]), "+f"(d[57]), "+f"(d[58]), "+f"(d[59]), "+f"(d[60]), "+f"(d[61]), "+f"(d[62]), "+f"(d[63]), "+f"(d[64]), "+f"(d[65]), "+f"(d[66]), "+f"(d[67]), "+f"(d[68]), "+f"(d[69]), "+f"(d[70]), "+f"(d[71]), "+f"(d[72]), "+f"(d[73]), "+f"(d[74]), "+f"(d[75]), "+f"(d[76]), "+f"(d[77]), "+f"(d[78]), "+f"(d[79]), "+f"(d[80]), "+f"(d[81]), "+f"(d[82]), "+f"(d[83]), "+f"(d[84]), "+f"(d[85]), "+f"(d[86]), "+f"(d[87]), "+f"(d[88]), "+f"(d[89]), "+f"(d[90]), "+f"(d[91]), "+f"(d[92]), "+f"(d[93]), "+f"(d[94]), "+f"(d[95])
    : "r"(a0), "r"(a1), "r"(a2), "r"(a3), "r"(b), "n"(BHI));
}
template<uint32_t BHI> __device__ __forceinline__ void wg_rs_z_n192(float* d, uint32_t a0, uint32_t a1, uint32_t a2, uint32_t a3, uint32_t b) {
  asm volatile("{\n.reg .pred p;\n.reg .b64 db;\nsetp.ne.b32 p, 0, 0;\nmov.b64 db, {%100, %101};\n"
    "wgmma.mma_async.sync.aligned.m64n192k16.f32.bf16.bf16 {%0, %1, %2, %3, %4, %5, %6, %7, %8, %9, %10, %11, %12, %13, %14, %15, %16, %17, %18, %19, %20, %21, %22, %23, %24, %25, %26, %27, %28, %29, %30, %31, %32, %33, %34, %35, %36, %37, %38, %39, %40, %41, %42, %43, %44, %45, %46, %47, %48, %49, %50, %51, %52, %53, %54, %55, %56, %57, %58, %59, %60, %61, %62, %63, %64, %65, %66, %67, %68, %69, %70, %71, %72, %73, %74, %75, %76, %77, %78, %79, %80, %81, %82, %83, %84, %85, %86, %87, %88, %89, %90, %91, %92, %93, %94, %95}, {%96, %97, %98, %99}, db, p, 1, 1, 1;\n}\n"
    : "=f"(d[0]), "=f"(d[1]), "=f"(d[2]), "=f"(d[3]), "=f"(d[4]), "=f"(d[5]), "=f"(d[6]), "=f"(d[7]), "=f"(d[8]), "=f"(d[9]), "=f"(d[10]), "=f"(d[11]), "=f"(d[12]), "=f"(d[13]), "=f"(d[14]), "=f"(d[15]), "=f"(d[16]), "=f"(d[17]), "=f"(d[18]), "=f"(d[19]), "=f"(d[20]), "=f"(d[21]), "=f"(d[22]), "=f"(d[23]), "=f"(d[24]), "=f"(d[25]), "=f"(d[26]), "=f"(d[27]), "=f"(d[28]), "=f"(d[29]), "=f"(d[30]), "=f"(d[31]), "=f"(d[32]), "=f"(d[33]), "=f"(d[34]), "=f"(d[35]), "=f"(d[36]), "=f"(d[37]), "=f"(d[38]), "=f"(d[39]), "=f"(d[40]), "=f"(d[41]), "=f"(d[42]), "=f"(d[43]), "=f"(d[44]), "=f"(d[45]), "=f"(d[46]), "=f"(d[47]), "=f"(d[48]), "=f"(d[49]), "=f"(d[50]), "=f"(d[51]), "=f"(d[52]), "=f"(d[53]), "=f"(d[54]), "=f"(d[55]), "=f"(d[56]), "=f"(d[57]), "=f"(d[58]), "=f"(d[59]), "=f"(d[60]), "=f"(d[61]), "=f"(d[62]), "=f"(d[63]), "=f"(d[64]), "=f"(d[65]), "=f"(d[66]), "=f"(d[67]), "=f"(d[68]), "=f"(d[69]), "=f"(d[70]), "=f"(d[71]), "=f"(d[72]), "=f"(d[73]), "=f"(d[74]), "=f"(d[75]), "=f"(d[76]), "=f"(d[77]), "=f"(d[78]), "=f"(d[79]), "=f"(d[80]), "=f"(d[81]), "=f"(d[82]), "=f"(d[83]), "=f"(d[84]), "=f"(d[85]), "=f"(d[86]), "=f"(d[87]), "=f"(d[88]), "=f"(d[89]), "=f"(d[90]), "=f"(d[91]), "=f"(d[92]), "=f"(d[93]), "=f"(d[94]), "=f"(d[95])
    : "r"(a0), "r"(a1), "r"(a2), "r"(a3), "r"(b), "n"(BHI));
}
template<uint32_t AHI, uint32_t BHI> __device__ __forceinline__ void wg_ss_n128(float* d, uint32_t a, uint32_t b) {
  asm volatile("{\n.reg .pred p;\n.reg .b64 da, db;\nsetp.ne.b32 p, 1, 0;\nmov.b64 da, {%64, %66};\nmov.b64 db, {%65, %67};\n"
    "wgmma.mma_async.sync.aligned.m64n128k16.f32.bf16.bf16 {%0, %1, %2, %3, %4, %5, %6, %7, %8, %9, %10, %11, %12, %13, %14, %15, %16, %17, %18, %19, %20, %21, %22, %23, %24, %25, %26, %27, %28, %29, %30, %31, %32, %33, %34, %35, %36, %37, %38, %39, %40, %41, %42, %43, %44, %45, %46, %47, %48, %49, %50, %51, %52, %53, %54, %55, %56, %57, %58, %59, %60, %61, %62, %63}, da, db, p, 1, 1, 0, 1;\n}\n"
    : "+f"(d[0]), "+f"(d[1]), "+f"(d[2]), "+f"(d[3]), "+f"(d[4]), "+f"(d[5]), "+f"(d[6]), "+f"(d[7]), "+f"(d[8]), "+f"(d[9]), "+f"(d[10]), "+f"(d[11]), "+f"(d[12]), "+f"(d[13]), "+f"(d[14]), "+f"(d[15]), "+f"(d[16]), "+f"(d[17]), "+f"(d[18]), "+f"(d[19]), "+f"(d[20]), "+f"(d[21]), "+f"(d[22]), "+f"(d[23]), "+f"(d[24]), "+f"(d[25]), "+f"(d[26]), "+f"(d[27]), "+f"(d[28]), "+f"(d[29]), "+f"(d[30]), "+f"(d[31]), "+f"(d[32]), "+f"(d[33]), "+f"(d[34]), "+f"(d[35]), "+f"(d[36]), "+f"(d[37]), "+f"(d[38]), "+f"(d[39]), "+f"(d[40]), "+f"(d[41]), "+f"(d[42]), "+f"(d[43]), "+f"(d[44]), "+f"(d[45]), "+f"(d[46]), "+f"(d[47]), "+f"(d[48]), "+f"(d[49]), "+f"(d[50]), "+f"(d[51]), "+f"(d[52]), "+f"(d[53]), "+f"(d[54]), "+f"(d[55]), "+f"(d[56]), "+f"(d[57]), "+f"(d[58]), "+f"(d[59]), "+f"(d[60]), "+f"(d[61]), "+f"(d[62]), "+f"(d[63])
    : "r"(a), "r"(b), "n"(AHI), "n"(BHI));
}
template<uint32_t AHI, uint32_t BHI> __device__ __forceinline__ void wg_ss_z_n128(float* d, uint32_t a, uint32_t b) {
  asm volatile("{\n.reg .pred p;\n.reg .b64 da, db;\nsetp.ne.b32 p, 0, 0;\nmov.b64 da, {%64, %66};\nmov.b64 db, {%65, %67};\n"
    "wgmma.mma_async.sync.aligned.m64n128k16.f32.bf16.bf16 {%0, %1, %2, %3, %4, %5, %6, %7, %8, %9, %10, %11, %12, %13, %14, %15, %16, %17, %18, %19, %20, %21, %22, %23, %24, %25, %26, %27, %28, %29, %30, %31, %32, %33, %34, %35, %36, %37, %38, %39, %40, %41, %42, %43, %44, %45, %46, %47, %48, %49, %50, %51, %52, %53, %54, %55, %56, %57, %58, %59, %60, %61, %62, %63}, da, db, p, 1, 1, 0, 1;\n}\n"
    : "=f"(d[0]), "=f"(d[1]), "=f"(d[2]), "=f"(d[3]), "=f"(d[4]), "=f"(d[5]), "=f"(d[6]), "=f"(d[7]), "=f"(d[8]), "=f"(d[9]), "=f"(d[10]), "=f"(d[11]), "=f"(d[12]), "=f"(d[13]), "=f"(d[14]), "=f"(d[15]), "=f"(d[16]), "=f"(d[17]), "=f"(d[18]), "=f"(d[19]), "=f"(d[20]), "=f"(d[21]), "=f"(d[22]), "=f"(d[23]), "=f"(d[24]), "=f"(d[25]), "=f"(d[26]), "=f"(d[27]), "=f"(d[28]), "=f"(d[29]), "=f"(d[30]), "=f"(d[31]), "=f"(d[32]), "=f"(d[33]), "=f"(d[34]), "=f"(d[35]), "=f"(d[36]), "=f"(d[37]), "=f"(d[38]), "=f"(d[39]), "=f"(d[40]), "=f"(d[41]), "=f"(d[42]), "=f"(d[43]), "=f"(d[44]), "=f"(d[45]), "=f"(d[46]), "=f"(d[47]), "=f"(d[48]), "=f"(d[49]), "=f"(d[50]), "=f"(d[51]), "=f"(d[52]), "=f"(d[53]), "=f"(d[54]), "=f"(d[55]), "=f"(d[56]), "=f"(d[57]), "=f"(d[58]), "=f"(d[59]), "=f"(d[60]), "=f"(d[61]), "=f"(d[62]), "=f"(d[63])
    : "r"(a), "r"(b), "n"(AHI), "n"(BHI));
}
template<uint32_t AHI, uint32_t BHI> __device__ __forceinline__ void wg_ss_n160(float* d, uint32_t a, uint32_t b) {
  asm volatile("{\n.reg .pred p;\n.reg .b64 da, db;\nsetp.ne.b32 p, 1, 0;\nmov.b64 da, {%80, %82};\nmov.b64 db, {%81, %83};\n"
    "wgmma.mma_async.sync.aligned.m64n160k16.f32.bf16.bf16 {%0, %1, %2, %3, %4, %5, %6, %7, %8, %9, %10, %11, %12, %13, %14, %15, %16, %17, %18, %19, %20, %21, %22, %23, %24, %25, %26, %27, %28, %29, %30, %31, %32, %33, %34, %35, %36, %37, %38, %39, %40, %41, %42, %43, %44, %45, %46, %47, %48, %49, %50, %51, %52, %53, %54, %55, %56, %57, %58, %59, %60, %61, %62, %63, %64, %65, %66, %67, %68, %69, %70, %71, %72, %73, %74, %75, %76, %77, %78, %79}, da, db, p, 1, 1, 0, 1;\n}\n"
    : "+f"(d[0]), "+f"(d[1]), "+f"(d[2]), "+f"(d[3]), "+f"(d[4]), "+f"(d[5]), "+f"(d[6]), "+f"(d[7]), "+f"(d[8]), "+f"(d[9]), "+f"(d[10]), "+f"(d[11]), "+f"(d[12]), "+f"(d[13]), "+f"(d[14]), "+f"(d[15]), "+f"(d[16]), "+f"(d[17]), "+f"(d[18]), "+f"(d[19]), "+f"(d[20]), "+f"(d[21]), "+f"(d[22]), "+f"(d[23]), "+f"(d[24]), "+f"(d[25]), "+f"(d[26]), "+f"(d[27]), "+f"(d[28]), "+f"(d[29]), "+f"(d[30]), "+f"(d[31]), "+f"(d[32]), "+f"(d[33]), "+f"(d[34]), "+f"(d[35]), "+f"(d[36]), "+f"(d[37]), "+f"(d[38]), "+f"(d[39]), "+f"(d[40]), "+f"(d[41]), "+f"(d[42]), "+f"(d[43]), "+f"(d[44]), "+f"(d[45]), "+f"(d[46]), "+f"(d[47]), "+f"(d[48]), "+f"(d[49]), "+f"(d[50]), "+f"(d[51]), "+f"(d[52]), "+f"(d[53]), "+f"(d[54]), "+f"(d[55]), "+f"(d[56]), "+f"(d[57]), "+f"(d[58]), "+f"(d[59]), "+f"(d[60]), "+f"(d[61]), "+f"(d[62]), "+f"(d[63]), "+f"(d[64]), "+f"(d[65]), "+f"(d[66]), "+f"(d[67]), "+f"(d[68]), "+f"(d[69]), "+f"(d[70]), "+f"(d[71]), "+f"(d[72]), "+f"(d[73]), "+f"(d[74]), "+f"(d[75]), "+f"(d[76]), "+f"(d[77]), "+f"(d[78]), "+f"(d[79])
    : "r"(a), "r"(b), "n"(AHI), "n"(BHI));
}
template<uint32_t AHI, uint32_t BHI> __device__ __forceinline__ void wg_ss_z_n160(float* d, uint32_t a, uint32_t b) {
  asm volatile("{\n.reg .pred p;\n.reg .b64 da, db;\nsetp.ne.b32 p, 0, 0;\nmov.b64 da, {%80, %82};\nmov.b64 db, {%81, %83};\n"
    "wgmma.mma_async.sync.aligned.m64n160k16.f32.bf16.bf16 {%0, %1, %2, %3, %4, %5, %6, %7, %8, %9, %10, %11, %12, %13, %14, %15, %16, %17, %18, %19, %20, %21, %22, %23, %24, %25, %26, %27, %28, %29, %30, %31, %32, %33, %34, %35, %36, %37, %38, %39, %40, %41, %42, %43, %44, %45, %46, %47, %48, %49, %50, %51, %52, %53, %54, %55, %56, %57, %58, %59, %60, %61, %62, %63, %64, %65, %66, %67, %68, %69, %70, %71, %72, %73, %74, %75, %76, %77, %78, %79}, da, db, p, 1, 1, 0, 1;\n}\n"
    : "=f"(d[0]), "=f"(d[1]), "=f"(d[2]), "=f"(d[3]), "=f"(d[4]), "=f"(d[5]), "=f"(d[6]), "=f"(d[7]), "=f"(d[8]), "=f"(d[9]), "=f"(d[10]), "=f"(d[11]), "=f"(d[12]), "=f"(d[13]), "=f"(d[14]), "=f"(d[15]), "=f"(d[16]), "=f"(d[17]), "=f"(d[18]), "=f"(d[19]), "=f"(d[20]), "=f"(d[21]), "=f"(d[22]), "=f"(d[23]), "=f"(d[24]), "=f"(d[25]), "=f"(d[26]), "=f"(d[27]), "=f"(d[28]), "=f"(d[29]), "=f"(d[30]), "=f"(d[31]), "=f"(d[32]), "=f"(d[33]), "=f"(d[34]), "=f"(d[35]), "=f"(d[36]), "=f"(d[37]), "=f"(d[38]), "=f"(d[39]), "=f"(d[40]), "=f"(d[41]), "=f"(d[42]), "=f"(d[43]), "=f"(d[44]), "=f"(d[45]), "=f"(d[46]), "=f"(d[47]), "=f"(d[48]), "=f"(d[49]), "=f"(d[50]), "=f"(d[51]), "=f"(d[52]), "=f"(d[53]), "=f"(d[54]), "=f"(d[55]), "=f"(d[56]), "=f"(d[57]), "=f"(d[58]), "=f"(d[59]), "=f"(d[60]), "=f"(d[61]), "=f"(d[62]), "=f"(d[63]), "=f"(d[64]), "=f"(d[65]), "=f"(d[66]), "=f"(d[67]), "=f"(d[68]), "=f"(d[69]), "=f"(d[70]), "=f"(d[71]), "=f"(d[72]), "=f"(d[73]), "=f"(d[74]), "=f"(d[75]), "=f"(d[76]), "=f"(d[77]), "=f"(d[78]), "=f"(d[79])
    : "r"(a), "r"(b), "n"(AHI), "n"(BHI));
}
template<uint32_t BHI> __device__ __forceinline__ void wg_rs_n32(float* d, uint32_t a0, uint32_t a1, uint32_t a2, uint32_t a3, uint32_t b) {
  asm volatile("{\n.reg .pred p;\n.reg .b64 db;\nsetp.ne.b32 p, 1, 0;\nmov.b64 db, {%20, %21};\n"
    "wgmma.mma_async.sync.aligned.m64n32k16.f32.bf16.bf16 {%0, %1, %2, %3, %4, %5, %6, %7, %8, %9, %10, %11, %12, %13, %14, %15}, {%16, %17, %18, %19}, db, p, 1, 1, 1;\n}\n"
    : "+f"(d[0]), "+f"(d[1]), "+f"(d[2]), "+f"(d[3]), "+f"(d[4]), "+f"(d[5]), "+f"(d[6]), "+f"(d[7]), "+f"(d[8]), "+f"(d[9]), "+f"(d[10]), "+f"(d[11]), "+f"(d[12]), "+f"(d[13]), "+f"(d[14]), "+f"(d[15])
    : "r"(a0), "r"(a1), "r"(a2), "r"(a3), "r"(b), "n"(BHI));
}
template<uint32_t BHI> __device__ __forceinline__ void wg_rs_z_n32(float* d, uint32_t a0, uint32_t a1, uint32_t a2, uint32_t a3, uint32_t b) {
  asm volatile("{\n.reg .pred p;\n.reg .b64 db;\nsetp.ne.b32 p, 0, 0;\nmov.b64 db, {%20, %21};\n"
    "wgmma.mma_async.sync.aligned.m64n32k16.f32.bf16.bf16 {%0, %1, %2, %3, %4, %5, %6, %7, %8, %9, %10, %11, %12, %13, %14, %15}, {%16, %17, %18, %19}, db, p, 1, 1, 1;\n}\n"
    : "=f"(d[0]), "=f"(d[1]), "=f"(d[2]), "=f"(d[3]), "=f"(d[4]), "=f"(d[5]), "=f"(d[6]), "=f"(d[7]), "=f"(d[8]), "=f"(d[9]), "=f"(d[10]), "=f"(d[11]), "=f"(d[12]), "=f"(d[13]), "=f"(d[14]), "=f"(d[15])
    : "r"(a0), "r"(a1), "r"(a2), "r"(a3), "r"(b), "n"(BHI));
}
template<uint32_t BHI> __device__ __forceinline__ void wg_rs_n64(float* d, uint32_t a0, uint32_t a1, uint32_t a2, uint32_t a3, uint32_t b) {
  asm volatile("{\n.reg .pred p;\n.reg .b64 db;\nsetp.ne.b32 p, 1, 0;\nmov.b64 db, {%36, %37};\n"
    "wgmma.mma_async.sync.aligned.m64n64k16.f32.bf16.bf16 {%0, %1, %2, %3, %4, %5, %6, %7, %8, %9, %10, %11, %12, %13, %14, %15, %16, %17, %18, %19, %20, %21, %22, %23, %24, %25, %26, %27, %28, %29, %30, %31}, {%32, %33, %34, %35}, db, p, 1, 1, 0;\n}\n"
    : "+f"(d[0]), "+f"(d[1]), "+f"(d[2]), "+f"(d[3]), "+f"(d[4]), "+f"(d[5]), "+f"(d[6]), "+f"(d[7]), "+f"(d[8]), "+f"(d[9]), "+f"(d[10]), "+f"(d[11]), "+f"(d[12]), "+f"(d[13]), "+f"(d[14]), "+f"(d[15]), "+f"(d[16]), "+f"(d[17]), "+f"(d[18]), "+f"(d[19]), "+f"(d[20]), "+f"(d[21]), "+f"(d[22]), "+f"(d[23]), "+f"(d[24]), "+f"(d[25]), "+f"(d[26]), "+f"(d[27]), "+f"(d[28]), "+f"(d[29]), "+f"(d[30]), "+f"(d[31])
    : "r"(a0), "r"(a1), "r"(a2), "r"(a3), "r"(b), "n"(BHI));
}
template<uint32_t BHI> __device__ __forceinline__ void wg_rs_z_n64(float* d, uint32_t a0, uint32_t a1, uint32_t a2, uint32_t a3, uint32_t b) {
  asm volatile("{\n.reg .pred p;\n.reg .b64 db;\nsetp.ne.b32 p, 0, 0;\nmov.b64 db, {%36, %37};\n"
    "wgmma.mma_async.sync.aligned.m64n64k16.f32.bf16.bf16 {%0, %1, %2, %3, %4, %5, %6, %7, %8, %9, %10, %11, %12, %13, %14, %15, %16, %17, %18, %19, %20, %21, %22, %23, %24, %25, %26, %27, %28, %29, %30, %31}, {%32, %33, %34, %35}, db, p, 1, 1, 0;\n}\n"
    : "=f"(d[0]), "=f"(d[1]), "=f"(d[2]), "=f"(d[3]), "=f"(d[4]), "=f"(d[5]), "=f"(d[6]), "=f"(d[7]), "=f"(d[8]), "=f"(d[9]), "=f"(d[10]), "=f"(d[11]), "=f"(d[12]), "=f"(d[13]), "=f"(d[14]), "=f"(d[15]), "=f"(d[16]), "=f"(d[17]), "=f"(d[18]), "=f"(d[19]), "=f"(d[20]), "=f"(d[21]), "=f"(d[22]), "=f"(d[23]), "=f"(d[24]), "=f"(d[25]), "=f"(d[26]), "=f"(d[27]), "=f"(d[28]), "=f"(d[29]), "=f"(d[30]), "=f"(d[31])
    : "r"(a0), "r"(a1), "r"(a2), "r"(a3), "r"(b), "n"(BHI));
}
template<uint32_t BHI> __device__ __forceinline__ void wg_rs_n24(float* d, uint32_t a0, uint32_t a1, uint32_t a2, uint32_t a3, uint32_t b) {
  asm volatile("{\n.reg .pred p;\n.reg .b64 db;\nsetp.ne.b32 p, 1, 0;\nmov.b64 db, {%16, %17};\n"
    "wgmma.mma_async.sync.aligned.m64n24k16.f32.bf16.bf16 {%0, %1, %2, %3, %4, %5, %6, %7, %8, %9, %10, %11}, {%12, %13, %14, %15}, db, p, 1, 1, 1;\n}\n"
    : "+f"(d[0]), "+f"(d[1]), "+f"(d[2]), "+f"(d[3]), "+f"(d[4]), "+f"(d[5]), "+f"(d[6]), "+f"(d[7]), "+f"(d[8]), "+f"(d[9]), "+f"(d[10]), "+f"(d[11])
    : "r"(a0), "r"(a1), "r"(a2), "r"(a3), "r"(b), "n"(BHI));
}
template<uint32_t BHI> __device__ __forceinline__ void wg_rs_z_n24(float* d, uint32_t a0, uint32_t a1, uint32_t a2, uint32_t a3, uint32_t b) {
  asm volatile("{\n.reg .pred p;\n.reg .b64 db;\nsetp.ne.b32 p, 0, 0;\nmov.b64 db, {%16, %17};\n"
    "wgmma.mma_async.sync.aligned.m64n24k16.f32.bf16.bf16 {%0, %1, %2, %3, %4, %5, %6, %7, %8, %9, %10, %11}, {%12, %13, %14, %15}, db, p, 1, 1, 1;\n}\n"
    : "=f"(d[0]), "=f"(d[1]), "=f"(d[2]), "=f"(d[3]), "=f"(d[4]), "=f"(d[5]), "=f"(d[6]), "=f"(d[7]), "=f"(d[8]), "=f"(d[9]), "=f"(d[10]), "=f"(d[11])
    : "r"(a0), "r"(a1), "r"(a2), "r"(a3), "r"(b), "n"(BHI));
}
template<uint32_t BHI> __device__ __forceinline__ void wg_rsb_n64(float* d, uint32_t a0, uint32_t a1, uint32_t a2, uint32_t a3, uint32_t b) {
  asm volatile("{\n.reg .pred p;\n.reg .b64 db;\nsetp.ne.b32 p, 1, 0;\nmov.b64 db, {%36, %37};\n"
    "wgmma.mma_async.sync.aligned.m64n64k16.f32.bf16.bf16 {%0, %1, %2, %3, %4, %5, %6, %7, %8, %9, %10, %11, %12, %13, %14, %15, %16, %17, %18, %19, %20, %21, %22, %23, %24, %25, %26, %27, %28, %29, %30, %31}, {%32, %33, %34, %35}, db, p, 1, 1, 1;\n}\n"
    : "+f"(d[0]), "+f"(d[1]), "+f"(d[2]), "+f"(d[3]), "+f"(d[4]), "+f"(d[5]), "+f"(d[6]), "+f"(d[7]), "+f"(d[8]), "+f"(d[9]), "+f"(d[10]), "+f"(d[11]), "+f"(d[12]), "+f"(d[13]), "+f"(d[14]), "+f"(d[15]), "+f"(d[16]), "+f"(d[17]), "+f"(d[18]), "+f"(d[19]), "+f"(d[20]), "+f"(d[21]), "+f"(d[22]), "+f"(d[23]), "+f"(d[24]), "+f"(d[25]), "+f"(d[26]), "+f"(d[27]), "+f"(d[28]), "+f"(d[29]), "+f"(d[30]), "+f"(d[31])
    : "r"(a0), "r"(a1), "r"(a2), "r"(a3), "r"(b), "n"(BHI));
}
template<uint32_t BHI> __device__ __forceinline__ void wg_rsb_z_n64(float* d, uint32_t a0, uint32_t a1, uint32_t a2, uint32_t a3, uint32_t b) {
  asm volatile("{\n.reg .pred p;\n.reg .b64 db;\nsetp.ne.b32 p, 0, 0;\nmov.b64 db, {%36, %37};\n"
    "wgmma.mma_async.sync.aligned.m64n64k16.f32.bf16.bf16 {%0, %1, %2, %3, %4, %5, %6, %7, %8, %9, %10, %11, %12, %13, %14, %15, %16, %17, %18, %19, %20, %21, %22, %23, %24, %25, %26, %27, %28, %29, %30, %31}, {%32, %33, %34, %35}, db, p, 1, 1, 1;\n}\n"
    : "=f"(d[0]), "=f"(d[1]), "=f"(d[2]), "=f"(d[3]), "=f"(d[4]), "=f"(d[5]), "=f"(d[6]), "=f"(d[7]), "=f"(d[8]), "=f"(d[9]), "=f"(d[10]), "=f"(d[11]), "=f"(d[12]), "=f"(d[13]), "=f"(d[14]), "=f"(d[15]), "=f"(d[16]), "=f"(d[17]), "=f"(d[18]), "=f"(d[19]), "=f"(d[20]), "=f"(d[21]), "=f"(d[22]), "=f"(d[23]), "=f"(d[24]), "=f"(d[25]), "=f"(d[26]), "=f"(d[27]), "=f"(d[28]), "=f"(d[29]), "=f"(d[30]), "=f"(d[31])
    : "r"(a0), "r"(a1), "r"(a2), "r"(a3), "r"(b), "n"(BHI));
}

__device__ __forceinline__ void wg_fence() { asm volatile("wgmma.fence.sync.aligned;" ::: "memory"); }
__device__ __forceinline__ void wg_commit() { asm volatile("wgmma.commit_group.sync.aligned;" ::: "memory"); }
template <int N> __device__ __forceinline__ void wg_wait() { asm volatile("wgmma.wait_group.sync.aligned %0;" ::"n"(N) : "memory"); }
template <int R> __device__ __forceinline__ void pin(float* d) {
#pragma unroll
  for (int i = 0; i < R; i++) asm volatile("" : "+f"(d[i])::"memory");
}
template <int R> __device__ __forceinline__ void pin(uint32_t* d) {
#pragma unroll
  for (int i = 0; i < R; i++) asm volatile("" : "+r"(d[i])::"memory");
}
__device__ __forceinline__ float ex2(float x) { float y; asm("ex2.approx.ftz.f32 %0, %1;" : "=f"(y) : "f"(x)); return y; }
__device__ __forceinline__ float tanh_fast(float x) { float y; asm("tanh.approx.f32 %0, %1;" : "=f"(y) : "f"(x)); return y; }
__device__ __forceinline__ uint32_t pack(float lo, float hi) { uint32_t r; asm("cvt.rn.bf16x2.f32 %0, %1, %2;" : "=r"(r) : "f"(hi), "f"(lo)); return r; }
__device__ __forceinline__ float bf_lo(uint32_t v) { return __uint_as_float(v << 16); }
__device__ __forceinline__ float bf_hi(uint32_t v) { return __uint_as_float(v & 0xffff0000u); }
__device__ __forceinline__ float bf_round(float x) { return bf_lo(pack(x, 0.f)); }

__device__ __forceinline__ void mbar_init(uint32_t bar, uint32_t cnt) { asm volatile("mbarrier.init.shared::cta.b64 [%0], %1;" ::"r"(bar), "r"(cnt) : "memory"); }
__device__ __forceinline__ void mbar_expect(uint32_t bar, uint32_t bytes) { asm volatile("mbarrier.arrive.expect_tx.shared::cta.b64 _, [%0], %1;" ::"r"(bar), "r"(bytes) : "memory"); }
__device__ __forceinline__ void mbar_wait(uint32_t bar, uint32_t parity) {
  asm volatile(
      "{\n.reg .pred p;\n.reg .u32 c;\n"
      "mbarrier.try_wait.parity.shared::cta.b64 p, [%0], %1;\n"
      "@p bra.uni DONE;\n"
      "mov.u32 c, 0;\n"
      "LOOP:\n"
      "mbarrier.try_wait.parity.shared::cta.b64 p, [%0], %1;\n"
      "@p bra.uni DONE;\n"
      "add.u32 c, c, 1;\n"
      "setp.lt.u32 p, c, 0x4000000;\n"
      "@p bra.uni LOOP;\n"
      "trap;\n"
      "DONE:\n}\n" ::"r"(bar), "r"(parity) : "memory");
}
__device__ __forceinline__ uint32_t mbar_test(uint32_t bar, uint32_t parity) {
  uint32_t ok;
  asm volatile("{\n.reg .pred p;\nmbarrier.test_wait.parity.shared::cta.b64 p, [%1], %2;\nselp.u32 %0, 1, 0, p;\n}\n" : "=r"(ok) : "r"(bar), "r"(parity) : "memory");
  return ok;
}
__device__ __forceinline__ void mbar_arrive_if(uint32_t bar, uint32_t cond) {
  asm volatile("{\n.reg .pred p;\nsetp.ne.u32 p, %1, 0;\n@p mbarrier.arrive.shared::cta.b64 _, [%0];\n}\n" ::"r"(bar), "r"(cond) : "memory");
}
__device__ __forceinline__ uint32_t bsub2(uint32_t a, uint32_t b) { uint32_t d; asm("sub.rn.bf16x2 %0, %1, %2;" : "=r"(d) : "r"(a), "r"(b)); return d; }
__device__ __forceinline__ uint32_t bscale2(uint32_t d, uint32_t hi, uint32_t lo) {
  uint32_t t, r;
  asm("mul.rn.bf16x2 %0, %1, %2;" : "=r"(t) : "r"(d), "r"(lo));
  asm("fma.rn.bf16x2 %0, %1, %2, %3;" : "=r"(r) : "r"(d), "r"(hi), "r"(t));
  return r;
}
__device__ __forceinline__ void flag_wait(const uint32_t* f, uint32_t target) {
  asm volatile(
      "{\n.reg .pred p;\n.reg .u32 c, v;\n"
      "mov.u32 c, 0;\n"
      "LOOP:\n"
      "ld.acquire.gpu.global.u32 v, [%0];\n"
      "sub.u32 v, v, %1;\n"
      "setp.ge.s32 p, v, 0;\n"
      "@p bra DONE;\n"
      "add.u32 c, c, 1;\n"
      "setp.lt.u32 p, c, 0x1000000;\n"
      "@p bra LOOP;\n"
      "trap;\n"
      "DONE:\n}\n" ::"l"(f), "r"(target) : "memory");
}
__device__ __forceinline__ uint32_t flag_wait_v(const uint32_t* f, uint32_t target) {
  uint32_t v;
  asm volatile(
      "{\n.reg .pred p;\n.reg .u32 c, d;\n"
      "mov.u32 c, 0;\n"
      "LOOP:\n"
      "ld.acquire.gpu.global.u32 %0, [%1];\n"
      "sub.u32 d, %0, %2;\n"
      "setp.ge.s32 p, d, 0;\n"
      "@p bra DONE;\n"
      "add.u32 c, c, 1;\n"
      "setp.lt.u32 p, c, 0x1000000;\n"
      "@p bra LOOP;\n"
      "trap;\n"
      "DONE:\n}\n" : "=&r"(v) : "l"(f), "r"(target) : "memory");
  return v;
}
__device__ __forceinline__ float sqrt_fast(float x) { float y; asm("sqrt.approx.f32 %0, %1;" : "=f"(y) : "f"(x)); return y; }
__device__ __forceinline__ float rcp_fast(float x) { float y; asm("rcp.approx.ftz.f32 %0, %1;" : "=f"(y) : "f"(x)); return y; }
__device__ __forceinline__ void ldsm4(uint32_t* v, uint32_t addr) {
  asm volatile("ldmatrix.sync.aligned.m8n8.x4.shared.b16 {%0,%1,%2,%3}, [%4];" : "=r"(v[0]), "=r"(v[1]), "=r"(v[2]), "=r"(v[3]) : "r"(addr) : "memory");
}
__device__ __forceinline__ void stsm4(uint32_t addr, uint32_t a, uint32_t b, uint32_t c, uint32_t d) {
  asm volatile("stmatrix.sync.aligned.m8n8.x4.shared.b16 [%0], {%1,%2,%3,%4};" ::"r"(addr), "r"(a), "r"(b), "r"(c), "r"(d) : "memory");
}
__device__ __forceinline__ void flag_add(uint32_t* f) { asm volatile("red.relaxed.gpu.global.add.u32 [%0], 1;" ::"l"(f) : "memory"); }
__device__ __forceinline__ void fence_gpu() { asm volatile("fence.acq_rel.gpu;" ::: "memory"); }
#define FENCE_G 1
__device__ __forceinline__ void fence_async() { if (FENCE_G) asm volatile("fence.proxy.async.global;" ::: "memory"); else asm volatile("fence.proxy.async;" ::: "memory"); }
__device__ __forceinline__ void tma2d(uint32_t dst, const CUtensorMap* tm, uint32_t bar, int c0, int c1) {
  asm volatile("cp.async.bulk.tensor.2d.shared::cluster.global.mbarrier::complete_tx::bytes [%0], [%1, {%3, %4}], [%2];" ::"r"(dst), "l"(tm), "r"(bar), "r"(c0), "r"(c1) : "memory");
}
__device__ __forceinline__ void tma2d_h(uint32_t dst, const CUtensorMap* tm, uint32_t bar, int c0, int c1, uint64_t pol) {
  asm volatile("cp.async.bulk.tensor.2d.shared::cluster.global.mbarrier::complete_tx::bytes.L2::cache_hint [%0], [%1, {%3, %4}], [%2], %5;" ::"r"(dst), "l"(tm), "r"(bar), "r"(c0), "r"(c1), "l"(pol) : "memory");
}
__device__ __forceinline__ void bulk_s2g(void* dst, uint32_t src, uint32_t bytes) {
  asm volatile("cp.async.bulk.global.shared::cta.bulk_group [%0], [%1], %2;" ::"l"(dst), "r"(src), "r"(bytes) : "memory");
}
__device__ __forceinline__ void mma_ones(float* c, const uint32_t* a) {
  asm("mma.sync.aligned.m16n8k16.row.col.f32.bf16.bf16.f32 {%0,%1,%2,%3}, {%4,%5,%6,%7}, {%8,%8}, {%0,%1,%2,%3};"
      : "+f"(c[0]), "+f"(c[1]), "+f"(c[2]), "+f"(c[3]) : "r"(a[0]), "r"(a[1]), "r"(a[2]), "r"(a[3]), "r"(0x3f803f80u));
}
__device__ __forceinline__ void tma5d(uint32_t dst, const CUtensorMap* tm, uint32_t bar, int c0, int c4) {
  asm volatile("cp.async.bulk.tensor.5d.shared::cluster.global.mbarrier::complete_tx::bytes [%0], [%1, {%3, %5, %5, %5, %4}], [%2];" ::"r"(dst), "l"(tm), "r"(bar), "r"(c0), "r"(c4), "r"(0) : "memory");
}
__device__ __forceinline__ void tma3d(uint32_t dst, const CUtensorMap* tm, uint32_t bar, int c0, int c2) {
  asm volatile("cp.async.bulk.tensor.3d.shared::cluster.global.mbarrier::complete_tx::bytes [%0], [%1, {%3, %5, %4}], [%2];" ::"r"(dst), "l"(tm), "r"(bar), "r"(c0), "r"(c2), "r"(0) : "memory");
}
__device__ __forceinline__ void bulk_g2s(uint32_t dst, const void* src, uint32_t bytes, uint32_t bar) {
  asm volatile("cp.async.bulk.shared::cluster.global.mbarrier::complete_tx::bytes [%0], [%1], %2, [%3];" ::"r"(dst), "l"(src), "r"(bytes), "r"(bar) : "memory");
}
__device__ __forceinline__ void pf_line(const void* p) { asm volatile("prefetch.global.L2 [%0];" ::"l"(p) : "memory"); }
__device__ __forceinline__ int fresh_tid() { int v; asm volatile("mov.u32 %0, %%tid.x;" : "=r"(v)); return v; }
struct Att {
  float s[32];
  float o[12];
  uint32_t p[16];
  uint32_t q[8];
};

__device__ __forceinline__ float warp_sum(float v) {
#pragma unroll 1
  for (int d = 16; d; d >>= 1) v += __shfl_xor_sync(0xffffffffu, v, d);
  return v;
}
#define OPAQUE(x) asm volatile("" : "+r"(x))
__device__ __forceinline__ void attn_slow_row(int cta, uint32_t& w) {
  float mx = -INFINITY;
#pragma unroll 1
  for (uint32_t key = threadIdx.x & 31; key < SEQ; key += 32) {
    float s = 0.f;
#pragma unroll 1
    for (uint32_t v = 0; v < 9; v++) {
      OPAQUE(w); OPAQUE(key);
      const uint32_t hp = (w >> 4) & 3, pos = (v + hp) & 3;
      const uint32_t q = g_Q[(((cta * 4 + hp) * 2 + (v >> 3)) * 256 + ((w >> 6) & 7) * 32 + (w & 7) * 4 + pos) * 4 + 2 * ((v >> 2) & 1) + ((w >> 3) & 1)];
      const uint32_t u = g_KV[(4 * (cta & 7) + hp) * SEQ * 20 + (key >> 3) * 160 + (key & 7) * 4 + (v >> 2) * 32 + pos];
      s = fmaf(bf_lo(q), bf_lo(u), fmaf(bf_hi(q), bf_hi(u), s));
    }
    g_S[(cta * 8 + ((w >> 6) & 7)) * SEQ + key] = s;
    mx = fmaxf(mx, s);
  }
#pragma unroll 1
  for (int d = 16; d; d >>= 1) mx = fmaxf(mx, __shfl_xor_sync(0xffffffffu, mx, d));
  float l = 0.f;
#pragma unroll 1
  for (uint32_t key = threadIdx.x & 31; key < SEQ; key += 32) l += ex2(g_S[(cta * 8 + ((w >> 6) & 7)) * SEQ + key] - mx);
  l = 2.f * rcp_fast(warp_sum(l));
#pragma unroll 1
  for (uint32_t v = w >> 9; v < 9; v++) {
    float a = 0.f, b = 0.f;
#pragma unroll 1
    for (uint32_t key = threadIdx.x & 31; key < SEQ; key += 32) {
      OPAQUE(w); OPAQUE(v);
      const uint32_t hp = (w >> 4) & 3;
      const uint32_t u = g_KV[(4 * (cta & 7) + hp) * SEQ * 20 + (key >> 3) * 160 + (key & 7) * 4 + (v < 8 ? (3 + (v >> 2)) * 32 + (v & 3) : 64 + ((hp + 2) & 3))];
      const float p = ex2(g_S[(cta * 8 + ((w >> 6) & 7)) * SEQ + key] - mx);
      a = fmaf(p, bf_lo(u), a); b = fmaf(p, bf_hi(u), b);
    }
    a = warp_sum(a); b = warp_sum(b);
    OPAQUE(w);
    const uint32_t hp = (w >> 4) & 3;
    if ((threadIdx.x & 31) == 0) g_O[cta * 9 * 512 + (((w >> 6) & 7) * 16 + (w & 15)) * 4 + (v < 8 ? (2 * hp + (v >> 2)) * 512 + (v & 3) : 8 * 512 + hp)] = pack(a * l, b * l);
  }
}

__device__ __forceinline__ uint32_t bad_heads(uint32_t bad_addr, int wr) {
  uint32_t bad;
  __syncwarp();
  asm volatile("ld.volatile.shared.u32 %0, [%1];" : "=r"(bad) : "r"(bad_addr) : "memory");
  return __shfl_sync(0xffffffffu, (bad >> (4 * wr)) & 15, 0);
}
__device__ __forceinline__ void repair_rows(int cta, int wr, uint32_t bad, int last_head, bool final) {
#pragma unroll 1
  for (uint32_t w = wr * 64; w < wr * 64 + 64; w++) {
    if (!((bad >> ((w >> 4) & 3)) & 1)) continue;
    if (final && ((w >> 4) & 3) != last_head) w |= 8u << 9;
    attn_slow_row(cta, w);
    w &= 511;
  }
  __syncwarp();
}
__device__ __forceinline__ void o_normalise(const float* o, uint32_t* w, uint32_t& x0, uint32_t& x1, int hp, int lane, uint32_t bad_addr, int wr) {
  const int src = (lane & ~3) | ((hp + 1) & 3);
  float l0 = __shfl_sync(0xffffffffu, o[0], src), l1 = __shfl_sync(0xffffffffu, o[2], src);
  float sa = 0.f;
#pragma unroll
  for (int i = 0; i < 12; i++) sa += fabsf(o[i]);
  bool ok = (l0 <= 1.329228e36f) && (l1 <= 1.329228e36f) && (l0 > 0.f) && (l1 > 0.f) && (sa <= 3.0e38f);
  float i0 = 2.f * rcp_fast(l0), i1 = 2.f * rcp_fast(l1);
  w[0] = pack(o[4] * i0, o[5] * i0);
  w[1] = pack(o[6] * i1, o[7] * i1);
  w[2] = pack(o[8] * i0, o[9] * i0);
  w[3] = pack(o[10] * i1, o[11] * i1);
  if ((lane & 3) == ((hp + 2) & 3)) { x0 = pack(o[0] * i0, o[1] * i0); x1 = pack(o[2] * i1, o[3] * i1); }
  if (!ok) asm volatile("red.shared.or.b32 [%0], %1;" ::"r"(bad_addr), "r"(1u << (4 * wr + hp)) : "memory");
}

__device__ __forceinline__ void issue_pv(Att& a, uint32_t kdesc) {
  const uint32_t vdesc = kdesc + 192 + (LO_V - LO_K);
#pragma unroll
  for (int k = 0; k < 4; k++) wg_rs_n24<HI_V>(a.o, a.p[4 * k], a.p[4 * k + 1], a.p[4 * k + 2], a.p[4 * k + 3], vdesc + k * 48);
}
__device__ __forceinline__ void issue_att(Att& a, uint32_t kdesc) {
  issue_pv(a, kdesc);
  wg_rs_z_n64<HI_K>(a.s, a.q[0], a.q[1], a.q[2], a.q[3], kdesc);
  wg_rs_n64<HI_K>(a.s, a.q[4], a.q[5], a.q[6], a.q[7], kdesc + 16);
}
__device__ __forceinline__ void softmax_a(Att& a) {
#pragma unroll
  for (int i = 0; i < SM_A; i++) a.p[i] = pack(ex2(a.s[2 * i]), ex2(a.s[2 * i + 1]));
  pin<SM_A>(a.p);
}
__device__ __forceinline__ void softmax_b(Att& a) {
#pragma unroll
  for (int i = SM_A; i < SM_B; i++) a.p[i] = pack(ex2(a.s[2 * i]), ex2(a.s[2 * i + 1]));
  a.s[2 * SM_B] = ex2(a.s[2 * SM_B]); a.s[2 * SM_B + 1] = ex2(a.s[2 * SM_B + 1]);
  pin<SM_B - SM_A>(a.p + SM_A); pin<2>(a.s + 2 * SM_B);
}
__device__ __forceinline__ void softmax_c(Att& a) {
  a.p[SM_B] = pack(a.s[2 * SM_B], a.s[2 * SM_B + 1]);
#pragma unroll
  for (int i = SM_B + 1; i < 16; i++) a.p[i] = pack(ex2(a.s[2 * i]), ex2(a.s[2 * i + 1]));
  pin<16 - SM_B>(a.p + SM_B);
}
__device__ __forceinline__ void first_tile(Att& a, int hp, int lane) {
  float m0 = fmaxf(a.s[0], a.s[1]), m1 = fmaxf(a.s[2], a.s[3]);
#pragma unroll
  for (int i = 4; i < 32; i += 4) { m0 = fmaxf(m0, fmaxf(a.s[i], a.s[i + 1])); m1 = fmaxf(m1, fmaxf(a.s[i + 2], a.s[i + 3])); }
  m0 = fmaxf(m0, __shfl_xor_sync(0xffffffffu, m0, 1)); m1 = fmaxf(m1, __shfl_xor_sync(0xffffffffu, m1, 1));
  m0 = fmaxf(m0, __shfl_xor_sync(0xffffffffu, m0, 2)); m1 = fmaxf(m1, __shfl_xor_sync(0xffffffffu, m1, 2));
  float n0 = -(m0 + MOFF), n1 = -(m1 + MOFF);
  float h0 = bf_round(n0), h1 = bf_round(n1);
  uint32_t e0 = pack(h0, n0 - h0), e1 = pack(h1, n1 - h1);
  n0 = h0 + bf_hi(e0); n1 = h1 + bf_hi(e1);
  if ((lane & 3) == ((hp + 1) & 3)) { a.q[4] = e0; a.q[5] = e1; }
#pragma unroll
  for (int i = 0; i < 32; i += 4) { a.s[i] += n0; a.s[i + 1] += n0; a.s[i + 2] += n1; a.s[i + 3] += n1; }
#pragma unroll
  for (int i = 0; i < 12; i++) a.o[i] = 0.f;
  pin<12>(a.o); pin<8>(a.q);
}
__device__ __forceinline__ void fetch_q(uint32_t* q, int cta, int hp, int tid) {
  const uint4* src = reinterpret_cast<const uint4*>(g_Q) + (cta * 4 + hp) * 512 + tid;
  const uint4 u = __ldcg(src);
  const uint2 v = __ldcg(reinterpret_cast<const uint2*>(src + 256));
  q[0] = u.x; q[1] = u.y; q[2] = u.z; q[3] = u.w; q[4] = v.x; q[5] = v.y;
}
__device__ __forceinline__ void h_epilogue(const float* acc, uint32_t* dst) {
#pragma unroll
  for (int b = 0; b < 4; b++) {
    uint32_t w[2][2];
#pragma unroll
    for (int i = 0; i < 2; i++) {
      float h[4];
#pragma unroll
      for (int e = 0; e < 4; e++) {
        const float g = acc[(2 * b + i) * 4 + e], u = acc[32 + (2 * b + i) * 4 + e];
        h[e] = fmaf(tanh_fast(0.5f * g), u, u);
      }
      w[0][i] = pack(h[0], h[1]); w[1][i] = pack(h[2], h[3]);
    }
    if (!EXP_NOST || w[0][0] == 0x12345678) {
    *reinterpret_cast<uint2*>(dst + 1024 * b) = make_uint2(w[0][0], w[0][1]);
    *reinterpret_cast<uint2*>(dst + 1024 * b + 32) = make_uint2(w[1][0], w[1][1]);
    }
  }
}
__device__ __forceinline__ void rotate9(uint32_t (&v)[9][2]) {
#pragma unroll
  for (int rh = 0; rh < 2; rh++) {
    const uint32_t r = v[8][rh];
#pragma unroll
    for (int i = 8; i > 0; i--) v[i][rh] = v[i - 1][rh];
    v[0][rh] = r;
  }
}
template <int HP> __device__ __forceinline__ void store_kv_head(uint32_t (&pk)[2][9][2], uint32_t* kvp, int lane, uint32_t sk = 0, uint32_t sv = 0) {
  const int t = lane & 3, dv = ((t - HP) & 3) - t;
  const bool up = t < HP;
#pragma unroll
  for (int rh = 0; rh < 2; rh++) {
    uint32_t* d = kvp + HP * SEQ * 20 + rh * 160;
    const uint32_t c0 = up ? pk[0][2 * HP + 1][rh] : pk[0][2 * HP][rh], c1 = up ? pk[0][2 * HP + 2][rh] : pk[0][2 * HP + 1][rh];
    const uint32_t c3 = up ? pk[1][2 * HP + 1][rh] : pk[1][2 * HP][rh], c4 = up ? pk[1][2 * HP + 2][rh] : pk[1][2 * HP + 1][rh];
    const uint32_t v9 = __shfl_sync(0xffffffffu, pk[1][2 * HP + 2][rh], (lane & ~3) | HP);
    const uint32_t c2 = t == HP ? pk[0][2 * HP + 2][rh] : t == ((HP + 1) & 3) ? 0x3f803f80u : t == ((HP + 2) & 3) ? v9 : 0u;
    d[0] = c0; d[32] = c1; d[64] = c2; d[96 + dv] = c3; d[128 + dv] = c4;
    if (sk) {
      asm volatile("st.shared.b32 [%0], %1;\nst.shared.b32 [%0 + 128], %2;\nst.shared.b32 [%0 + 256], %3;" ::"r"(sk + rh * 384), "r"(c0), "r"(c1), "r"(c2) : "memory");
      asm volatile("st.shared.b32 [%0], %1;\nst.shared.b32 [%2 + 128], %3;\nst.shared.b32 [%2 + 256], %4;" ::"r"(sv + rh * 384), "r"(c2), "r"(sv + rh * 384 + dv * 4), "r"(c3), "r"(c4) : "memory");
    }
  }
}

template <int OFF> __device__ __forceinline__ void ld4(uint32_t* v, const void* p) {
  asm volatile("ld.relaxed.gpu.global.v4.b32 {%0,%1,%2,%3}, [%4 + %5];" : "=r"(v[0]), "=r"(v[1]), "=r"(v[2]), "=r"(v[3]) : "l"(p), "n"(OFF) : "memory");
}
template <int OFF> __device__ __forceinline__ void ld2(uint32_t* v, const void* p) {
  asm volatile("ld.relaxed.gpu.global.v2.b32 {%0,%1}, [%2 + %3];" : "=r"(v[0]), "=r"(v[1]) : "l"(p), "n"(OFF) : "memory");
}
__device__ __forceinline__ void stage_partials(const float* acc, uint32_t dst, int tid) {
  const int lane = tid & 31, row = (tid >> 5) * 16 + (lane & 15);
  const uint32_t r128 = dst + row * 128, r64 = dst + 49152 + row * 64;
#pragma unroll
  for (int i = 0; i < 12; i++) {
    const float* v = acc + 8 * i;
    stsm4(r128 + (i >> 2) * 16384 + (((2 * (i & 3) + (lane >> 4)) ^ (row & 7)) << 4), pack(v[0], v[1]), pack(v[2], v[3]), pack(v[4], v[5]), pack(v[6], v[7]));
  }
#pragma unroll
  for (int i = 0; i < 2; i++) {
    const float* v = acc + 128 + 8 * i;
    stsm4(r64 + (((2 * i + (lane >> 4)) ^ ((row >> 1) & 3)) << 4), pack(v[0], v[1]), pack(v[2], v[3]), pack(v[4], v[5]), pack(v[6], v[7]));
  }
}
__device__ __forceinline__ void final_epilogue(const float* acc, const Params& prm, int m, int hh, int q, int tid) {
  uint32_t r[18];
#pragma unroll
  for (int i = 0; i < 16; i++) r[i] = pack(acc[2 * i] * 0.5f, acc[2 * i + 1] * 0.5f);
#pragma unroll
  for (int i = 0; i < 2; i++) {
    const int o = 32 + 4 * i;
    const float a0 = (q & 2) ? acc[o + 2] : acc[o], a1 = (q & 2) ? acc[o + 10] : acc[o + 8];
    const float b0 = (q & 2) ? acc[o + 3] : acc[o + 1], b1 = (q & 2) ? acc[o + 11] : acc[o + 9];
    r[16 + i] = pack(((q & 1) ? a1 : a0) * 0.5f, ((q & 1) ? b1 : b0) * 0.5f);
  }
  const size_t off = (size_t)(128 * m + (tid >> 5) * 16 + ((tid & 31) >> 2)) * DM + 2 * (tid & 3);
  const bool odd = tid & 1;
  uint32_t* o1 = reinterpret_cast<uint32_t*>(prm.out + off + 320 * hh + 64 * q) + (odd ? 3 : 0);
  uint32_t* o2 = reinterpret_cast<uint32_t*>(prm.out + off + 256 + 32 * hh + 16 * (q & 1) + (q >> 1) * 8 * DM) + (odd ? 3 : 0);
#pragma unroll
  for (int i = 0; i < 9; i++) {
    const uint32_t A = i < 8 ? r[4 * (i >> 1) + (i & 1)] : r[16], B = i < 8 ? r[4 * (i >> 1) + 2 + (i & 1)] : r[17];
    const uint32_t y = __shfl_xor_sync(0xffffffffu, odd ? A : B, 1);
    *reinterpret_cast<uint2*>(i < 8 ? o1 + 8 * (i >> 1) + (i & 1) * 8 * (DM / 2) : o2) = odd ? make_uint2(y, B) : make_uint2(A, y);
  }
}

__global__ void __launch_bounds__(384, 1) fused_kernel(const __grid_constant__ Params prm) {
  extern __shared__ __align__(1024) uint8_t smem[];
  const uint32_t sb = (uint32_t)__cvta_generic_to_shared(smem);
  const uint32_t bar = sb + SM_BAR;
  const int cta = CLUSTER ? blockIdx.x : (blockIdx.x & 15) * 8 + (blockIdx.x >> 4);
  const int m = cta >> 3, j = cta & 7;
  const int wr = __shfl_sync(0xffffffffu, (int)(threadIdx.x >> 5), 0);
  const int wg = wr >> 2;
  const int lane = threadIdx.x & 31;
  STAMP(0);
  if (CLUSTER && wr != 8) asm volatile("barrier.cluster.arrive.relaxed.aligned;" ::: "memory");
  if (PF_X && threadIdx.x < 144) pf_line(prm.x + (size_t)cta * 16 * DM + threadIdx.x * 64);
  if (wg == 2 && lane == 0) {
    if (wr == 8) {
      asm volatile("prefetch.tensormap [%0];" ::"l"(CLUSTER ? &prm.xh : &prm.xm) : "memory");
#pragma unroll
      for (int c = 0; c < 9; c++) mbar_init(bar + 8 * (B_X + c), 1);
#pragma unroll
      for (int c = 0; c < 9; c++) mbar_expect(bar + 8 * (B_X + c), 16384);
      asm volatile("fence.proxy.async.shared::cta;" ::: "memory");
      if (CLUSTER) asm volatile("fence.mbarrier_init.release.cluster;" ::: "memory");
      else {
#pragma unroll
        for (int c = 0; c < 3; c++) tma2d(sb + SM_XN + c * 16384, &prm.xm, bar + 8 * (B_X + c), 64 * c, 128 * m);
      }
    } else {
      if (wr == 9) {
#pragma unroll
        for (int i = 0; i < 8; i++) mbar_init(bar + 8 * (B_F + i), 2);
#pragma unroll
        for (int i = 0; i < 3; i++) mbar_init(bar + 8 * (B_QF + i), 1);
      } else if (wr == 10) {
#pragma unroll
        for (int i = 0; i < 8; i++) mbar_init(bar + 8 * (B_E + i), 8);
#pragma unroll
        for (int i = 0; i < 3; i++) mbar_init(bar + 8 * (B_QE + i), 8);
      } else {
#pragma unroll
        for (int i = B_SK1; i <= B_SP; i++) mbar_init(bar + 8 * i, 8);
        mbar_init(bar + 8 * B_OL, 1); mbar_init(bar + 8 * B_RX, 1);
        mbar_init(bar + 8 * B_NR, 4); mbar_init(bar + 8 * (B_NR + 1), 4);
        asm volatile("st.shared.u32 [%0], 0;" ::"r"(sb + SM_BAD) : "memory");
        if (sb & 1023) asm volatile("trap;");
      }
      asm volatile("fence.proxy.async.shared::cta;" ::: "memory");
    }
  }
  if (wr == 0) {
    const uint32_t one = (lane >> 3) == (lane & 3) ? ((lane & 4) ? 0x3f800000u : 0x00003f80u) : 0u;
    asm volatile("st.shared.v4.b32 [%0], {%1,%2,%2,%1};" ::"r"(sb + SM_ID + lane * 16), "r"(one), "r"(0) : "memory");
  }
  if (CLUSTER && wr == 8) { __syncwarp(); asm volatile("barrier.cluster.arrive.release.aligned;" ::: "memory"); }
  __syncthreads();

  if (wg == 2) {
    asm volatile("setmaxnreg.dec.sync.aligned.u32 24;");
    const int pw = wr & 3;
    const uint32_t epoch = *(volatile uint32_t*)FLAG_EPOCH(cta);
    const int hh = j & 1;
#define ACOL(A) (320 * hh + 64 * (((j >> 1) + 1 + (A)) & 3))
    if (pw == 0) {
      if (CLUSTER) asm volatile("barrier.cluster.wait.acquire.aligned;" ::: "memory");
      if (lane == 0) {
        if (CLUSTER) {
#pragma unroll
          for (int c = 0; c < 9; c++)
            asm volatile("cp.async.bulk.tensor.2d.shared::cluster.global.mbarrier::complete_tx::bytes.multicast::cluster [%0], [%1, {%3, %4}], [%2], %5;"
                         ::"r"(sb + SM_XN + c * 16384 + hh * 8192), "l"(&prm.xh), "r"(bar + 8 * (B_X + c)), "r"(64 * c), "r"(128 * m + 64 * hh), "h"((uint16_t)3) : "memory");
        } else {
#pragma unroll
          for (int c = 3; c < 9; c++) tma2d(sb + SM_XN + c * 16384, &prm.xm, bar + 8 * (B_X + c), 64 * c, 128 * m);
        }
        uint64_t pol;
        asm volatile("createpolicy.fractional.L2::evict_first.b64 %0, 1.0;" : "=l"(pol));
#pragma unroll 1
        for (int kb = 0; kb < 9; kb++) {
          const int s = kb % 3;
          if (kb >= 3) mbar_wait(bar + 8 * (B_QE + s), (kb / 3 - 1) & 1);
          const uint32_t fb = bar + 8 * (B_QF + s), dst = sb + SM_RING + s * QST;
          mbar_expect(fb, QST);
#pragma unroll
          for (int p = 0; p < 3; p++) {
            tma2d(dst + p * 8192, &prm.wqkv64, fb, 576 * p + 72 * j + 8 * hh, 64 * kb);
            tma2d(dst + 24576 + p * 1024, &prm.wqkv8, fb, 576 * p + 72 * j + 64 - 64 * hh, 64 * kb);
          }
        }
        asm volatile("st.shared.u32 [%0], %1;" ::"r"(sb + SM_TAG), "r"((epoch + 1) & 1) : "memory");
        int col = 576 * j, kr = 0;
#pragma unroll 1
        for (int n = 0; n < N_G2; n++) {
          const uint32_t fb = bar + 8 * (B_F + (n & 7)), dst = sb + SM_RING + (n & 3) * BST;
          mbar_expect(fb, BST);
          if (n >= 4) mbar_wait(bar + 8 * (B_E + ((n - 3) & 7)), ((n - 3) >> 3) & 1);
          else if (n != 2) mbar_wait(bar + 8 * (B_QE + (n == 3 ? 2 : n)), 0);
          tma2d_h(dst, &prm.wg, fb, col, kr, pol);
          tma2d_h(dst + 8192, &prm.wu, fb, col, kr, pol);
          if ((kr += 64) == 576) { kr = 0; col += 64; }
        }
        uint32_t seen = 0;
#pragma unroll 1
        for (int b = 0; b < 26; b++) {
          const int n = N_G2 + 2 * b;
          const uint32_t fb = bar + 8 * (B_F + (n & 7)), dst = sb + (b & 3) * G2ST;
          const int own = b < 10 || b == 20 || b == 21, jj = own ? j : (j ^ 1), lb = b < 10 ? b : b < 20 ? b - 10 : 10 + (b & 1), need = (3 * lb + 6) >> 2;
          if (b < 24) {
            if (b == 10 || b == 20 || b == 22) seen = 0;
            if (seen < need) { seen = flag_wait_v(FLAG_H(m * 8 + jj), 9 * epoch + need) - 9 * epoch; fence_async(); }
          } else {
            flag_wait(FLAG_O((cta & ~1) + b - 24), epoch + 1);
            fence_async();
          }
          mbar_wait(bar + 8 * (B_E + ((n - 5) & 7)), ((n - 5) >> 3) & 1);
          if (b == 0) STAMPW(16);
          mbar_expect(fb, G2ST);
          if (b < 24) {
            bulk_g2s(dst, g_H + (m * 576 + 72 * jj + 6 * lb) * 512, 12288, fb);
#pragma unroll
            for (int a = 0; a < 4; a++) tma5d(dst + 12288 + a * 6144, &prm.wd[0], fb, ACOL(a), 36 * jj + 3 * lb);
            tma5d(dst + 36864, &prm.wd[1 + hh], fb, 0, 36 * jj + 3 * lb);
          } else {
            const int r = b - 24;
            bulk_g2s(dst, g_O + ((cta & ~1) + r) * 9 * 512 + r * 1024, 12288, fb);
#pragma unroll
            for (int a = 0; a < 4; a++) tma3d(dst + 12288 + a * 6144, &prm.wo3[0], fb, ACOL(a), 4 * (j & 6) + 5 * r);
            tma3d(dst + 36864, &prm.wo3[1 + hh], fb, 0, 4 * (j & 6) + 5 * r);
          }
          if (b == 0) STAMPW(17);
        }
        mbar_wait(bar + 8 * B_SP, 0);
        mbar_expect(bar + 8 * B_OL, 49152 + 32768);
        tma2d(sb + SM_RES, &prm.xm, bar + 8 * B_OL, ACOL(3), 128 * m);
        __nanosleep(200);
        tma2d(sb + SM_RES + 16384, &prm.xm, bar + 8 * B_OL, 256 + 32 * hh, 128 * m);
#pragma unroll 1
        for (int i = 0; i < 4; i++) {
          __nanosleep(200);
          tma3d(sb + SM_LB + i * 4096, &prm.wo2[0], bar + 8 * B_OL, ACOL(3), 8 * i + 3);
          tma3d(sb + SM_LB + 24576 + i * 4096, &prm.wo2[1 + hh], bar + 8 * B_OL, 0, 8 * i + 3);
          tma3d(sb + SM_LB + 16384 + i * 2048, &prm.wo16[0], bar + 8 * B_OL, ACOL(3), 8 * i);
          tma3d(sb + SM_LB + 40960 + i * 2048, &prm.wo16[1 + hh], bar + 8 * B_OL, 0, 8 * i);
        }
      }
    } else if (pw == 1) {
      if (lane == 0) {
        const int hx = hh * 3;
        int u = 0, kslot = 0, vrow = 0, kb = 0;
#pragma unroll 1
        for (int n = 0; n <= N_END; n++) {
          const uint32_t fb = bar + 8 * (B_F + (n & 7)), dst = sb + SM_KV + kslot * KVST;
          const bool att = n >= N_G2 || (n >= NG0 && kb != 0);
          if (++kb == 9) kb = 0;
          mbar_expect(fb, !att || u < 2 ? 0 : (u == 2 || u == 128) ? KVST / 2 : KVST);
          if (n >= N_AO || (n > N_G2 && !(n & 1))) mbar_expect(fb, 0);
          if (u == 2 && att) { flag_wait(FLAG_KV(0, j), 16 * epoch + 16); fence_async(); STAMPW(18); }
          if (n >= 4) mbar_wait(bar + 8 * (B_E + ((n - 3) & 7)), ((n - 3) >> 3) & 1);
          if (att) {
            const int krow = (4 * j + ((u >> 5) ^ hx)) * 256 + ((u + 2 * m) & 31) * 8;
            if (u >= 2 && u < 128) tma2d(dst, &prm.kv, fb, 0, krow);
            if (u >= 3) tma2d(dst + 3072, &prm.kv, fb, 128, vrow);
            vrow = krow; u++;
            if (++kslot == 3) kslot = 0;
            if (u == 16) { flag_wait(FLAG_KV(1, j), 16 * epoch + 16); fence_async(); }
          }
        }
      }
    } else if (pw == 2) {
      if (lane == 0) {
#pragma unroll 1
        for (int i = 2; i < 19; i++) asm volatile("prefetch.tensormap [%0];" ::"l"(&prm.xm + i) : "memory");
        mbar_wait(bar + 8 * B_SK1, 0);
        STAMPW(22);
        fence_gpu(); flag_add(FLAG_KV(0, j));
        STAMPW(20);
        mbar_wait(bar + 8 * B_SK2, 0);
        fence_gpu(); flag_add(FLAG_KV(1, j));
#pragma unroll 1
        for (int t = 0; t < 9; t++) { mbar_wait(bar + 8 * B_SH, t & 1); if (EXP_DELAY) __nanosleep(EXP_DELAY); fence_gpu(); flag_add(FLAG_H(cta)); }
        mbar_wait(bar + 8 * B_SO1, 0);
        fence_gpu(); flag_add(FLAG_O(cta));
      }
    } else {
      mbar_wait(bar + 8 * (B_X + PF_Q), 0);
#pragma unroll 1
      for (int i = lane; i < 122; i += 32) pf_line(prm.pwqkv + (size_t)min(i * 128 + cta, 15551) * 64);
      mbar_wait(bar + 8 * (B_QE + PF_G1), 0);
#pragma unroll 1
      for (int t = -3; t < 9; t++) {
        if (t >= 0) { mbar_wait(bar + 8 * B_SH, t & 1); if (EXP_PFD) __nanosleep(EXP_PFD); }
        if (t < 6) {
#pragma unroll 1
          for (int i = lane; i < 72; i += 32) pf_line((i >= 36 ? prm.pwu : prm.pwg) + (size_t)(36 * m + (i >= 36 ? i - 36 : i)) * FF + 576 * j + 64 * (t + 3));
        }
        if (t >= 5) {
#pragma unroll 1
          for (int i = lane; i < 81; i += 32) {
            const int l = (2 * m + hh) * 81 + i, r = l / 9;
            pf_line(prm.pwd + (size_t)(1152 * (j >> 1) + 576 * (r / 144) + 144 * (t - 5) + r % 144) * DM + 64 * (l % 9));
          }
        }
      }
      if (cta * 41 + lane < 5184) pf_line(prm.pwo + (size_t)(cta * 41 + lane) * 64);
      if (lane < 9 && cta * 41 + 32 + lane < 5184) pf_line(prm.pwo + (size_t)(cta * 41 + 32 + lane) * 64);
      if (lane == 0) {
      mbar_wait(bar + 8 * B_SP, 0);
      const int q = j >> 1;
#pragma unroll 1
      for (int i = 0; i < 14; i++) {
        bulk_s2g(g_P + cta * 3584 + i * 256, sb + SM_SEND + i * 4096, 4096);
        asm volatile("cp.async.bulk.commit_group;\ncp.async.bulk.wait_group.read %0;" ::"n"(SEND_DEPTH) : "memory");
      }
      asm volatile("cp.async.bulk.wait_group 0;" ::: "memory");
      fence_gpu();
      flag_add(FLAG_P(cta));
      STAMPW(15);
      mbar_expect(bar + 8 * B_RX, 73728);
#pragma unroll 1
      for (int a = 0; a < 3; a++) {
        const int src = m * 8 + 2 * ((q + 3 - a) & 3) + hh;
        flag_wait(FLAG_P(src), epoch + 1);
        fence_async();
        bulk_g2s(sb + SM_RECV + a * 24576, g_P + src * 3584 + a * 1024, 16384, bar + 8 * B_RX);
        bulk_g2s(sb + SM_RECV + a * 24576 + 16384, g_P + src * 3584 + 3072, 8192, bar + 8 * B_RX);
        if (RX_SLEEP) __nanosleep(RX_SLEEP);
      }
      STAMPW(25);
      *FLAG_EPOCH(cta) = epoch + 1;
      }
    }
  } else {
    const int tid = threadIdx.x;
    const int t = lane & 3;
    const uint32_t l0 = lane == 0;
    const uint32_t adesc = (((sb + SM_XN + wg * 8192) & 0x3FFFF) >> 4) | LO_A;
    const uint32_t bdesc = (((sb + SM_RING) & 0x3FFFF) >> 4) | LO_B;
    const uint32_t kdesc0 = (((sb + SM_KV) & 0x3FFFF) >> 4) | LO_K;
    const int hx = (j & 1) * 3;
    float accA[64], accB[64];
    Att a;
    uint32_t gs = 0, s8 = 0;
#define G1_ISSUE(ACC, AD, BD) _Pragma("unroll") for (int k = 0; k < 4; k++) wg_ss_n128<HI_SW128, HI_SW128>(ACC, (AD) + k * 2, (BD) + k * 128);
#define G1_ISSUE_Z(ACC, BD)                                                                                    \
  wg_ss_z_n128<HI_SW128, HI_SW128>(ACC, adesc, BD);                                                            \
  _Pragma("unroll") for (int k = 1; k < 4; k++) wg_ss_n128<HI_SW128, HI_SW128>(ACC, adesc + k * 2, (BD) + k * 128);
#define F_BAR (bar + 8 * B_F + 8 * s8)
#define F_PH ((gs >> 3) & 1)
#define RELEASE() mbar_arrive_if(bar + 8 * B_E + 8 * s8, l0);
#define NEXT_SLOT() { gs++; s8 = s8 == 7 ? 0 : s8 + 1; }
#define G1_ONLY() { mbar_wait(F_BAR, F_PH); wg_fence(); G1_ISSUE(accA, adesc + gs * 1024, bdesc + (gs & 3) * 1024) wg_commit(); wg_wait<1>(); RELEASE() NEXT_SLOT() }
    {
      const int lr = wr * 16 + (lane & 15);
      uint32_t ra[4];
#pragma unroll
      for (int k = 0; k < 4; k++) ra[k] = sb + SM_XN + lr * 128 + (((2 * k + (lane >> 4)) ^ (lr & 7)) << 4);
      STAMP(26);
      float cs[2][4] = {}, q0 = 0.f, q1 = 0.f, q2 = 0.f, q3 = 0.f;
#pragma unroll 1
      for (int c = 0; c < 9; c++) {
        mbar_wait(bar + 8 * (B_X + c), 0);
        if (c == 0) STAMP(27);
        if (c == 8) STAMP(28);
        uint32_t v[4][4];
#pragma unroll
        for (int k = 0; k < 4; k++) ldsm4(v[k], ra[k] + c * 16384);
#pragma unroll
        for (int k = 0; k < 4; k++) {
          mma_ones(cs[k & 1], v[k]);
#pragma unroll
          for (int e = 0; e < 4; e += 2) {
            const float x0 = bf_lo(v[k][e]), x1 = bf_hi(v[k][e]), y0 = bf_lo(v[k][e + 1]), y1 = bf_hi(v[k][e + 1]);
            q0 = fmaf(x0, x0, q0); q1 = fmaf(x1, x1, q1); q2 = fmaf(y0, y0, q2); q3 = fmaf(y1, y1, q3);
          }
        }
      }
      STAMP(11);
      asm volatile("setmaxnreg.inc.sync.aligned.u32 240;");
      const float mean0 = (cs[0][0] + cs[1][0]) * (1.f / 576.f), mean1 = (cs[0][2] + cs[1][2]) * (1.f / 576.f);
      q0 += q1; q2 += q3;
      q0 += __shfl_xor_sync(0xffffffffu, q0, 1); q2 += __shfl_xor_sync(0xffffffffu, q2, 1);
      q0 += __shfl_xor_sync(0xffffffffu, q0, 2); q2 += __shfl_xor_sync(0xffffffffu, q2, 2);
      float var0 = fmaf(q0, 1.f / 576.f, -mean0 * mean0), var1 = fmaf(q2, 1.f / 576.f, -mean1 * mean1);
      if (__any_sync(0xffffffffu, !(mean0 * mean0 <= 8.f * var0) || !(mean1 * mean1 <= 8.f * var1))) {
        q0 = q2 = 0.f;
#pragma unroll 1
        for (int i = 0; i < 36; i++) {
          uint32_t v[4];
          ldsm4(v, ((ra[0] + (i >> 2) * 16384) ^ ((i & 3) << 5)));
#pragma unroll
          for (int e = 0; e < 4; e += 2) {
            const float x0 = bf_lo(v[e]) - mean0, x1 = bf_hi(v[e]) - mean0, y0 = bf_lo(v[e + 1]) - mean1, y1 = bf_hi(v[e + 1]) - mean1;
            q0 = fmaf(x0, x0, fmaf(x1, x1, q0)); q2 = fmaf(y0, y0, fmaf(y1, y1, q2));
          }
        }
        q0 += __shfl_xor_sync(0xffffffffu, q0, 1); q2 += __shfl_xor_sync(0xffffffffu, q2, 1);
        q0 += __shfl_xor_sync(0xffffffffu, q0, 2); q2 += __shfl_xor_sync(0xffffffffu, q2, 2);
        var0 = q0 * (1.f / 576.f); var1 = q2 * (1.f / 576.f);
      }
      const float inv0 = rcp_fast(bf_round(sqrt_fast(bf_round(bf_round(var0) + 1e-5f)))), inv1 = rcp_fast(bf_round(sqrt_fast(bf_round(bf_round(var1) + 1e-5f))));
      const uint32_t mb0 = pack(mean0, mean0), mb1 = pack(mean1, mean1);
      const uint32_t h0 = pack(inv0, inv0), h1 = pack(inv1, inv1);
      const uint32_t e0 = pack(inv0 - bf_lo(h0), inv0 - bf_lo(h0)), e1 = pack(inv1 - bf_lo(h1), inv1 - bf_lo(h1));
      float aq[96], ar[12];
      uint32_t v[4][4], xn[4][4];
#pragma unroll
      for (int k = 0; k < 4; k++) ldsm4(v[k], ra[k]);
#pragma unroll
      for (int i = 0; i < 96; i++) aq[i] = 0.f;
#pragma unroll
      for (int i = 0; i < 12; i++) ar[i] = 0.f;
      pin<96>(aq); pin<12>(ar);
      STAMP(1);
      const uint32_t rdesc = (((sb + SM_RING + 24576) & 0x3FFFF) >> 4) | LO_R;
      uint32_t s = 0, ph = 0;
#pragma unroll 1
      for (int kb = 0; kb < 9; kb++) {
#pragma unroll
        for (int k = 0; k < 4; k++) {
          xn[k][0] = bscale2(bsub2(v[k][0], mb0), h0, e0); xn[k][1] = bscale2(bsub2(v[k][1], mb1), h1, e1);
          xn[k][2] = bscale2(bsub2(v[k][2], mb0), h0, e0); xn[k][3] = bscale2(bsub2(v[k][3], mb1), h1, e1);
        }
        pin<16>(&xn[0][0]);
        mbar_wait(bar + 8 * B_QF + 8 * s, ph);
        wg_fence();
#pragma unroll
        for (int k = 0; k < 4; k++) {
          wg_rs_n192<HI_SW128>(aq, xn[k][0], xn[k][1], xn[k][2], xn[k][3], bdesc + s * (QST >> 4) + k * 128);
          wg_rs_n24<HI_R>(ar, xn[k][0], xn[k][1], xn[k][2], xn[k][3], rdesc + s * (QST >> 4) + k * 16);
        }
        wg_commit();
#pragma unroll
        for (int k = 0; k < 4; k++) stsm4(ra[k] + kb * 16384, xn[k][0], xn[k][1], xn[k][2], xn[k][3]);
#pragma unroll
        for (int k = 0; k < 4; k++) ldsm4(v[k], ra[k] + (kb < 8 ? kb + 1 : 8) * 16384);
        if (kb == 8) {
          asm volatile("fence.proxy.async.shared::cta;" ::: "memory");
          __syncwarp();
          mbar_arrive_if(bar + 8 * B_NR + 8 * wg, l0);
        }
        wg_wait<0>();
        mbar_arrive_if(bar + 8 * B_QE + 8 * s, l0);
        if (++s == 3) { s = 0; ph ^= 1; }
      }
      pin<96>(aq); pin<12>(ar);
      STAMP(2);
      uint32_t* kvp = g_KV + (size_t)(4 * j) * SEQ * 20 + (16 * m + 2 * wr) * 160 + lane;
      uint32_t pk[2][9][2];
#pragma unroll
      for (int p = 0; p < 2; p++)
#pragma unroll
        for (int i = 0; i < 9; i++) {
          const float* src = i < 8 ? &aq[(8 * (p + 1) + i) * 4] : &ar[4 * (p + 1)];
          pk[p][i][0] = pack(src[0], src[1]); pk[p][i][1] = pack(src[2], src[3]);
        }
      const uint32_t sk = sb + SM_KV + wg * KVST + (wr & 3) * 768 + lane * 4;
      mbar_wait(bar + 8 * (B_QE + 2), 0);
      if (hx) {
#pragma unroll
        for (int p = 0; p < 2; p++) { rotate9(pk[p]); }
        store_kv_head<3>(pk, kvp, lane, sk, sk + KVST + 3072);
      } else store_kv_head<0>(pk, kvp, lane, sk, sk + KVST + 3072);
      asm volatile("fence.proxy.async.shared::cta;" ::: "memory");
      __syncwarp();
      mbar_arrive_if(bar + 8 * B_SK1, l0);
      mbar_arrive_if(bar + 8 * B_LK, l0);
      STAMP(3);
      mbar_wait(bar + 8 * B_NR + 8 * wg, 0);
      mbar_wait(bar + 8 * B_F, 0);
      wg_fence();
      G1_ISSUE_Z(accA, bdesc)
      wg_commit();
      RELEASE()
      NEXT_SLOT()
      mbar_wait(F_BAR, F_PH);
      G1_ISSUE(accA, adesc + 1024, bdesc + 1024)
      wg_commit();
      uint32_t pq[9][2];
#pragma unroll
      for (int i = 0; i < 9; i++) {
        const float* src = i < 8 ? &aq[i * 4] : &ar[0];
        pq[i][0] = pack(bf_round(src[0]) * QSCALE, bf_round(src[1]) * QSCALE); pq[i][1] = pack(bf_round(src[2]) * QSCALE, bf_round(src[3]) * QSCALE);
      }
      if (hx) rotate9(pq);
      pin<18>(&pq[0][0]);
      wg_wait<1>();
      RELEASE()
      NEXT_SLOT()
      G1_ONLY()
      mbar_wait(F_BAR, F_PH);
      G1_ISSUE(accA, adesc + 3 * 1024, bdesc + 3 * 1024)
      wg_commit();
      if (hx) store_kv_head<0>(pk, kvp, lane); else store_kv_head<3>(pk, kvp, lane);
      store_kv_head<1>(pk, kvp, lane);
      store_kv_head<2>(pk, kvp, lane);
      __syncwarp();
      mbar_arrive_if(bar + 8 * B_SK2, l0);
      wg_wait<1>();
      RELEASE()
      NEXT_SLOT()
      mbar_wait(F_BAR, F_PH);
      G1_ISSUE(accA, adesc + 4 * 1024, bdesc)
      wg_commit();
      uint4* qp = reinterpret_cast<uint4*>(g_Q) + cta * 4 * 512 + tid;
#pragma unroll
      for (int hp = 0; hp < 4; hp++) {
        const bool up = t < hp;
        const uint4 u = make_uint4(up ? pq[2 * hp + 1][0] : pq[2 * hp][0], up ? pq[2 * hp + 1][1] : pq[2 * hp][1],
                                   up ? pq[2 * hp + 2][0] : pq[2 * hp + 1][0], up ? pq[2 * hp + 2][1] : pq[2 * hp + 1][1]);
        const uint4 v = make_uint4(t == hp ? pq[2 * hp + 2][0] : 0u, t == hp ? pq[2 * hp + 2][1] : 0u, 0u, 0u);
        qp[hp * 512] = u; qp[hp * 512 + 256] = v;
        if (hp == 0 || (hp == 3 && hx)) { a.q[0] = u.x; a.q[1] = u.y; a.q[2] = u.z; a.q[3] = u.w; a.q[4] = v.x; a.q[5] = v.y; }
      }
      a.q[6] = __shfl_sync(0xffffffffu, lane, 0); a.q[7] = __shfl_sync(0xffffffffu, lane >> 1, 1);
#pragma unroll
      for (int i = 0; i < 16; i++) a.p[i] = 0;
#pragma unroll
      for (int i = 0; i < 12; i++) a.o[i] = 0.f;
      pin<16>(a.p); pin<12>(a.o); pin<8>(a.q);
      wg_wait<1>();
      RELEASE()
      NEXT_SLOT()
    }
    static_assert(NG0 == 5 || NG0 == 7, "item boundaries must fall into even F tiles / even GEMM2 slots");
#pragma unroll 1
    while (gs < NG0) G1_ONLY()
    STAMP(4);
    mbar_wait(bar + 8 * B_LK, 0);
    mbar_wait(F_BAR, F_PH);
    STAMP(23);
    uint32_t kd = kdesc0;
    uint32_t it = 0;
    uint32_t ox0 = 0, ox1 = 0;
    bool special = true;
    uint32_t qn[6] = {0, 0, 0, 0, 0, 0};
    uint32_t* hdst = g_H + ((m * 576 + 72 * j + (t >> 1)) * 128 + 16 * wr + (lane >> 2)) * 4 + 2 * (t & 1);
    uint32_t ad = adesc + NG0 * 1024, bd = bdesc + (gs & 3) * 1024;

#define ITEM_FIRST()                                                                                           \
  {                                                                                                            \
    pin<12>(a.o);                                                                                              \
    if (it != 0) {                                                                                             \
      uint32_t w[4];                                                                                           \
      o_normalise(a.o, w, ox0, ox1, ((it >> 5) - 1) ^ hx, lane, sb + SM_BAD, wr);                              \
      uint32_t* d = g_O + cta * 9 * 512 + (((it >> 5) - 1) ^ hx) * 1024 + wr * 64 + lane;                      \
      d[0] = w[0]; d[32] = w[1]; d[512] = w[2]; d[544] = w[3];                                                 \
    }                                                                                                          \
    if (it == 96) mbar_arrive_if(bar + 8 * B_SO1, l0 & (bad_heads(sb + SM_BAD, wr) == 0));                     \
    first_tile(a, (it >> 5) ^ hx, lane);                                                                       \
  }
#define ITEM_NEXTQ() { if (it & 2) { _Pragma("unroll") for (int i = 0; i < 6; i++) a.q[i] = qn[i]; } else fetch_q(qn, cta, ((it >> 5) + 1) ^ hx, tid); }
#define KV_ADVANCE() { kd = kd == kdesc0 + 768 ? kdesc0 : kd + 384; }
#define WAIT_UNLESS(OK) if (__builtin_expect(!(OK), 0)) mbar_wait(F_BAR, F_PH);
#define SOFTMAX_NEXT() { softmax_a(a); softmax_b(a); mbar_wait(F_BAR, F_PH); softmax_c(a); }
#define EPI_STEP(ACCN, ACCO)                                                                                   \
  {                                                                                                            \
    wg_fence();                                                                                                \
    G1_ISSUE_Z(ACCN, bd)                                                                                       \
    wg_commit();                                                                                               \
    wg_wait<1>();                                                                                              \
    pin<64>(ACCO);                                                                                             \
    RELEASE()                                                                                                  \
    NEXT_SLOT()                                                                                                \
    ad = adesc + 1024; bd = bdesc + (gs & 3) * 1024;                                                           \
    const uint32_t ok = mbar_test(F_BAR, F_PH);                                                                \
    h_epilogue(ACCO, hdst);                                                                                    \
    hdst += 4096;                                                                                              \
    __syncwarp();                                                                                              \
    mbar_arrive_if(bar + 8 * B_SH, l0);                                                                        \
    WAIT_UNLESS(ok)                                                                                            \
  }
#define ATT_LOOP1(ACC, ITEMS)                                                                                  \
  do {                                                                                                         \
    wg_fence();                                                                                                \
    issue_att(a, kd);                                                                                          \
    wg_commit();                                                                                               \
    G1_ISSUE(ACC, ad, bd)                                                                                      \
    wg_commit();                                                                                               \
    wg_wait<1>();                                                                                              \
    pin<32>(a.s);                                                                                              \
    RELEASE()                                                                                                  \
    TRACE()                                                                                                    \
    if (ITEMS) { if (__builtin_expect(special, 0)) { if (it & 1) ITEM_NEXTQ() else { if (it == 64) fetch_q(qn, cta, 3 ^ hx, tid); ITEM_FIRST() } } } \
    NEXT_SLOT() it++;                                                                                                \
    if (ITEMS) special = (0xA0000001u >> (it & 31)) & 1;                                                                  \
    KV_ADVANCE()                                                                                               \
    ad += 1024; bd = bdesc + (gs & 3) * 1024;                                                                  \
    SOFTMAX_NEXT()                                                                                             \
    pin<8>(a.q);                                                                                               \
  } while (ad != adesc + 9 * 1024);
#pragma unroll 1
    for (int pr = 0;; pr++) {
      ATT_LOOP1(accA, true)
      if (pr == 4) break;
      if (pr == 2) STAMP(29);
      EPI_STEP(accB, accA)
      if (pr == 2) STAMP(30);
      ATT_LOOP1(accB, false)
      if (pr == 2) STAMP(31);
      EPI_STEP(accA, accB)
      special = false;
      if (pr == 2) STAMP(21);
      if (pr == 3) STAMP(14);
    }
    STAMP(5);
    wg_wait<0>();
    pin<64>(accA);
    h_epilogue(accA, hdst);
    __syncwarp();
    mbar_arrive_if(bar + 8 * B_SH, l0);
    mbar_wait(bar + 8 * B_E, 0);
    asm volatile("st.shared.v4.b32 [%0], {%1,%2,%3,%4};\nst.shared.v2.b32 [%5], {%6,%7};" ::"r"(sb + SM_QS + tid * 16), "r"(qn[0]), "r"(qn[1]), "r"(qn[2]), "r"(qn[3]),
                 "r"(sb + SM_QS + 4096 + tid * 8), "r"(qn[4]), "r"(qn[5]) : "memory");
    STAMP(6);
    STAMP(12);

    float acc2[144];
    const uint32_t a2desc = (((sb + wg * 1024) & 0x3FFFF) >> 4) | LO_O;
    const uint32_t b2desc = (((sb + 12288) & 0x3FFFF) >> 4) | LO_B48;
    ad = a2desc; bd = b2desc;
#define G2_LO(K) wg_ss_n128<HI_O, HI_SW128>(acc2, ad + (K) * 256, bd + (K) * 128);
#define G2_HI(K) wg_ss_n160<HI_O, HI_SW128>(acc2 + 64, ad + (K) * 256, bd + (K) * 128 + 768);
#define ATT_PAIR(ZERO)                                                                                         \
  {                                                                                                            \
    wg_fence();                                                                                                \
    issue_att(a, kd);                                                                                          \
    wg_commit();                                                                                               \
    if (ZERO) { wg_ss_z_n128<HI_O, HI_SW128>(acc2, ad, bd); wg_ss_z_n160<HI_O, HI_SW128>(acc2 + 64, ad, bd + 768); } \
    else { G2_LO(0) G2_HI(0) }                                                                                 \
    G2_LO(1)                                                                                                   \
    wg_commit();                                                                                               \
    wg_wait<1>();                                                                                              \
    pin<32>(a.s);                                                                                              \
    RELEASE()                                                                                                  \
    TRACE()                                                                                                    \
    if (!(ZERO)) { if (__builtin_expect(gs == N_G2 + 96 - IT_G2, 0)) ITEM_FIRST() }                                    \
    NEXT_SLOT() it++;                                                                                                \
    KV_ADVANCE()                                                                                               \
    SOFTMAX_NEXT()                                                                                             \
    pin<8>(a.q);                                                                                               \
    wg_fence();                                                                                                \
    issue_att(a, kd);                                                                                          \
    wg_commit();                                                                                               \
    G2_HI(1) G2_LO(2) G2_HI(2)                                                                                 \
    wg_commit();                                                                                               \
    wg_wait<1>();                                                                                              \
    pin<32>(a.s);                                                                                              \
    RELEASE()                                                                                                  \
    TRACE()                                                                                                    \
    if (!(ZERO) && __builtin_expect(gs == N_G2 + 95 - IT_G2, 0)) {                                                     \
      const int ft = fresh_tid();                                                                              \
      asm volatile("ld.shared.v4.b32 {%0,%1,%2,%3}, [%6];\nld.shared.v2.b32 {%4,%5}, [%7];" : "=r"(a.q[0]), "=r"(a.q[1]), "=r"(a.q[2]), "=r"(a.q[3]), \
                   "=r"(a.q[4]), "=r"(a.q[5]) : "r"(sb + SM_QS + ft * 16), "r"(sb + SM_QS + 4096 + ft * 8) : "memory"); \
    }                                                                                                          \
    NEXT_SLOT() it++;                                                                                                \
    KV_ADVANCE()                                                                                               \
    ad = a2desc + (((gs - N_G2) >> 1) & 3) * 2688; bd = ad + (b2desc - a2desc);                                \
    SOFTMAX_NEXT()                                                                                             \
    pin<8>(a.q);                                                                                               \
  }
    ATT_PAIR(true)
#pragma unroll 1
    for (int half = 0; half < 2; half++) {
      const uint32_t stop = half ? N_AO : N_G2 + 46;
      do ATT_PAIR(false) while (gs != stop);
      if (!half) {
        const uint32_t bad = bad_heads(sb + SM_BAD, wr);
        if (bad) { repair_rows(cta, wr, bad, 3 ^ hx, false); mbar_arrive_if(bar + 8 * B_SO1, l0); }
      }
    }
    STAMP(13);
    wg_wait<0>();
    pin<144>(acc2);
    mbar_wait(bar + 8 * (B_E + 1), 0);
    stage_partials(acc2, sb + SM_SEND, fresh_tid());
    asm volatile("fence.proxy.async.shared::cta;" ::: "memory");
    __syncwarp();
    mbar_arrive_if(bar + 8 * B_SP, l0);
    do {
      wg_fence();
      issue_att(a, kd);
      wg_commit();
      wg_wait<0>();
      pin<32>(a.s);
      RELEASE()
      TRACE()
      NEXT_SLOT() it++;
      KV_ADVANCE()
      SOFTMAX_NEXT()
    } while (gs != N_END);
    STAMP(7);
    wg_fence();
    issue_pv(a, kd);
    wg_commit();
    int tid2, bid2;
    asm volatile("mov.u32 %0, %%tid.x;" : "=r"(tid2));
    asm volatile("mov.u32 %0, %%ctaid.x;" : "=r"(bid2));
    const int m2 = CLUSTER ? bid2 >> 3 : bid2 & 15, j2 = CLUSTER ? bid2 & 7 : bid2 >> 4;
    uint32_t tag;
    asm volatile("ld.shared.u32 %0, [%1];" : "=r"(tag) : "r"(sb + SM_TAG) : "memory");
    wg_wait<0>();
    pin<12>(a.o);
    {
      uint32_t w[4];
      o_normalise(a.o, w, ox0, ox1, 3 ^ hx, lane, sb + SM_BAD, wr);
      ox0 = __shfl_xor_sync(0xffffffffu, ox0, 2); ox1 = __shfl_xor_sync(0xffffffffu, ox1, 2);
      const uint32_t bad = bad_heads(sb + SM_BAD, wr);
      if (bad) {
        uint32_t* d = g_O + cta * 9 * 512 + wr * 64 + lane;
        uint32_t* h = d + (3 ^ hx) * 1024;
        h[0] = w[0]; h[32] = w[1]; h[512] = w[2]; h[544] = w[3]; d[4096] = ox0; d[4128] = ox1;
        __syncwarp();
        repair_rows(cta, wr, bad, 3 ^ hx, true);
        w[0] = __ldcg(h); w[1] = __ldcg(h + 32); w[2] = __ldcg(h + 512); w[3] = __ldcg(h + 544); ox0 = __ldcg(d + 4096); ox1 = __ldcg(d + 4128);
      }
      asm volatile("st.relaxed.gpu.global.v4.b32 [%0], {%1,%2,%3,%4};" ::"l"(g_L + (m2 * 8 + j2) * 384 + tid2), "r"((w[0] & ~1u) | tag), "r"((w[1] & ~1u) | tag),
                   "r"((w[2] & ~1u) | tag), "r"((w[3] & ~1u) | tag) : "memory");
      asm volatile("st.relaxed.gpu.global.v2.b32 [%0], {%1,%2};" ::"l"(reinterpret_cast<uint2*>(g_L + (m2 * 8 + j2) * 384 + 256) + tid2), "r"((ox0 & ~1u) | tag),
                   "r"((ox1 & ~1u) | tag) : "memory");
    }
    STAMP(8);
    uint32_t la[48];
    const uint4* p4 = g_L + m2 * 8 * 384 + tid2;
    const uint2* p2 = reinterpret_cast<const uint2*>(g_L + m2 * 8 * 384 + 256) + tid2;
#define LOAD_LA2() { ld2<0>(la + 32, p2); ld2<6144>(la + 34, p2); ld2<12288>(la + 36, p2); ld2<18432>(la + 38, p2); \
                     ld2<24576>(la + 40, p2); ld2<30720>(la + 42, p2); ld2<36864>(la + 44, p2); ld2<43008>(la + 46, p2); }
#define LOAD_LA4() { ld4<0>(la, p4); ld4<6144>(la + 4, p4); ld4<12288>(la + 8, p4); ld4<18432>(la + 12, p4); \
                     ld4<24576>(la + 16, p4); ld4<30720>(la + 20, p4); ld4<36864>(la + 24, p4); ld4<43008>(la + 28, p4); }
    LOAD_LA4()
    LOAD_LA2()
    float fin[48];
    uint32_t id[4][4];
    {
      uint32_t id2[4][4];
#pragma unroll
      for (int k = 0; k < 4; k++) {
        asm volatile("ld.volatile.shared.v4.b32 {%0,%1,%2,%3}, [%4];" : "=r"(id[k][0]), "=r"(id[k][1]), "=r"(id[k][2]), "=r"(id[k][3])
                     : "r"(sb + SM_ID + ((wr & 3) == k ? lane : 1) * 16) : "memory");
#pragma unroll
        for (int e = 0; e < 4; e++) id2[k][e] = id[k][e] + (id[k][e] & 0x00800080u);
      }
      pin<16>(&id[0][0]); pin<16>(&id2[0][0]);
      const uint32_t xdesc = (((sb + SM_RES + wg * 8192) & 0x3FFFF) >> 4) | LO_B;
      mbar_wait(bar + 8 * B_OL, 0);
      wg_fence();
      wg_rsb_z_n64<HI_SW128>(fin, id2[0][0], id2[0][1], id2[0][2], id2[0][3], xdesc);
      wg_rs_z_n32<HI_SW128>(fin + 32, id2[0][0], id2[0][1], id2[0][2], id2[0][3], xdesc + 1024);
#pragma unroll
      for (int k = 1; k < 4; k++) {
        wg_rsb_n64<HI_SW128>(fin, id2[k][0], id2[k][1], id2[k][2], id2[k][3], xdesc + k * 128);
        wg_rs_n32<HI_SW128>(fin + 32, id2[k][0], id2[k][1], id2[k][2], id2[k][3], xdesc + 1024 + k * 128);
      }
      wg_commit();
      wg_wait<0>();
      pin<48>(fin);
#pragma unroll
      for (int i = 0; i < 48; i++) fin[i] += acc2[96 + i];
      pin<48>(fin);
    }
    for (uint32_t tries = 0; tries < 0x400000u; tries++) {
      uint32_t bad = 0;
#pragma unroll
      for (int i = 0; i < 48; i++) bad |= la[i] ^ tag;
      if (__all_sync(0xffffffffu, !(bad & 1))) break;
      LOAD_LA4()
      LOAD_LA2()
    }
#pragma unroll
    for (int i = 0; i < 48; i++) la[i] ^= tag;
    pin<48>(la);
    STAMP(19);
    const uint32_t ldesc = (((sb + SM_LB) & 0x3FFFF) >> 4) | LO_B;
    wg_fence();
#pragma unroll
    for (int k = 0; k < 12; k++) {
      wg_rsb_n64<HI_SW128>(fin, la[4 * k], la[4 * k + 1], la[4 * k + 2], la[4 * k + 3], ldesc + k * 128);
      wg_rs_n32<HI_SW128>(fin + 32, la[4 * k], la[4 * k + 1], la[4 * k + 2], la[4 * k + 3], ldesc + 1536 + k * 128);
    }
    wg_commit();
    const uint32_t pdesc = (((sb + SM_RECV + wg * 8192) & 0x3FFFF) >> 4) | LO_B, hdesc = (((sb + SM_RECV + 16384 + wg * 4096) & 0x3FFFF) >> 4) | LO_B;
    mbar_wait(bar + 8 * B_RX, 0);
    STAMP(24);
    wg_fence();
#pragma unroll
    for (int a3 = 0; a3 < 3; a3++)
#pragma unroll
      for (int k = 0; k < 4; k++) {
        wg_rsb_n64<HI_SW128>(fin, id[k][0], id[k][1], id[k][2], id[k][3], pdesc + a3 * 1536 + k * 128);
        wg_rs_n32<HI_SW64>(fin + 32, id[k][0], id[k][1], id[k][2], id[k][3], hdesc + a3 * 1536 + k * 64);
      }
    wg_commit();
    wg_wait<0>();
    pin<48>(fin);
    STAMP(9);
    final_epilogue(fin, prm, m2, j2 & 1, j2 >> 1, tid2);
    STAMP(10);
  }
}

typedef CUresult (*EncodeFn)(CUtensorMap*, CUtensorMapDataType, cuuint32_t, void*, const cuuint64_t*, const cuuint64_t*, const cuuint32_t*, const cuuint32_t*,
                             CUtensorMapInterleave, CUtensorMapSwizzle, CUtensorMapL2promotion, CUtensorMapFloatOOBfill);

void enc2d(EncodeFn enc, CUtensorMap* tm, const void* base, uint64_t w, uint64_t h, uint64_t pitch_elems, uint32_t bw, uint32_t bh, CUtensorMapSwizzle sw) {
  cuuint64_t dims[2] = {w, h}, str[1] = {pitch_elems * 2};
  cuuint32_t box[2] = {bw, bh}, es[2] = {1, 1};
  enc(tm, CU_TENSOR_MAP_DATA_TYPE_BFLOAT16, 2, const_cast<void*>(base), dims, str, box, es, CU_TENSOR_MAP_INTERLEAVE_NONE, sw,
      CU_TENSOR_MAP_L2_PROMOTION_L2_128B, CU_TENSOR_MAP_FLOAT_OOB_FILL_NONE);
}

}

extern "C" void kernel_launch(void* const* d_in, const int* in_sizes, int n_in, void* d_out, int out_size) {
  (void)in_sizes; (void)n_in; (void)out_size;
  const __nv_bfloat16* x = (const __nv_bfloat16*)d_in[0];
  const __nv_bfloat16* wqkv = (const __nv_bfloat16*)d_in[1];
  const __nv_bfloat16* wo = (const __nv_bfloat16*)d_in[2];
  const __nv_bfloat16* wg = (const __nv_bfloat16*)d_in[4];
  const __nv_bfloat16* wu = (const __nv_bfloat16*)d_in[5];
  const __nv_bfloat16* wd = (const __nv_bfloat16*)d_in[6];
  void* fn = nullptr;
  cudaDriverEntryPointQueryResult qr;
  cudaGetDriverEntryPoint("cuTensorMapEncodeTiled", &fn, cudaEnableDefault, &qr);
  EncodeFn enc = (EncodeFn)fn;
  void* kvp = nullptr;
  cudaGetSymbolAddress(&kvp, g_KV);
  Params p;
  enc2d(enc, &p.xm, x, DM, SEQ, DM, 64, 128, CU_TENSOR_MAP_SWIZZLE_128B);
  enc2d(enc, &p.xh, x, DM, SEQ, DM, 64, 64, CU_TENSOR_MAP_SWIZZLE_128B);
  enc2d(enc, &p.kv, kvp, 320, 32 * 256, 320, 192, 8, CU_TENSOR_MAP_SWIZZLE_NONE);
  enc2d(enc, &p.wqkv64, wqkv, 3 * DM, DM, 3 * DM, 64, 64, CU_TENSOR_MAP_SWIZZLE_128B);
  enc2d(enc, &p.wqkv8, wqkv, 3 * DM, DM, 3 * DM, 8, 64, CU_TENSOR_MAP_SWIZZLE_NONE);
  enc2d(enc, &p.wg, wg, FF, DM, FF, 64, 64, CU_TENSOR_MAP_SWIZZLE_128B);
  enc2d(enc, &p.wu, wu, FF, DM, FF, 64, 64, CU_TENSOR_MAP_SWIZZLE_128B);
  for (int v = 0; v < 3; v++) {
    const cuuint64_t wdt = v ? 32 : DM;
    const int c0 = v ? 256 + 32 * (v - 1) : 0;
    for (int e = 0; e < 3; e++) {
      cuuint64_t d3[3] = {wdt, e == 2 ? 2u : 16u, 32}, s3[2] = {DM * 2, 18 * DM * 2};
      cuuint32_t b3[3] = {64, e == 2 ? 2u : 16u, e == 0 ? 3u : e == 1 ? 2u : 8u}, e3[3] = {1, 1, 1};
      enc(e == 0 ? &p.wo3[v] : e == 1 ? &p.wo2[v] : &p.wo16[v], CU_TENSOR_MAP_DATA_TYPE_BFLOAT16, 3, (void*)(wo + c0 + (e == 2 ? 16 * DM : 0)), d3, s3, b3, e3,
          CU_TENSOR_MAP_INTERLEAVE_NONE, CU_TENSOR_MAP_SWIZZLE_128B, CU_TENSOR_MAP_L2_PROMOTION_L2_128B, CU_TENSOR_MAP_FLOAT_OOB_FILL_NONE);
    }
    cuuint64_t dims[5] = {wdt, 2, 2, 4, FF / 16}, str[4] = {DM * 2, 8 * DM * 2, 2 * DM * 2, 16 * DM * 2};
    cuuint32_t box[5] = {64, 2, 2, 4, 3}, es[5] = {1, 1, 1, 1, 1};
    enc(&p.wd[v], CU_TENSOR_MAP_DATA_TYPE_BFLOAT16, 5, (void*)(wd + c0), dims, str, box, es, CU_TENSOR_MAP_INTERLEAVE_NONE,
        CU_TENSOR_MAP_SWIZZLE_128B, CU_TENSOR_MAP_L2_PROMOTION_L2_128B, CU_TENSOR_MAP_FLOAT_OOB_FILL_NONE);
  }
  p.x = x; p.pwqkv = wqkv; p.pwo = wo; p.pwg = wg; p.pwu = wu; p.pwd = wd;
  p.out = (__nv_bfloat16*)d_out;
  cudaFuncSetAttribute(fused_kernel, cudaFuncAttributeMaxDynamicSharedMemorySize, SM_TOTAL);
  cudaLaunchConfig_t cfg = {};
  cfg.gridDim = dim3(NCTA); cfg.blockDim = dim3(384); cfg.dynamicSmemBytes = SM_TOTAL; cfg.stream = cudaStreamPerThread;
  cudaLaunchAttribute at[1];
  at[0].id = cudaLaunchAttributeClusterDimension; at[0].val.clusterDim.x = CLUSTER ? 2 : 1; at[0].val.clusterDim.y = 1; at[0].val.clusterDim.z = 1;
  cfg.attrs = at; cfg.numAttrs = CLUSTER ? 1 : 0;
  cudaLaunchKernelEx(&cfg, fused_kernel, p);
}
```

```cpp
#include <cuda_runtime.h>
#include <cuda.h>
#include <cuda_bf16.h>
#include <stdint.h>

namespace {

constexpr int SEQ = 2048, DM = 576, FF = 4608;
constexpr int NCTA = 128;

constexpr uint32_t SM_XN = 0;
constexpr uint32_t SM_RING = 147456;
constexpr uint32_t SM_KV = 212992;
constexpr uint32_t QST = 27648, BST = 16384, KVST = 6144;
constexpr uint32_t G2ST = 43008;
constexpr uint32_t SM_LB = 0, SM_RES = 49152, SM_SEND = 86016, SM_RECV = SM_SEND;
constexpr uint32_t SM_QS = 204800;
constexpr uint32_t SM_ID = 231424;
constexpr uint32_t SM_BAR = 231936;
constexpr uint32_t SM_TAG = 232436;
constexpr uint32_t SM_BAD = 232432;
constexpr uint32_t SM_TOTAL = 232448;
enum { B_F = 0, B_E = 8, B_QF = 16, B_QE = 19, B_SK1 = 22, B_SK2 = 23, B_SH = 24, B_SO1 = 25, B_LK = 26, B_SP = 27, B_OL = 28, B_RX = 29, B_NR = 30, B_X = 32, B_N = 41 };
constexpr int N_G2 = 81, N_AO = 133;
#define N_END (136 + NG0)
#define IT_G2 (73 - NG0)
#define SM_A 7
#define SM_B 12
#define PF_Q 6
constexpr int PF_G1 = 1;
#define NG0_ 5
constexpr int NG0 = NG0_;

constexpr uint32_t HI_SW128 = 0x40000040u;
constexpr uint32_t LO_A = 1u << 16;
constexpr uint32_t LO_B = 512u << 16;
constexpr uint32_t HI_R = 64u, LO_R = 8u << 16;
constexpr uint32_t HI_K = 24u, LO_K = 8u << 16;
constexpr uint32_t HI_V = 8u, LO_V = 24u << 16;
constexpr uint32_t LO_B48 = 384u << 16;
constexpr uint32_t HI_O = 8u, LO_O = 128u << 16;
constexpr uint32_t HI_SW64 = 0x80000020u;

constexpr uint32_t QS_HI = 0x3eae3eaeu, QS_LO = 0x39553955u;
constexpr float MOFF = 90.f;

struct __align__(64) Params {
  CUtensorMap xm, wqkv64, wqkv8, wg, wu, kv, wd[3], wo3[3], wo2[3], wo16[3];
  const __nv_bfloat16 *x, *pwqkv, *pwo, *pwg, *pwu, *pwd;
  __nv_bfloat16* out;
};

__device__ __align__(1024) uint32_t g_H[16 * 576 * 512];
__device__ __align__(1024) uint32_t g_O[NCTA * 9 * 512];
__device__ __align__(1024) uint32_t g_KV[32 * SEQ * 20];
__device__ __align__(1024) uint32_t g_Q[NCTA * 4 * 256 * 8];
__device__ __align__(1024) uint4 g_P[NCTA * 3584];
__device__ __align__(1024) uint4 g_L[NCTA * 384];
__device__ float g_S[NCTA * 8 * SEQ];
__device__ uint32_t g_flags[16 * 32 + NCTA * 32 * 4];
#define FLAG_KV(l, j) (&g_flags[((l) * 8 + (j)) * 32])
#define FLAG_H(c) (&g_flags[16 * 32 + (c) * 32])
#define FLAG_O(c) (&g_flags[16 * 32 + NCTA * 32 + (c) * 32])
#define FLAG_P(c) (&g_flags[16 * 32 + NCTA * 64 + (c) * 32])
#define FLAG_EPOCH(c) (&g_flags[16 * 32 + NCTA * 96 + (c) * 32])
#define STAMP(i)
#define STAMPW(i)
#define TRACE()

template<uint32_t BHI> __device__ __forceinline__ void wg_rs_n192(float* d, uint32_t a0, uint32_t a1, uint32_t a2, uint32_t a3, uint32_t b) {
  asm volatile("{\n.reg .pred p;\n.reg .b64 db;\nsetp.ne.b32 p, 1, 0;\nmov.b64 db, {%100, %101};\n"
    "wgmma.mma_async.sync.aligned.m64n192k16.f32.bf16.bf16 {%0, %1, %2, %3, %4, %5, %6, %7, %8, %9, %10, %11, %12, %13, %14, %15, %16, %17, %18, %19, %20, %21, %22, %23, %24, %25, %26, %27, %28, %29, %30, %31, %32, %33, %34, %35, %36, %37, %38, %39, %40, %41, %42, %43, %44, %45, %46, %47, %48, %49, %50, %51, %52, %53, %54, %55, %56, %57, %58, %59, %60, %61, %62, %63, %64, %65, %66, %67, %68, %69, %70, %71, %72, %73, %74, %75, %76, %77, %78, %79, %80, %81, %82, %83, %84, %85, %86, %87, %88, %89, %90, %91, %92, %93, %94, %95}, {%96, %97, %98, %99}, db, p, 1, 1, 1;\n}\n"
    : "+f"(d[0]), "+f"(d[1]), "+f"(d[2]), "+f"(d[3]), "+f"(d[4]), "+f"(d[5]), "+f"(d[6]), "+f"(d[7]), "+f"(d[8]), "+f"(d[9]), "+f"(d[10]), "+f"(d[11]), "+f"(d[12]), "+f"(d[13]), "+f"(d[14]), "+f"(d[15]), "+f"(d[16]), "+f"(d[17]), "+f"(d[18]), "+f"(d[19]), "+f"(d[20]), "+f"(d[21]), "+f"(d[22]), "+f"(d[23]), "+f"(d[24]), "+f"(d[25]), "+f"(d[26]), "+f"(d[27]), "+f"(d[28]), "+f"(d[29]), "+f"(d[30]), "+f"(d[31]), "+f"(d[32]), "+f"(d[33]), "+f"(d[34]), "+f"(d[35]), "+f"(d[36]), "+f"(d[37]), "+f"(d[38]), "+f"(d[39]), "+f"(d[40]), "+f"(d[41]), "+f"(d[42]), "+f"(d[43]), "+f"(d[44]), "+f"(d[45]), "+f"(d[46]), "+f"(d[47]), "+f"(d[48]), "+f"(d[49]), "+f"(d[50]), "+f"(d[51]), "+f"(d[52]), "+f"(d[53]), "+f"(d[54]), "+f"(d[55]), "+f"(d[56]), "+f"(d[57]), "+f"(d[58]), "+f"(d[59]), "+f"(d[60]), "+f"(d[61]), "+f"(d[62]), "+f"(d[63]), "+f"(d[64]), "+f"(d[65]), "+f"(d[66]), "+f"(d[67]), "+f"(d[68]), "+f"(d[69]), "+f"(d[70]), "+f"(d[71]), "+f"(d[72]), "+f"(d[73]), "+f"(d[74]), "+f"(d[75]), "+f"(d[76]), "+f"(d[77]), "+f"(d[78]), "+f"(d[79]), "+f"(d[80]), "+f"(d[81]), "+f"(d[82]), "+f"(d[83]), "+f"(d[84]), "+f"(d[85]), "+f"(d[86]), "+f"(d[87]), "+f"(d[88]), "+f"(d[89]), "+f"(d[90]), "+f"(d[91]), "+f"(d[92]), "+f"(d[93]), "+f"(d[94]), "+f"(d[95])
    : "r"(a0), "r"(a1), "r"(a2), "r"(a3), "r"(b), "n"(BHI));
}
template<uint32_t BHI> __device__ __forceinline__ void wg_rs_z_n192(float* d, uint32_t a0, uint32_t a1, uint32_t a2, uint32_t a3, uint32_t b) {
  asm volatile("{\n.reg .pred p;\n.reg .b64 db;\nsetp.ne.b32 p, 0, 0;\nmov.b64 db, {%100, %101};\n"
    "wgmma.mma_async.sync.aligned.m64n192k16.f32.bf16.bf16 {%0, %1, %2, %3, %4, %5, %6, %7, %8, %9, %10, %11, %12, %13, %14, %15, %16, %17, %18, %19, %20, %21, %22, %23, %24, %25, %26, %27, %28, %29, %30, %31, %32, %33, %34, %35, %36, %37, %38, %39, %40, %41, %42, %43, %44, %45, %46, %47, %48, %49, %50, %51, %52, %53, %54, %55, %56, %57, %58, %59, %60, %61, %62, %63, %64, %65, %66, %67, %68, %69, %70, %71, %72, %73, %74, %75, %76, %77, %78, %79, %80, %81, %82, %83, %84, %85, %86, %87, %88, %89, %90, %91, %92, %93, %94, %95}, {%96, %97, %98, %99}, db, p, 1, 1, 1;\n}\n"
    : "=f"(d[0]), "=f"(d[1]), "=f"(d[2]), "=f"(d[3]), "=f"(d[4]), "=f"(d[5]), "=f"(d[6]), "=f"(d[7]), "=f"(d[8]), "=f"(d[9]), "=f"(d[10]), "=f"(d[11]), "=f"(d[12]), "=f"(d[13]), "=f"(d[14]), "=f"(d[15]), "=f"(d[16]), "=f"(d[17]), "=f"(d[18]), "=f"(d[19]), "=f"(d[20]), "=f"(d[21]), "=f"(d[22]), "=f"(d[23]), "=f"(d[24]), "=f"(d[25]), "=f"(d[26]), "=f"(d[27]), "=f"(d[28]), "=f"(d[29]), "=f"(d[30]), "=f"(d[31]), "=f"(d[32]), "=f"(d[33]), "=f"(d[34]), "=f"(d[35]), "=f"(d[36]), "=f"(d[37]), "=f"(d[38]), "=f"(d[39]), "=f"(d[40]), "=f"(d[41]), "=f"(d[42]), "=f"(d[43]), "=f"(d[44]), "=f"(d[45]), "=f"(d[46]), "=f"(d[47]), "=f"(d[48]), "=f"(d[49]), "=f"(d[50]), "=f"(d[51]), "=f"(d[52]), "=f"(d[53]), "=f"(d[54]), "=f"(d[55]), "=f"(d[56]), "=f"(d[57]), "=f"(d[58]), "=f"(d[59]), "=f"(d[60]), "=f"(d[61]), "=f"(d[62]), "=f"(d[63]), "=f"(d[64]), "=f"(d[65]), "=f"(d[66]), "=f"(d[67]), "=f"(d[68]), "=f"(d[69]), "=f"(d[70]), "=f"(d[71]), "=f"(d[72]), "=f"(d[73]), "=f"(d[74]), "=f"(d[75]), "=f"(d[76]), "=f"(d[77]), "=f"(d[78]), "=f"(d[79]), "=f"(d[80]), "=f"(d[81]), "=f"(d[82]), "=f"(d[83]), "=f"(d[84]), "=f"(d[85]), "=f"(d[86]), "=f"(d[87]), "=f"(d[88]), "=f"(d[89]), "=f"(d[90]), "=f"(d[91]), "=f"(d[92]), "=f"(d[93]), "=f"(d[94]), "=f"(d[95])
    : "r"(a0), "r"(a1), "r"(a2), "r"(a3), "r"(b), "n"(BHI));
}
template<uint32_t AHI, uint32_t BHI> __device__ __forceinline__ void wg_ss_n128(float* d, uint32_t a, uint32_t b) {
  asm volatile("{\n.reg .pred p;\n.reg .b64 da, db;\nsetp.ne.b32 p, 1, 0;\nmov.b64 da, {%64, %66};\nmov.b64 db, {%65, %67};\n"
    "wgmma.mma_async.sync.aligned.m64n128k16.f32.bf16.bf16 {%0, %1, %2, %3, %4, %5, %6, %7, %8, %9, %10, %11, %12, %13, %14, %15, %16, %17, %18, %19, %20, %21, %22, %23, %24, %25, %26, %27, %28, %29, %30, %31, %32, %33, %34, %35, %36, %37, %38, %39, %40, %41, %42, %43, %44, %45, %46, %47, %48, %49, %50, %51, %52, %53, %54, %55, %56, %57, %58, %59, %60, %61, %62, %63}, da, db, p, 1, 1, 0, 1;\n}\n"
    : "+f"(d[0]), "+f"(d[1]), "+f"(d[2]), "+f"(d[3]), "+f"(d[4]), "+f"(d[5]), "+f"(d[6]), "+f"(d[7]), "+f"(d[8]), "+f"(d[9]), "+f"(d[10]), "+f"(d[11]), "+f"(d[12]), "+f"(d[13]), "+f"(d[14]), "+f"(d[15]), "+f"(d[16]), "+f"(d[17]), "+f"(d[18]), "+f"(d[19]), "+f"(d[20]), "+f"(d[21]), "+f"(d[22]), "+f"(d[23]), "+f"(d[24]), "+f"(d[25]), "+f"(d[26]), "+f"(d[27]), "+f"(d[28]), "+f"(d[29]), "+f"(d[30]), "+f"(d[31]), "+f"(d[32]), "+f"(d[33]), "+f"(d[34]), "+f"(d[35]), "+f"(d[36]), "+f"(d[37]), "+f"(d[38]), "+f"(d[39]), "+f"(d[40]), "+f"(d[41]), "+f"(d[42]), "+f"(d[43]), "+f"(d[44]), "+f"(d[45]), "+f"(d[46]), "+f"(d[47]), "+f"(d[48]), "+f"(d[49]), "+f"(d[50]), "+f"(d[51]), "+f"(d[52]), "+f"(d[53]), "+f"(d[54]), "+f"(d[55]), "+f"(d[56]), "+f"(d[57]), "+f"(d[58]), "+f"(d[59]), "+f"(d[60]), "+f"(d[61]), "+f"(d[62]), "+f"(d[63])
    : "r"(a), "r"(b), "n"(AHI), "n"(BHI));
}
template<uint32_t AHI, uint32_t BHI> __device__ __forceinline__ void wg_ss_z_n128(float* d, uint32_t a, uint32_t b) {
  asm volatile("{\n.reg .pred p;\n.reg .b64 da, db;\nsetp.ne.b32 p, 0, 0;\nmov.b64 da, {%64, %66};\nmov.b64 db, {%65, %67};\n"
    "wgmma.mma_async.sync.aligned.m64n128k16.f32.bf16.bf16 {%0, %1, %2, %3, %4, %5, %6, %7, %8, %9, %10, %11, %12, %13, %14, %15, %16, %17, %18, %19, %20, %21, %22, %23, %24, %25, %26, %27, %28, %29, %30, %31, %32, %33, %34, %35, %36, %37, %38, %39, %40, %41, %42, %43, %44, %45, %46, %47, %48, %49, %50, %51, %52, %53, %54, %55, %56, %57, %58, %59, %60, %61, %62, %63}, da, db, p, 1, 1, 0, 1;\n}\n"
    : "=f"(d[0]), "=f"(d[1]), "=f"(d[2]), "=f"(d[3]), "=f"(d[4]), "=f"(d[5]), "=f"(d[6]), "=f"(d[7]), "=f"(d[8]), "=f"(d[9]), "=f"(d[10]), "=f"(d[11]), "=f"(d[12]), "=f"(d[13]), "=f"(d[14]), "=f"(d[15]), "=f"(d[16]), "=f"(d[17]), "=f"(d[18]), "=f"(d[19]), "=f"(d[20]), "=f"(d[21]), "=f"(d[22]), "=f"(d[23]), "=f"(d[24]), "=f"(d[25]), "=f"(d[26]), "=f"(d[27]), "=f"(d[28]), "=f"(d[29]), "=f"(d[30]), "=f"(d[31]), "=f"(d[32]), "=f"(d[33]), "=f"(d[34]), "=f"(d[35]), "=f"(d[36]), "=f"(d[37]), "=f"(d[38]), "=f"(d[39]), "=f"(d[40]), "=f"(d[41]), "=f"(d[42]), "=f"(d[43]), "=f"(d[44]), "=f"(d[45]), "=f"(d[46]), "=f"(d[47]), "=f"(d[48]), "=f"(d[49]), "=f"(d[50]), "=f"(d[51]), "=f"(d[52]), "=f"(d[53]), "=f"(d[54]), "=f"(d[55]), "=f"(d[56]), "=f"(d[57]), "=f"(d[58]), "=f"(d[59]), "=f"(d[60]), "=f"(d[61]), "=f"(d[62]), "=f"(d[63])
    : "r"(a), "r"(b), "n"(AHI), "n"(BHI));
}
template<uint32_t AHI, uint32_t BHI> __device__ __forceinline__ void wg_ss_n160(float* d, uint32_t a, uint32_t b) {
  asm volatile("{\n.reg .pred p;\n.reg .b64 da, db;\nsetp.ne.b32 p, 1, 0;\nmov.b64 da, {%80, %82};\nmov.b64 db, {%81, %83};\n"
    "wgmma.mma_async.sync.aligned.m64n160k16.f32.bf16.bf16 {%0, %1, %2, %3, %4, %5, %6, %7, %8, %9, %10, %11, %12, %13, %14, %15, %16, %17, %18, %19, %20, %21, %22, %23, %24, %25, %26, %27, %28, %29, %30, %31, %32, %33, %34, %35, %36, %37, %38, %39, %40, %41, %42, %43, %44, %45, %46, %47, %48, %49, %50, %51, %52, %53, %54, %55, %56, %57, %58, %59, %60, %61, %62, %63, %64, %65, %66, %67, %68, %69, %70, %71, %72, %73, %74, %75, %76, %77, %78, %79}, da, db, p, 1, 1, 0, 1;\n}\n"
    : "+f"(d[0]), "+f"(d[1]), "+f"(d[2]), "+f"(d[3]), "+f"(d[4]), "+f"(d[5]), "+f"(d[6]), "+f"(d[7]), "+f"(d[8]), "+f"(d[9]), "+f"(d[10]), "+f"(d[11]), "+f"(d[12]), "+f"(d[13]), "+f"(d[14]), "+f"(d[15]), "+f"(d[16]), "+f"(d[17]), "+f"(d[18]), "+f"(d[19]), "+f"(d[20]), "+f"(d[21]), "+f"(d[22]), "+f"(d[23]), "+f"(d[24]), "+f"(d[25]), "+f"(d[26]), "+f"(d[27]), "+f"(d[28]), "+f"(d[29]), "+f"(d[30]), "+f"(d[31]), "+f"(d[32]), "+f"(d[33]), "+f"(d[34]), "+f"(d[35]), "+f"(d[36]), "+f"(d[37]), "+f"(d[38]), "+f"(d[39]), "+f"(d[40]), "+f"(d[41]), "+f"(d[42]), "+f"(d[43]), "+f"(d[44]), "+f"(d[45]), "+f"(d[46]), "+f"(d[47]), "+f"(d[48]), "+f"(d[49]), "+f"(d[50]), "+f"(d[51]), "+f"(d[52]), "+f"(d[53]), "+f"(d[54]), "+f"(d[55]), "+f"(d[56]), "+f"(d[57]), "+f"(d[58]), "+f"(d[59]), "+f"(d[60]), "+f"(d[61]), "+f"(d[62]), "+f"(d[63]), "+f"(d[64]), "+f"(d[65]), "+f"(d[66]), "+f"(d[67]), "+f"(d[68]), "+f"(d[69]), "+f"(d[70]), "+f"(d[71]), "+f"(d[72]), "+f"(d[73]), "+f"(d[74]), "+f"(d[75]), "+f"(d[76]), "+f"(d[77]), "+f"(d[78]), "+f"(d[79])
    : "r"(a), "r"(b), "n"(AHI), "n"(BHI));
}
template<uint32_t AHI, uint32_t BHI> __device__ __forceinline__ void wg_ss_z_n160(float* d, uint32_t a, uint32_t b) {
  asm volatile("{\n.reg .pred p;\n.reg .b64 da, db;\nsetp.ne.b32 p, 0, 0;\nmov.b64 da, {%80, %82};\nmov.b64 db, {%81, %83};\n"
    "wgmma.mma_async.sync.aligned.m64n160k16.f32.bf16.bf16 {%0, %1, %2, %3, %4, %5, %6, %7, %8, %9, %10, %11, %12, %13, %14, %15, %16, %17, %18, %19, %20, %21, %22, %23, %24, %25, %26, %27, %28, %29, %30, %31, %32, %33, %34, %35, %36, %37, %38, %39, %40, %41, %42, %43, %44, %45, %46, %47, %48, %49, %50, %51, %52, %53, %54, %55, %56, %57, %58, %59, %60, %61, %62, %63, %64, %65, %66, %67, %68, %69, %70, %71, %72, %73, %74, %75, %76, %77, %78, %79}, da, db, p, 1, 1, 0, 1;\n}\n"
    : "=f"(d[0]), "=f"(d[1]), "=f"(d[2]), "=f"(d[3]), "=f"(d[4]), "=f"(d[5]), "=f"(d[6]), "=f"(d[7]), "=f"(d[8]), "=f"(d[9]), "=f"(d[10]), "=f"(d[11]), "=f"(d[12]), "=f"(d[13]), "=f"(d[14]), "=f"(d[15]), "=f"(d[16]), "=f"(d[17]), "=f"(d[18]), "=f"(d[19]), "=f"(d[20]), "=f"(d[21]), "=f"(d[22]), "=f"(d[23]), "=f"(d[24]), "=f"(d[25]), "=f"(d[26]), "=f"(d[27]), "=f"(d[28]), "=f"(d[29]), "=f"(d[30]), "=f"(d[31]), "=f"(d[32]), "=f"(d[33]), "=f"(d[34]), "=f"(d[35]), "=f"(d[36]), "=f"(d[37]), "=f"(d[38]), "=f"(d[39]), "=f"(d[40]), "=f"(d[41]), "=f"(d[42]), "=f"(d[43]), "=f"(d[44]), "=f"(d[45]), "=f"(d[46]), "=f"(d[47]), "=f"(d[48]), "=f"(d[49]), "=f"(d[50]), "=f"(d[51]), "=f"(d[52]), "=f"(d[53]), "=f"(d[54]), "=f"(d[55]), "=f"(d[56]), "=f"(d[57]), "=f"(d[58]), "=f"(d[59]), "=f"(d[60]), "=f"(d[61]), "=f"(d[62]), "=f"(d[63]), "=f"(d[64]), "=f"(d[65]), "=f"(d[66]), "=f"(d[67]), "=f"(d[68]), "=f"(d[69]), "=f"(d[70]), "=f"(d[71]), "=f"(d[72]), "=f"(d[73]), "=f"(d[74]), "=f"(d[75]), "=f"(d[76]), "=f"(d[77]), "=f"(d[78]), "=f"(d[79])
    : "r"(a), "r"(b), "n"(AHI), "n"(BHI));
}
template<uint32_t BHI> __device__ __forceinline__ void wg_rs_n32(float* d, uint32_t a0, uint32_t a1, uint32_t a2, uint32_t a3, uint32_t b) {
  asm volatile("{\n.reg .pred p;\n.reg .b64 db;\nsetp.ne.b32 p, 1, 0;\nmov.b64 db, {%20, %21};\n"
    "wgmma.mma_async.sync.aligned.m64n32k16.f32.bf16.bf16 {%0, %1, %2, %3, %4, %5, %6, %7, %8, %9, %10, %11, %12, %13, %14, %15}, {%16, %17, %18, %19}, db, p, 1, 1, 1;\n}\n"
    : "+f"(d[0]), "+f"(d[1]), "+f"(d[2]), "+f"(d[3]), "+f"(d[4]), "+f"(d[5]), "+f"(d[6]), "+f"(d[7]), "+f"(d[8]), "+f"(d[9]), "+f"(d[10]), "+f"(d[11]), "+f"(d[12]), "+f"(d[13]), "+f"(d[14]), "+f"(d[15])
    : "r"(a0), "r"(a1), "r"(a2), "r"(a3), "r"(b), "n"(BHI));
}
template<uint32_t BHI> __device__ __forceinline__ void wg_rs_z_n32(float* d, uint32_t a0, uint32_t a1, uint32_t a2, uint32_t a3, uint32_t b) {
  asm volatile("{\n.reg .pred p;\n.reg .b64 db;\nsetp.ne.b32 p, 0, 0;\nmov.b64 db, {%20, %21};\n"
    "wgmma.mma_async.sync.aligned.m64n32k16.f32.bf16.bf16 {%0, %1, %2, %3, %4, %5, %6, %7, %8, %9, %10, %11, %12, %13, %14, %15}, {%16, %17, %18, %19}, db, p, 1, 1, 1;\n}\n"
    : "=f"(d[0]), "=f"(d[1]), "=f"(d[2]), "=f"(d[3]), "=f"(d[4]), "=f"(d[5]), "=f"(d[6]), "=f"(d[7]), "=f"(d[8]), "=f"(d[9]), "=f"(d[10]), "=f"(d[11]), "=f"(d[12]), "=f"(d[13]), "=f"(d[14]), "=f"(d[15])
    : "r"(a0), "r"(a1), "r"(a2), "r"(a3), "r"(b), "n"(BHI));
}
template<uint32_t BHI> __device__ __forceinline__ void wg_rs_n64(float* d, uint32_t a0, uint32_t a1, uint32_t a2, uint32_t a3, uint32_t b) {
  asm volatile("{\n.reg .pred p;\n.reg .b64 db;\nsetp.ne.b32 p, 1, 0;\nmov.b64 db, {%36, %37};\n"
    "wgmma.mma_async.sync.aligned.m64n64k16.f32.bf16.bf16 {%0, %1, %2, %3, %4, %5, %6, %7, %8, %9, %10, %11, %12, %13, %14, %15, %16, %17, %18, %19, %20, %21, %22, %23, %24, %25, %26, %27, %28, %29, %30, %31}, {%32, %33, %34, %35}, db, p, 1, 1, 0;\n}\n"
    : "+f"(d[0]), "+f"(d[1]), "+f"(d[2]), "+f"(d[3]), "+f"(d[4]), "+f"(d[5]), "+f"(d[6]), "+f"(d[7]), "+f"(d[8]), "+f"(d[9]), "+f"(d[10]), "+f"(d[11]), "+f"(d[12]), "+f"(d[13]), "+f"(d[14]), "+f"(d[15]), "+f"(d[16]), "+f"(d[17]), "+f"(d[18]), "+f"(d[19]), "+f"(d[20]), "+f"(d[21]), "+f"(d[22]), "+f"(d[23]), "+f"(d[24]), "+f"(d[25]), "+f"(d[26]), "+f"(d[27]), "+f"(d[28]), "+f"(d[29]), "+f"(d[30]), "+f"(d[31])
    : "r"(a0), "r"(a1), "r"(a2), "r"(a3), "r"(b), "n"(BHI));
}
template<uint32_t BHI> __device__ __forceinline__ void wg_rs_z_n64(float* d, uint32_t a0, uint32_t a1, uint32_t a2, uint32_t a3, uint32_t b) {
  asm volatile("{\n.reg .pred p;\n.reg .b64 db;\nsetp.ne.b32 p, 0, 0;\nmov.b64 db, {%36, %37};\n"
    "wgmma.mma_async.sync.aligned.m64n64k16.f32.bf16.bf16 {%0, %1, %2, %3, %4, %5, %6, %7, %8, %9, %10, %11, %12, %13, %14, %15, %16, %17, %18, %19, %20, %21, %22, %23, %24, %25, %26, %27, %28, %29, %30, %31}, {%32, %33, %34, %35}, db, p, 1, 1, 0;\n}\n"
    : "=f"(d[0]), "=f"(d[1]), "=f"(d[2]), "=f"(d[3]), "=f"(d[4]), "=f"(d[5]), "=f"(d[6]), "=f"(d[7]), "=f"(d[8]), "=f"(d[9]), "=f"(d[10]), "=f"(d[11]), "=f"(d[12]), "=f"(d[13]), "=f"(d[14]), "=f"(d[15]), "=f"(d[16]), "=f"(d[17]), "=f"(d[18]), "=f"(d[19]), "=f"(d[20]), "=f"(d[21]), "=f"(d[22]), "=f"(d[23]), "=f"(d[24]), "=f"(d[25]), "=f"(d[26]), "=f"(d[27]), "=f"(d[28]), "=f"(d[29]), "=f"(d[30]), "=f"(d[31])
    : "r"(a0), "r"(a1), "r"(a2), "r"(a3), "r"(b), "n"(BHI));
}
template<uint32_t BHI> __device__ __forceinline__ void wg_rs_n24(float* d, uint32_t a0, uint32_t a1, uint32_t a2, uint32_t a3, uint32_t b) {
  asm volatile("{\n.reg .pred p;\n.reg .b64 db;\nsetp.ne.b32 p, 1, 0;\nmov.b64 db, {%16, %17};\n"
    "wgmma.mma_async.sync.aligned.m64n24k16.f32.bf16.bf16 {%0, %1, %2, %3, %4, %5, %6, %7, %8, %9, %10, %11}, {%12, %13, %14, %15}, db, p, 1, 1, 1;\n}\n"
    : "+f"(d[0]), "+f"(d[1]), "+f"(d[2]), "+f"(d[3]), "+f"(d[4]), "+f"(d[5]), "+f"(d[6]), "+f"(d[7]), "+f"(d[8]), "+f"(d[9]), "+f"(d[10]), "+f"(d[11])
    : "r"(a0), "r"(a1), "r"(a2), "r"(a3), "r"(b), "n"(BHI));
}
template<uint32_t BHI> __device__ __forceinline__ void wg_rs_z_n24(float* d, uint32_t a0, uint32_t a1, uint32_t a2, uint32_t a3, uint32_t b) {
  asm volatile("{\n.reg .pred p;\n.reg .b64 db;\nsetp.ne.b32 p, 0, 0;\nmov.b64 db, {%16, %17};\n"
    "wgmma.mma_async.sync.aligned.m64n24k16.f32.bf16.bf16 {%0, %1, %2, %3, %4, %5, %6, %7, %8, %9, %10, %11}, {%12, %13, %14, %15}, db, p, 1, 1, 1;\n}\n"
    : "=f"(d[0]), "=f"(d[1]), "=f"(d[2]), "=f"(d[3]), "=f"(d[4]), "=f"(d[5]), "=f"(d[6]), "=f"(d[7]), "=f"(d[8]), "=f"(d[9]), "=f"(d[10]), "=f"(d[11])
    : "r"(a0), "r"(a1), "r"(a2), "r"(a3), "r"(b), "n"(BHI));
}
template<uint32_t BHI> __device__ __forceinline__ void wg_rsb_n64(float* d, uint32_t a0, uint32_t a1, uint32_t a2, uint32_t a3, uint32_t b) {
  asm volatile("{\n.reg .pred p;\n.reg .b64 db;\nsetp.ne.b32 p, 1, 0;\nmov.b64 db, {%36, %37};\n"
    "wgmma.mma_async.sync.aligned.m64n64k16.f32.bf16.bf16 {%0, %1, %2, %3, %4, %5, %6, %7, %8, %9, %10, %11, %12, %13, %14, %15, %16, %17, %18, %19, %20, %21, %22, %23, %24, %25, %26, %27, %28, %29, %30, %31}, {%32, %33, %34, %35}, db, p, 1, 1, 1;\n}\n"
    : "+f"(d[0]), "+f"(d[1]), "+f"(d[2]), "+f"(d[3]), "+f"(d[4]), "+f"(d[5]), "+f"(d[6]), "+f"(d[7]), "+f"(d[8]), "+f"(d[9]), "+f"(d[10]), "+f"(d[11]), "+f"(d[12]), "+f"(d[13]), "+f"(d[14]), "+f"(d[15]), "+f"(d[16]), "+f"(d[17]), "+f"(d[18]), "+f"(d[19]), "+f"(d[20]), "+f"(d[21]), "+f"(d[22]), "+f"(d[23]), "+f"(d[24]), "+f"(d[25]), "+f"(d[26]), "+f"(d[27]), "+f"(d[28]), "+f"(d[29]), "+f"(d[30]), "+f"(d[31])
    : "r"(a0), "r"(a1), "r"(a2), "r"(a3), "r"(b), "n"(BHI));
}
template<uint32_t BHI> __device__ __forceinline__ void wg_rsb_z_n64(float* d, uint32_t a0, uint32_t a1, uint32_t a2, uint32_t a3, uint32_t b) {
  asm volatile("{\n.reg .pred p;\n.reg .b64 db;\nsetp.ne.b32 p, 0, 0;\nmov.b64 db, {%36, %37};\n"
    "wgmma.mma_async.sync.aligned.m64n64k16.f32.bf16.bf16 {%0, %1, %2, %3, %4, %5, %6, %7, %8, %9, %10, %11, %12, %13, %14, %15, %16, %17, %18, %19, %20, %21, %22, %23, %24, %25, %26, %27, %28, %29, %30, %31}, {%32, %33, %34, %35}, db, p, 1, 1, 1;\n}\n"
    : "=f"(d[0]), "=f"(d[1]), "=f"(d[2]), "=f"(d[3]), "=f"(d[4]), "=f"(d[5]), "=f"(d[6]), "=f"(d[7]), "=f"(d[8]), "=f"(d[9]), "=f"(d[10]), "=f"(d[11]), "=f"(d[12]), "=f"(d[13]), "=f"(d[14]), "=f"(d[15]), "=f"(d[16]), "=f"(d[17]), "=f"(d[18]), "=f"(d[19]), "=f"(d[20]), "=f"(d[21]), "=f"(d[22]), "=f"(d[23]), "=f"(d[24]), "=f"(d[25]), "=f"(d[26]), "=f"(d[27]), "=f"(d[28]), "=f"(d[29]), "=f"(d[30]), "=f"(d[31])
    : "r"(a0), "r"(a1), "r"(a2), "r"(a3), "r"(b), "n"(BHI));
}

__device__ __forceinline__ void wg_fence() { asm volatile("wgmma.fence.sync.aligned;" ::: "memory"); }
__device__ __forceinline__ void wg_commit() { asm volatile("wgmma.commit_group.sync.aligned;" ::: "memory"); }
template <int N> __device__ __forceinline__ void wg_wait() { asm volatile("wgmma.wait_group.sync.aligned %0;" ::"n"(N) : "memory"); }
template <int R> __device__ __forceinline__ void pin(float* d) {
#pragma unroll
  for (int i = 0; i < R; i++) asm volatile("" : "+f"(d[i])::"memory");
}
template <int R> __device__ __forceinline__ void pin(uint32_t* d) {
#pragma unroll
  for (int i = 0; i < R; i++) asm volatile("" : "+r"(d[i])::"memory");
}
__device__ __forceinline__ float ex2(float x) { float y; asm("ex2.approx.ftz.f32 %0, %1;" : "=f"(y) : "f"(x)); return y; }
__device__ __forceinline__ float tanh_fast(float x) { float y; asm("tanh.approx.f32 %0, %1;" : "=f"(y) : "f"(x)); return y; }
__device__ __forceinline__ uint32_t pack(float lo, float hi) { uint32_t r; asm("cvt.rn.bf16x2.f32 %0, %1, %2;" : "=r"(r) : "f"(hi), "f"(lo)); return r; }
__device__ __forceinline__ float bf_lo(uint32_t v) { return __uint_as_float(v << 16); }
__device__ __forceinline__ float bf_hi(uint32_t v) { return __uint_as_float(v & 0xffff0000u); }
__device__ __forceinline__ float bf_round(float x) { return bf_lo(pack(x, 0.f)); }

__device__ __forceinline__ void mbar_init(uint32_t bar, uint32_t cnt) { asm volatile("mbarrier.init.shared::cta.b64 [%0], %1;" ::"r"(bar), "r"(cnt) : "memory"); }
__device__ __forceinline__ void mbar_expect(uint32_t bar, uint32_t bytes) { asm volatile("mbarrier.arrive.expect_tx.shared::cta.b64 _, [%0], %1;" ::"r"(bar), "r"(bytes) : "memory"); }
__device__ __forceinline__ void mbar_wait(uint32_t bar, uint32_t parity) {
  asm volatile(
      "{\n.reg .pred p;\n.reg .u32 c;\n"
      "mbarrier.try_wait.parity.shared::cta.b64 p, [%0], %1;\n"
      "@p bra.uni DONE;\n"
      "mov.u32 c, 0;\n"
      "LOOP:\n"
      "mbarrier.try_wait.parity.shared::cta.b64 p, [%0], %1;\n"
      "@p bra.uni DONE;\n"
      "add.u32 c, c, 1;\n"
      "setp.lt.u32 p, c, 0x4000000;\n"
      "@p bra.uni LOOP;\n"
      "trap;\n"
      "DONE:\n}\n" ::"r"(bar), "r"(parity) : "memory");
}
__device__ __forceinline__ uint32_t mbar_test(uint32_t bar, uint32_t parity) {
  uint32_t ok;
  asm volatile("{\n.reg .pred p;\nmbarrier.test_wait.parity.shared::cta.b64 p, [%1], %2;\nselp.u32 %0, 1, 0, p;\n}\n" : "=r"(ok) : "r"(bar), "r"(parity) : "memory");
  return ok;
}
__device__ __forceinline__ void mbar_arrive_if(uint32_t bar, uint32_t cond) {
  asm volatile("{\n.reg .pred p;\nsetp.ne.u32 p, %1, 0;\n@p mbarrier.arrive.shared::cta.b64 _, [%0];\n}\n" ::"r"(bar), "r"(cond) : "memory");
}
__device__ __forceinline__ uint32_t bsub2(uint32_t a, uint32_t b) { uint32_t d; asm("sub.rn.bf16x2 %0, %1, %2;" : "=r"(d) : "r"(a), "r"(b)); return d; }
__device__ __forceinline__ uint32_t bscale2(uint32_t d, uint32_t hi, uint32_t lo) {
  uint32_t t, r;
  asm("mul.rn.bf16x2 %0, %1, %2;" : "=r"(t) : "r"(d), "r"(lo));
  asm("fma.rn.bf16x2 %0, %1, %2, %3;" : "=r"(r) : "r"(d), "r"(hi), "r"(t));
  return r;
}
__device__ __forceinline__ void flag_wait(const uint32_t* f, uint32_t target) {
  asm volatile(
      "{\n.reg .pred p;\n.reg .u32 c, v;\n"
      "mov.u32 c, 0;\n"
      "LOOP:\n"
      "ld.acquire.gpu.global.u32 v, [%0];\n"
      "sub.u32 v, v, %1;\n"
      "setp.ge.s32 p, v, 0;\n"
      "@p bra DONE;\n"
      "add.u32 c, c, 1;\n"
      "setp.lt.u32 p, c, 0x1000000;\n"
      "@p bra LOOP;\n"
      "trap;\n"
      "DONE:\n}\n" ::"l"(f), "r"(target) : "memory");
}
__device__ __forceinline__ uint32_t flag_wait_v(const uint32_t* f, uint32_t target) {
  uint32_t v;
  asm volatile(
      "{\n.reg .pred p;\n.reg .u32 c, d;\n"
      "mov.u32 c, 0;\n"
      "LOOP:\n"
      "ld.acquire.gpu.global.u32 %0, [%1];\n"
      "sub.u32 d, %0, %2;\n"
      "setp.ge.s32 p, d, 0;\n"
      "@p bra DONE;\n"
      "add.u32 c, c, 1;\n"
      "setp.lt.u32 p, c, 0x1000000;\n"
      "@p bra LOOP;\n"
      "trap;\n"
      "DONE:\n}\n" : "=&r"(v) : "l"(f), "r"(target) : "memory");
  return v;
}
__device__ __forceinline__ float sqrt_fast(float x) { float y; asm("sqrt.approx.f32 %0, %1;" : "=f"(y) : "f"(x)); return y; }
__device__ __forceinline__ float rcp_fast(float x) { float y; asm("rcp.approx.ftz.f32 %0, %1;" : "=f"(y) : "f"(x)); return y; }
__device__ __forceinline__ void ldsm4(uint32_t* v, uint32_t addr) {
  asm volatile("ldmatrix.sync.aligned.m8n8.x4.shared.b16 {%0,%1,%2,%3}, [%4];" : "=r"(v[0]), "=r"(v[1]), "=r"(v[2]), "=r"(v[3]) : "r"(addr) : "memory");
}
__device__ __forceinline__ void stsm4(uint32_t addr, uint32_t a, uint32_t b, uint32_t c, uint32_t d) {
  asm volatile("stmatrix.sync.aligned.m8n8.x4.shared.b16 [%0], {%1,%2,%3,%4};" ::"r"(addr), "r"(a), "r"(b), "r"(c), "r"(d) : "memory");
}
__device__ __forceinline__ void flag_add(uint32_t* f) { asm volatile("red.relaxed.gpu.global.add.u32 [%0], 1;" ::"l"(f) : "memory"); }
__device__ __forceinline__ void fence_gpu() { asm volatile("fence.acq_rel.gpu;" ::: "memory"); }
__device__ __forceinline__ void fence_async() { asm volatile("fence.proxy.async.global;" ::: "memory"); }
__device__ __forceinline__ void tma2d(uint32_t dst, const CUtensorMap* tm, uint32_t bar, int c0, int c1) {
  asm volatile("cp.async.bulk.tensor.2d.shared::cluster.global.mbarrier::complete_tx::bytes [%0], [%1, {%3, %4}], [%2];" ::"r"(dst), "l"(tm), "r"(bar), "r"(c0), "r"(c1) : "memory");
}
__device__ __forceinline__ void tma2d_h(uint32_t dst, const CUtensorMap* tm, uint32_t bar, int c0, int c1, uint64_t pol) {
  asm volatile("cp.async.bulk.tensor.2d.shared::cluster.global.mbarrier::complete_tx::bytes.L2::cache_hint [%0], [%1, {%3, %4}], [%2], %5;" ::"r"(dst), "l"(tm), "r"(bar), "r"(c0), "r"(c1), "l"(pol) : "memory");
}
__device__ __forceinline__ void bulk_s2g(void* dst, uint32_t src, uint32_t bytes) {
  asm volatile("cp.async.bulk.global.shared::cta.bulk_group [%0], [%1], %2;" ::"l"(dst), "r"(src), "r"(bytes) : "memory");
}
__device__ __forceinline__ void mma_ones(float* c, const uint32_t* a) {
  asm("mma.sync.aligned.m16n8k16.row.col.f32.bf16.bf16.f32 {%0,%1,%2,%3}, {%4,%5,%6,%7}, {%8,%8}, {%0,%1,%2,%3};"
      : "+f"(c[0]), "+f"(c[1]), "+f"(c[2]), "+f"(c[3]) : "r"(a[0]), "r"(a[1]), "r"(a[2]), "r"(a[3]), "r"(0x3f803f80u));
}
__device__ __forceinline__ void tma5d(uint32_t dst, const CUtensorMap* tm, uint32_t bar, int c0, int c4) {
  asm volatile("cp.async.bulk.tensor.5d.shared::cluster.global.mbarrier::complete_tx::bytes [%0], [%1, {%3, %5, %5, %5, %4}], [%2];" ::"r"(dst), "l"(tm), "r"(bar), "r"(c0), "r"(c4), "r"(0) : "memory");
}
__device__ __forceinline__ void tma3d(uint32_t dst, const CUtensorMap* tm, uint32_t bar, int c0, int c2) {
  asm volatile("cp.async.bulk.tensor.3d.shared::cluster.global.mbarrier::complete_tx::bytes [%0], [%1, {%3, %5, %4}], [%2];" ::"r"(dst), "l"(tm), "r"(bar), "r"(c0), "r"(c2), "r"(0) : "memory");
}
__device__ __forceinline__ void bulk_g2s(uint32_t dst, const void* src, uint32_t bytes, uint32_t bar) {
  asm volatile("cp.async.bulk.shared::cluster.global.mbarrier::complete_tx::bytes [%0], [%1], %2, [%3];" ::"r"(dst), "l"(src), "r"(bytes), "r"(bar) : "memory");
}
__device__ __forceinline__ void pf_line(const void* p) { asm volatile("prefetch.global.L2 [%0];" ::"l"(p) : "memory"); }
__device__ __forceinline__ int fresh_tid() { int v; asm volatile("mov.u32 %0, %%tid.x;" : "=r"(v)); return v; }
struct Att {
  float s[32];
  float o[12];
  uint32_t p[16];
  uint32_t q[8];
};

__device__ __forceinline__ float warp_sum(float v) {
#pragma unroll 1
  for (int d = 16; d; d >>= 1) v += __shfl_xor_sync(0xffffffffu, v, d);
  return v;
}
#define OPAQUE(x) asm volatile("" : "+r"(x))
__device__ __forceinline__ void attn_slow_row(int cta, uint32_t& w) {
  float mx = -INFINITY;
#pragma unroll 1
  for (uint32_t key = threadIdx.x & 31; key < SEQ; key += 32) {
    float s = 0.f;
#pragma unroll 1
    for (uint32_t v = 0; v < 9; v++) {
      OPAQUE(w); OPAQUE(key);
      const uint32_t hp = (w >> 4) & 3, pos = (v + hp) & 3;
      const uint32_t q = g_Q[(((cta * 4 + hp) * 2 + (v >> 3)) * 256 + ((w >> 6) & 7) * 32 + (w & 7) * 4 + pos) * 4 + 2 * ((v >> 2) & 1) + ((w >> 3) & 1)];
      const uint32_t u = g_KV[(4 * (cta & 7) + hp) * SEQ * 20 + (key >> 3) * 160 + (key & 7) * 4 + (v >> 2) * 32 + pos];
      s = fmaf(bf_lo(q), bf_lo(u), fmaf(bf_hi(q), bf_hi(u), s));
    }
    g_S[(cta * 8 + ((w >> 6) & 7)) * SEQ + key] = s;
    mx = fmaxf(mx, s);
  }
#pragma unroll 1
  for (int d = 16; d; d >>= 1) mx = fmaxf(mx, __shfl_xor_sync(0xffffffffu, mx, d));
  float l = 0.f;
#pragma unroll 1
  for (uint32_t key = threadIdx.x & 31; key < SEQ; key += 32) l += ex2(g_S[(cta * 8 + ((w >> 6) & 7)) * SEQ + key] - mx);
  l = 2.f * rcp_fast(warp_sum(l));
#pragma unroll 1
  for (uint32_t v = w >> 9; v < 9; v++) {
    float a = 0.f, b = 0.f;
#pragma unroll 1
    for (uint32_t key = threadIdx.x & 31; key < SEQ; key += 32) {
      OPAQUE(w); OPAQUE(v);
      const uint32_t hp = (w >> 4) & 3;
      const uint32_t u = g_KV[(4 * (cta & 7) + hp) * SEQ * 20 + (key >> 3) * 160 + (key & 7) * 4 + (v < 8 ? (3 + (v >> 2)) * 32 + (v & 3) : 64 + ((hp + 2) & 3))];
      const float p = ex2(g_S[(cta * 8 + ((w >> 6) & 7)) * SEQ + key] - mx);
      a = fmaf(p, bf_lo(u), a); b = fmaf(p, bf_hi(u), b);
    }
    a = warp_sum(a); b = warp_sum(b);
    OPAQUE(w);
    const uint32_t hp = (w >> 4) & 3;
    if ((threadIdx.x & 31) == 0) g_O[cta * 9 * 512 + (((w >> 6) & 7) * 16 + (w & 15)) * 4 + (v < 8 ? (2 * hp + (v >> 2)) * 512 + (v & 3) : 8 * 512 + hp)] = pack(a * l, b * l);
  }
}

__device__ __forceinline__ uint32_t bad_heads(uint32_t bad_addr, int wr) {
  uint32_t bad;
  __syncwarp();
  asm volatile("ld.volatile.shared.u32 %0, [%1];" : "=r"(bad) : "r"(bad_addr) : "memory");
  return __shfl_sync(0xffffffffu, (bad >> (4 * wr)) & 15, 0);
}
__device__ __forceinline__ void repair_rows(int cta, int wr, uint32_t bad, int last_head, bool final) {
#pragma unroll 1
  for (uint32_t w = wr * 64; w < wr * 64 + 64; w++) {
    if (!((bad >> ((w >> 4) & 3)) & 1)) continue;
    if (final && ((w >> 4) & 3) != last_head) w |= 8u << 9;
    attn_slow_row(cta, w);
    w &= 511;
  }
  __syncwarp();
}
__device__ __forceinline__ void o_normalise(const float* o, uint32_t* w, uint32_t& x0, uint32_t& x1, int hp, int lane, uint32_t bad_addr, int wr) {
  const int src = (lane & ~3) | ((hp + 1) & 3);
  float l0 = __shfl_sync(0xffffffffu, o[0], src), l1 = __shfl_sync(0xffffffffu, o[2], src);
  float sa = 0.f;
#pragma unroll
  for (int i = 0; i < 12; i++) sa += fabsf(o[i]);
  bool ok = (l0 <= 1.329228e36f) && (l1 <= 1.329228e36f) && (l0 > 0.f) && (l1 > 0.f) && (sa <= 3.0e38f);
  float i0 = 2.f * rcp_fast(l0), i1 = 2.f * rcp_fast(l1);
  w[0] = pack(o[4] * i0, o[5] * i0);
  w[1] = pack(o[6] * i1, o[7] * i1);
  w[2] = pack(o[8] * i0, o[9] * i0);
  w[3] = pack(o[10] * i1, o[11] * i1);
  if ((lane & 3) == ((hp + 2) & 3)) { x0 = pack(o[0] * i0, o[1] * i0); x1 = pack(o[2] * i1, o[3] * i1); }
  if (!ok) asm volatile("red.shared.or.b32 [%0], %1;" ::"r"(bad_addr), "r"(1u << (4 * wr + hp)) : "memory");
}

__device__ __forceinline__ void issue_pv(Att& a, uint32_t kdesc) {
  const uint32_t vdesc = kdesc + 192 + (LO_V - LO_K);
#pragma unroll
  for (int k = 0; k < 4; k++) wg_rs_n24<HI_V>(a.o, a.p[4 * k], a.p[4 * k + 1], a.p[4 * k + 2], a.p[4 * k + 3], vdesc + k * 48);
}
__device__ __forceinline__ void issue_att(Att& a, uint32_t kdesc) {
  issue_pv(a, kdesc);
  wg_rs_z_n64<HI_K>(a.s, a.q[0], a.q[1], a.q[2], a.q[3], kdesc);
  wg_rs_n64<HI_K>(a.s, a.q[4], a.q[5], a.q[6], a.q[7], kdesc + 16);
}
__device__ __forceinline__ void softmax_a(Att& a) {
#pragma unroll
  for (int i = 0; i < SM_A; i++) a.p[i] = pack(ex2(a.s[2 * i]), ex2(a.s[2 * i + 1]));
  pin<SM_A>(a.p);
}
__device__ __forceinline__ void softmax_b(Att& a) {
#pragma unroll
  for (int i = SM_A; i < SM_B; i++) a.p[i] = pack(ex2(a.s[2 * i]), ex2(a.s[2 * i + 1]));
  a.s[2 * SM_B] = ex2(a.s[2 * SM_B]); a.s[2 * SM_B + 1] = ex2(a.s[2 * SM_B + 1]);
  pin<SM_B - SM_A>(a.p + SM_A); pin<2>(a.s + 2 * SM_B);
}
__device__ __forceinline__ void softmax_c(Att& a) {
  a.p[SM_B] = pack(a.s[2 * SM_B], a.s[2 * SM_B + 1]);
#pragma unroll
  for (int i = SM_B + 1; i < 16; i++) a.p[i] = pack(ex2(a.s[2 * i]), ex2(a.s[2 * i + 1]));
  pin<16 - SM_B>(a.p + SM_B);
}
__device__ __forceinline__ void first_tile(Att& a, int hp, int lane) {
  float m0 = fmaxf(a.s[0], a.s[1]), m1 = fmaxf(a.s[2], a.s[3]);
#pragma unroll
  for (int i = 4; i < 32; i += 4) { m0 = fmaxf(m0, fmaxf(a.s[i], a.s[i + 1])); m1 = fmaxf(m1, fmaxf(a.s[i + 2], a.s[i + 3])); }
  m0 = fmaxf(m0, __shfl_xor_sync(0xffffffffu, m0, 1)); m1 = fmaxf(m1, __shfl_xor_sync(0xffffffffu, m1, 1));
  m0 = fmaxf(m0, __shfl_xor_sync(0xffffffffu, m0, 2)); m1 = fmaxf(m1, __shfl_xor_sync(0xffffffffu, m1, 2));
  float n0 = -(m0 + MOFF), n1 = -(m1 + MOFF);
  float h0 = bf_round(n0), h1 = bf_round(n1);
  uint32_t e0 = pack(h0, n0 - h0), e1 = pack(h1, n1 - h1);
  n0 = h0 + bf_hi(e0); n1 = h1 + bf_hi(e1);
  if ((lane & 3) == ((hp + 1) & 3)) { a.q[4] = e0; a.q[5] = e1; }
#pragma unroll
  for (int i = 0; i < 32; i += 4) { a.s[i] += n0; a.s[i + 1] += n0; a.s[i + 2] += n1; a.s[i + 3] += n1; }
#pragma unroll
  for (int i = 0; i < 12; i++) a.o[i] = 0.f;
  pin<12>(a.o); pin<8>(a.q);
}
__device__ __forceinline__ void fetch_q(uint32_t* q, int cta, int hp, int tid) {
  const uint4* src = reinterpret_cast<const uint4*>(g_Q) + (cta * 4 + hp) * 512 + tid;
  const uint4 u = __ldcg(src);
  const uint2 v = __ldcg(reinterpret_cast<const uint2*>(src + 256));
  q[0] = u.x; q[1] = u.y; q[2] = u.z; q[3] = u.w; q[4] = v.x; q[5] = v.y;
}
__device__ __forceinline__ void h_epilogue(const float* acc, uint32_t* dst) {
#pragma unroll
  for (int b = 0; b < 4; b++) {
    uint32_t w[2][2];
#pragma unroll
    for (int i = 0; i < 2; i++) {
      float h[4];
#pragma unroll
      for (int e = 0; e < 4; e++) {
        const float g = acc[(2 * b + i) * 4 + e], u = acc[32 + (2 * b + i) * 4 + e];
        h[e] = fmaf(tanh_fast(0.5f * g), u, u);
      }
      w[0][i] = pack(h[0], h[1]); w[1][i] = pack(h[2], h[3]);
    }
    *reinterpret_cast<uint2*>(dst + 1024 * b) = make_uint2(w[0][0], w[0][1]);
    *reinterpret_cast<uint2*>(dst + 1024 * b + 32) = make_uint2(w[1][0], w[1][1]);
  }
}
__device__ __forceinline__ void rotate9(uint32_t (&v)[9][2]) {
#pragma unroll
  for (int rh = 0; rh < 2; rh++) {
    const uint32_t r = v[8][rh];
#pragma unroll
    for (int i = 8; i > 0; i--) v[i][rh] = v[i - 1][rh];
    v[0][rh] = r;
  }
}
template <int HP> __device__ __forceinline__ void store_kv_head(uint32_t (&pk)[2][9][2], uint32_t* kvp, int lane, uint32_t sk = 0, uint32_t sv = 0) {
  const int t = lane & 3, dv = ((t - HP) & 3) - t;
  const bool up = t < HP;
#pragma unroll
  for (int rh = 0; rh < 2; rh++) {
    uint32_t* d = kvp + HP * SEQ * 20 + rh * 160;
    const uint32_t c0 = up ? pk[0][2 * HP + 1][rh] : pk[0][2 * HP][rh], c1 = up ? pk[0][2 * HP + 2][rh] : pk[0][2 * HP + 1][rh];
    const uint32_t c3 = up ? pk[1][2 * HP + 1][rh] : pk[1][2 * HP][rh], c4 = up ? pk[1][2 * HP + 2][rh] : pk[1][2 * HP + 1][rh];
    const uint32_t v9 = __shfl_sync(0xffffffffu, pk[1][2 * HP + 2][rh], (lane & ~3) | HP);
    const uint32_t c2 = t == HP ? pk[0][2 * HP + 2][rh] : t == ((HP + 1) & 3) ? 0x3f803f80u : t == ((HP + 2) & 3) ? v9 : 0u;
    d[0] = c0; d[32] = c1; d[64] = c2; d[96 + dv] = c3; d[128 + dv] = c4;
    if (sk) {
      asm volatile("st.shared.b32 [%0], %1;\nst.shared.b32 [%0 + 128], %2;\nst.shared.b32 [%0 + 256], %3;" ::"r"(sk + rh * 384), "r"(c0), "r"(c1), "r"(c2) : "memory");
      asm volatile("st.shared.b32 [%0], %1;\nst.shared.b32 [%2 + 128], %3;\nst.shared.b32 [%2 + 256], %4;" ::"r"(sv + rh * 384), "r"(c2), "r"(sv + rh * 384 + dv * 4), "r"(c3), "r"(c4) : "memory");
    }
  }
}

template <int OFF> __device__ __forceinline__ void ld4(uint32_t* v, const void* p) {
  asm volatile("ld.relaxed.gpu.global.v4.b32 {%0,%1,%2,%3}, [%4 + %5];" : "=r"(v[0]), "=r"(v[1]), "=r"(v[2]), "=r"(v[3]) : "l"(p), "n"(OFF) : "memory");
}
template <int OFF> __device__ __forceinline__ void ld2(uint32_t* v, const void* p) {
  asm volatile("ld.relaxed.gpu.global.v2.b32 {%0,%1}, [%2 + %3];" : "=r"(v[0]), "=r"(v[1]) : "l"(p), "n"(OFF) : "memory");
}
__device__ __forceinline__ void stage_partials(const float* acc, uint32_t dst, int tid) {
  const int lane = tid & 31, row = (tid >> 5) * 16 + (lane & 15);
  const uint32_t r128 = dst + row * 128, r64 = dst + 49152 + row * 64;
#pragma unroll
  for (int i = 0; i < 12; i++) {
    const float* v = acc + 8 * i;
    stsm4(r128 + (i >> 2) * 16384 + (((2 * (i & 3) + (lane >> 4)) ^ (row & 7)) << 4), pack(v[0], v[1]), pack(v[2], v[3]), pack(v[4], v[5]), pack(v[6], v[7]));
  }
#pragma unroll
  for (int i = 0; i < 2; i++) {
    const float* v = acc + 128 + 8 * i;
    stsm4(r64 + (((2 * i + (lane >> 4)) ^ ((row >> 1) & 3)) << 4), pack(v[0], v[1]), pack(v[2], v[3]), pack(v[4], v[5]), pack(v[6], v[7]));
  }
}
__device__ __forceinline__ void final_epilogue(const float* acc, const Params& prm, int m, int hh, int q, int tid) {
  uint32_t r[18];
#pragma unroll
  for (int i = 0; i < 16; i++) r[i] = pack(acc[2 * i] * 0.5f, acc[2 * i + 1] * 0.5f);
#pragma unroll
  for (int i = 0; i < 2; i++) {
    const int o = 32 + 4 * i;
    const float a0 = (q & 2) ? acc[o + 2] : acc[o], a1 = (q & 2) ? acc[o + 10] : acc[o + 8];
    const float b0 = (q & 2) ? acc[o + 3] : acc[o + 1], b1 = (q & 2) ? acc[o + 11] : acc[o + 9];
    r[16 + i] = pack(((q & 1) ? a1 : a0) * 0.5f, ((q & 1) ? b1 : b0) * 0.5f);
  }
  const size_t off = (size_t)(128 * m + (tid >> 5) * 16 + ((tid & 31) >> 2)) * DM + 2 * (tid & 3);
  const bool odd = tid & 1;
  uint32_t* o1 = reinterpret_cast<uint32_t*>(prm.out + off + 320 * hh + 64 * q) + (odd ? 3 : 0);
  uint32_t* o2 = reinterpret_cast<uint32_t*>(prm.out + off + 256 + 32 * hh + 16 * (q & 1) + (q >> 1) * 8 * DM) + (odd ? 3 : 0);
#pragma unroll
  for (int i = 0; i < 9; i++) {
    const uint32_t A = i < 8 ? r[4 * (i >> 1) + (i & 1)] : r[16], B = i < 8 ? r[4 * (i >> 1) + 2 + (i & 1)] : r[17];
    const uint32_t y = __shfl_xor_sync(0xffffffffu, odd ? A : B, 1);
    *reinterpret_cast<uint2*>(i < 8 ? o1 + 8 * (i >> 1) + (i & 1) * 8 * (DM / 2) : o2) = odd ? make_uint2(y, B) : make_uint2(A, y);
  }
}

__global__ void __launch_bounds__(384, 1) fused_kernel(const __grid_constant__ Params prm) {
  extern __shared__ __align__(1024) uint8_t smem[];
  const uint32_t sb = (uint32_t)__cvta_generic_to_shared(smem);
  const uint32_t bar = sb + SM_BAR;
  const int m = blockIdx.x & 15, j = blockIdx.x >> 4;
  const int cta = m * 8 + j;
  const int wr = __shfl_sync(0xffffffffu, (int)(threadIdx.x >> 5), 0);
  const int wg = wr >> 2;
  const int lane = threadIdx.x & 31;
  STAMP(0);
  if (wg == 2 && lane == 0) {
    if (wr == 8) {
      asm volatile("prefetch.tensormap [%0];" ::"l"(&prm.xm) : "memory");
#pragma unroll
      for (int c = 0; c < 9; c++) mbar_init(bar + 8 * (B_X + c), 1);
#pragma unroll
      for (int c = 0; c < 9; c++) mbar_expect(bar + 8 * (B_X + c), 16384);
      asm volatile("fence.proxy.async.shared::cta;" ::: "memory");
#pragma unroll
      for (int c = 0; c < 3; c++) tma2d(sb + SM_XN + c * 16384, &prm.xm, bar + 8 * (B_X + c), 64 * c, 128 * m);
    } else {
      if (wr == 9) {
#pragma unroll
        for (int i = 0; i < 8; i++) mbar_init(bar + 8 * (B_F + i), 2);
#pragma unroll
        for (int i = 0; i < 3; i++) mbar_init(bar + 8 * (B_QF + i), 1);
      } else if (wr == 10) {
#pragma unroll
        for (int i = 0; i < 8; i++) mbar_init(bar + 8 * (B_E + i), 8);
#pragma unroll
        for (int i = 0; i < 3; i++) mbar_init(bar + 8 * (B_QE + i), 8);
      } else {
#pragma unroll
        for (int i = B_SK1; i <= B_SP; i++) mbar_init(bar + 8 * i, 8);
        mbar_init(bar + 8 * B_OL, 1); mbar_init(bar + 8 * B_RX, 1);
        mbar_init(bar + 8 * B_NR, 4); mbar_init(bar + 8 * (B_NR + 1), 4);
        asm volatile("st.shared.u32 [%0], 0;" ::"r"(sb + SM_BAD) : "memory");
        if (sb & 1023) asm volatile("trap;");
      }
      asm volatile("fence.proxy.async.shared::cta;" ::: "memory");
    }
  }
  if (wr == 0) {
    const uint32_t one = (lane >> 3) == (lane & 3) ? ((lane & 4) ? 0x3f800000u : 0x00003f80u) : 0u;
    asm volatile("st.shared.v4.b32 [%0], {%1,%2,%2,%1};" ::"r"(sb + SM_ID + lane * 16), "r"(one), "r"(0) : "memory");
  }
  __syncthreads();

  if (wg == 2) {
    asm volatile("setmaxnreg.dec.sync.aligned.u32 24;");
    const int pw = wr & 3;
    const uint32_t epoch = *(volatile uint32_t*)FLAG_EPOCH(cta);
    const int hh = j & 1;
#define ACOL(A) (320 * hh + 64 * (((j >> 1) + 1 + (A)) & 3))
    if (pw == 0) {
      if (lane == 0) {
#pragma unroll
        for (int c = 3; c < 9; c++) tma2d(sb + SM_XN + c * 16384, &prm.xm, bar + 8 * (B_X + c), 64 * c, 128 * m);
        uint64_t pol;
        asm volatile("createpolicy.fractional.L2::evict_first.b64 %0, 1.0;" : "=l"(pol));
#pragma unroll 1
        for (int kb = 0; kb < 9; kb++) {
          const int s = kb % 3;
          if (kb >= 3) mbar_wait(bar + 8 * (B_QE + s), (kb / 3 - 1) & 1);
          const uint32_t fb = bar + 8 * (B_QF + s), dst = sb + SM_RING + s * QST;
          mbar_expect(fb, QST);
#pragma unroll
          for (int p = 0; p < 3; p++) {
            tma2d_h(dst + p * 8192, &prm.wqkv64, fb, 576 * p + 72 * j + 8 * hh, 64 * kb, pol);
            tma2d(dst + 24576 + p * 1024, &prm.wqkv8, fb, 576 * p + 72 * j + 64 - 64 * hh, 64 * kb);
          }
        }
        asm volatile("st.shared.u32 [%0], %1;" ::"r"(sb + SM_TAG), "r"((epoch + 1) & 1) : "memory");
        int col = 576 * j, kr = 0;
#pragma unroll 1
        for (int n = 0; n < N_G2; n++) {
          const uint32_t fb = bar + 8 * (B_F + (n & 7)), dst = sb + SM_RING + (n & 3) * BST;
          mbar_expect(fb, BST);
          if (n >= 4) mbar_wait(bar + 8 * (B_E + ((n - 3) & 7)), ((n - 3) >> 3) & 1);
          else if (n != 2) mbar_wait(bar + 8 * (B_QE + (n == 3 ? 2 : n)), 0);
          tma2d_h(dst, &prm.wg, fb, col, kr, pol);
          tma2d_h(dst + 8192, &prm.wu, fb, col, kr, pol);
          if ((kr += 64) == 576) { kr = 0; col += 64; }
        }
        uint32_t seen = 0;
#pragma unroll 1
        for (int b = 0; b < 26; b++) {
          const int n = N_G2 + 2 * b;
          const uint32_t fb = bar + 8 * (B_F + (n & 7)), dst = sb + (b & 3) * G2ST;
          const int own = b < 10 || b == 20 || b == 21, jj = own ? j : (j ^ 1), lb = b < 10 ? b : b < 20 ? b - 10 : 10 + (b & 1), need = (3 * lb + 6) >> 2;
          if (b < 24) {
            if (b == 10 || b == 20 || b == 22) seen = 0;
            if (seen < need) { seen = flag_wait_v(FLAG_H(m * 8 + jj), 9 * epoch + need) - 9 * epoch; fence_async(); }
          } else {
            flag_wait(FLAG_O((cta & ~1) + b - 24), epoch + 1);
            fence_async();
          }
          mbar_wait(bar + 8 * (B_E + ((n - 5) & 7)), ((n - 5) >> 3) & 1);
          if (b == 0) STAMPW(16);
          mbar_expect(fb, G2ST);
          if (b < 24) {
            bulk_g2s(dst, g_H + (m * 576 + 72 * jj + 6 * lb) * 512, 12288, fb);
#pragma unroll
            for (int a = 0; a < 4; a++) tma5d(dst + 12288 + a * 6144, &prm.wd[0], fb, ACOL(a), 36 * jj + 3 * lb);
            tma5d(dst + 36864, &prm.wd[1 + hh], fb, 0, 36 * jj + 3 * lb);
          } else {
            const int r = b - 24;
            bulk_g2s(dst, g_O + ((cta & ~1) + r) * 9 * 512 + r * 1024, 12288, fb);
#pragma unroll
            for (int a = 0; a < 4; a++) tma3d(dst + 12288 + a * 6144, &prm.wo3[0], fb, ACOL(a), 4 * (j & 6) + 5 * r);
            tma3d(dst + 36864, &prm.wo3[1 + hh], fb, 0, 4 * (j & 6) + 5 * r);
          }
          if (b == 0) STAMPW(17);
        }
        mbar_wait(bar + 8 * B_SP, 0);
        mbar_expect(bar + 8 * B_OL, 49152 + 32768);
        tma2d(sb + SM_RES, &prm.xm, bar + 8 * B_OL, ACOL(3), 128 * m);
        __nanosleep(200);
        tma2d(sb + SM_RES + 16384, &prm.xm, bar + 8 * B_OL, 256 + 32 * hh, 128 * m);
#pragma unroll 1
        for (int i = 0; i < 4; i++) {
          __nanosleep(200);
          tma3d(sb + SM_LB + i * 4096, &prm.wo2[0], bar + 8 * B_OL, ACOL(3), 8 * i + 3);
          tma3d(sb + SM_LB + 24576 + i * 4096, &prm.wo2[1 + hh], bar + 8 * B_OL, 0, 8 * i + 3);
          tma3d(sb + SM_LB + 16384 + i * 2048, &prm.wo16[0], bar + 8 * B_OL, ACOL(3), 8 * i);
          tma3d(sb + SM_LB + 40960 + i * 2048, &prm.wo16[1 + hh], bar + 8 * B_OL, 0, 8 * i);
        }
      }
    } else if (pw == 1) {
      if (lane == 0) {
        const int hx = hh * 3;
        int u = 0, kslot = 0, vrow = 0, kb = 0;
#pragma unroll 1
        for (int n = 0; n <= N_END; n++) {
          const uint32_t fb = bar + 8 * (B_F + (n & 7)), dst = sb + SM_KV + kslot * KVST;
          const bool att = n >= N_G2 || (n >= NG0 && kb != 0);
          if (++kb == 9) kb = 0;
          mbar_expect(fb, !att || u < 2 ? 0 : (u == 2 || u == 128) ? KVST / 2 : KVST);
          if (n >= N_AO || (n > N_G2 && !(n & 1))) mbar_expect(fb, 0);
          if (u == 2 && att) { flag_wait(FLAG_KV(0, j), 16 * epoch + 16); fence_async(); STAMPW(18); }
          if (n >= 4) mbar_wait(bar + 8 * (B_E + ((n - 3) & 7)), ((n - 3) >> 3) & 1);
          if (att) {
            const int krow = (4 * j + ((u >> 5) ^ hx)) * 256 + ((u + 2 * m) & 31) * 8;
            if (u >= 2 && u < 128) tma2d(dst, &prm.kv, fb, 0, krow);
            if (u >= 3) tma2d(dst + 3072, &prm.kv, fb, 128, vrow);
            vrow = krow; u++;
            if (++kslot == 3) kslot = 0;
            if (u == 16) { flag_wait(FLAG_KV(1, j), 16 * epoch + 16); fence_async(); }
          }
        }
      }
    } else if (pw == 2) {
      if (lane == 0) {
#pragma unroll 1
        for (int i = 1; i < 18; i++) asm volatile("prefetch.tensormap [%0];" ::"l"(&prm.xm + i) : "memory");
        mbar_wait(bar + 8 * B_SK1, 0);
        STAMPW(22);
        fence_gpu(); flag_add(FLAG_KV(0, j));
        STAMPW(20);
        mbar_wait(bar + 8 * B_SK2, 0);
        fence_gpu(); flag_add(FLAG_KV(1, j));
#pragma unroll 1
        for (int t = 0; t < 9; t++) { mbar_wait(bar + 8 * B_SH, t & 1); __nanosleep(1000); fence_gpu(); flag_add(FLAG_H(cta)); }
        mbar_wait(bar + 8 * B_SO1, 0);
        fence_gpu(); flag_add(FLAG_O(cta));
      }
    } else {
      mbar_wait(bar + 8 * (B_X + PF_Q), 0);
#pragma unroll 1
      for (int i = lane; i < 122; i += 32) pf_line(prm.pwqkv + (size_t)min(i * 128 + cta, 15551) * 64);
      mbar_wait(bar + 8 * (B_QE + PF_G1), 0);
#pragma unroll 1
      for (int t = -3; t < 9; t++) {
        if (t >= 0) { mbar_wait(bar + 8 * B_SH, t & 1); __nanosleep(1500); }
        if (t < 6) {
#pragma unroll 1
          for (int i = lane; i < 72; i += 32) pf_line((i >= 36 ? prm.pwu : prm.pwg) + (size_t)(36 * m + (i >= 36 ? i - 36 : i)) * FF + 576 * j + 64 * (t + 3));
        }
        if ((t == 2 || t == 6 || t == 8)) {
          const uint32_t* kv = g_KV + (size_t)(4 * j + ((t == 2 ? 1 : t == 6 ? 2 : 3) ^ (hh * 3))) * SEQ * 20 + m * 2560;
#pragma unroll 1
          for (int i = lane; i < 80; i += 32) pf_line(kv + i * 32);
        }
        if (t >= 5) {
#pragma unroll 1
          for (int i = lane; i < 81; i += 32) {
            const int l = (2 * m + hh) * 81 + i, r = l / 9;
            pf_line(prm.pwd + (size_t)(1152 * (j >> 1) + 576 * (r / 144) + 144 * (t - 5) + r % 144) * DM + 64 * (l % 9));
          }
        }
      }
      if (cta * 41 + lane < 5184) pf_line(prm.pwo + (size_t)(cta * 41 + lane) * 64);
      if (lane < 9 && cta * 41 + 32 + lane < 5184) pf_line(prm.pwo + (size_t)(cta * 41 + 32 + lane) * 64);
      if (lane == 0) {
      mbar_wait(bar + 8 * B_SP, 0);
      const int q = j >> 1;
#pragma unroll 1
      for (int i = 0; i < 14; i++) {
        bulk_s2g(g_P + cta * 3584 + i * 256, sb + SM_SEND + i * 4096, 4096);
        asm volatile("cp.async.bulk.commit_group;\ncp.async.bulk.wait_group.read 2;" ::: "memory");
      }
      asm volatile("cp.async.bulk.wait_group 0;" ::: "memory");
      fence_gpu();
      flag_add(FLAG_P(cta));
      STAMPW(15);
      mbar_expect(bar + 8 * B_RX, 73728);
#pragma unroll 1
      for (int a = 0; a < 3; a++) {
        const int src = m * 8 + 2 * ((q + 3 - a) & 3) + hh;
        flag_wait(FLAG_P(src), epoch + 1);
        fence_async();
        bulk_g2s(sb + SM_RECV + a * 24576, g_P + src * 3584 + a * 1024, 16384, bar + 8 * B_RX);
        bulk_g2s(sb + SM_RECV + a * 24576 + 16384, g_P + src * 3584 + 3072, 8192, bar + 8 * B_RX);
      }
      STAMPW(25);
      *FLAG_EPOCH(cta) = epoch + 1;
      }
    }
  } else {
    const int tid = threadIdx.x;
    const int t = lane & 3;
    const uint32_t l0 = lane == 0;
    const uint32_t adesc = (((sb + SM_XN + wg * 8192) & 0x3FFFF) >> 4) | LO_A;
    const uint32_t bdesc = (((sb + SM_RING) & 0x3FFFF) >> 4) | LO_B;
    const uint32_t kdesc0 = (((sb + SM_KV) & 0x3FFFF) >> 4) | LO_K;
    const int hx = (j & 1) * 3;
    float accA[64], accB[64];
    Att a;
    uint32_t gs = 0, s8 = 0;
#define G1_ISSUE(ACC, AD, BD) _Pragma("unroll") for (int k = 0; k < 4; k++) wg_ss_n128<HI_SW128, HI_SW128>(ACC, (AD) + k * 2, (BD) + k * 128);
#define G1_ISSUE_Z(ACC, BD)                                                                                    \
  wg_ss_z_n128<HI_SW128, HI_SW128>(ACC, adesc, BD);                                                            \
  _Pragma("unroll") for (int k = 1; k < 4; k++) wg_ss_n128<HI_SW128, HI_SW128>(ACC, adesc + k * 2, (BD) + k * 128);
#define F_BAR (bar + 8 * B_F + 8 * s8)
#define F_PH ((gs >> 3) & 1)
#define RELEASE() mbar_arrive_if(bar + 8 * B_E + 8 * s8, l0);
#define NEXT_SLOT() { gs++; s8 = s8 == 7 ? 0 : s8 + 1; }
#define G1_ONLY() { mbar_wait(F_BAR, F_PH); wg_fence(); G1_ISSUE(accA, adesc + gs * 1024, bdesc + (gs & 3) * 1024) wg_commit(); wg_wait<1>(); RELEASE() NEXT_SLOT() }
    {
      const int lr = wr * 16 + (lane & 15);
      uint32_t ra[4];
#pragma unroll
      for (int k = 0; k < 4; k++) ra[k] = sb + SM_XN + lr * 128 + (((2 * k + (lane >> 4)) ^ (lr & 7)) << 4);
      asm volatile("setmaxnreg.inc.sync.aligned.u32 240;");
      float aq[96], ar[12];
#pragma unroll
      for (int i = 0; i < 96; i++) aq[i] = __int_as_float(lane >> 5);
#pragma unroll
      for (int i = 0; i < 12; i++) ar[i] = __int_as_float(lane >> 5);
      pin<96>(aq); pin<12>(ar);
      float cs[2][4] = {}, q0 = 0.f, q1 = 0.f, q2 = 0.f, q3 = 0.f;
#pragma unroll 1
      for (int c = 0; c < 9; c++) {
        mbar_wait(bar + 8 * (B_X + c), 0);
        uint32_t v[4][4];
#pragma unroll
        for (int k = 0; k < 4; k++) ldsm4(v[k], ra[k] + c * 16384);
#pragma unroll
        for (int k = 0; k < 4; k++) {
          mma_ones(cs[k & 1], v[k]);
#pragma unroll
          for (int e = 0; e < 4; e += 2) {
            const float x0 = bf_lo(v[k][e]), x1 = bf_hi(v[k][e]), y0 = bf_lo(v[k][e + 1]), y1 = bf_hi(v[k][e + 1]);
            q0 = fmaf(x0, x0, q0); q1 = fmaf(x1, x1, q1); q2 = fmaf(y0, y0, q2); q3 = fmaf(y1, y1, q3);
          }
        }
      }
      STAMP(11);
      const float mean0 = (cs[0][0] + cs[1][0]) * (1.f / 576.f), mean1 = (cs[0][2] + cs[1][2]) * (1.f / 576.f);
      q0 += q1; q2 += q3;
      q0 += __shfl_xor_sync(0xffffffffu, q0, 1); q2 += __shfl_xor_sync(0xffffffffu, q2, 1);
      q0 += __shfl_xor_sync(0xffffffffu, q0, 2); q2 += __shfl_xor_sync(0xffffffffu, q2, 2);
      float var0 = fmaf(q0, 1.f / 576.f, -mean0 * mean0), var1 = fmaf(q2, 1.f / 576.f, -mean1 * mean1);
      if (__any_sync(0xffffffffu, !(mean0 * mean0 <= 8.f * var0) || !(mean1 * mean1 <= 8.f * var1))) {
        q0 = q2 = 0.f;
#pragma unroll 1
        for (int i = 0; i < 36; i++) {
          uint32_t v[4];
          ldsm4(v, ((ra[0] + (i >> 2) * 16384) ^ ((i & 3) << 5)));
#pragma unroll
          for (int e = 0; e < 4; e += 2) {
            const float x0 = bf_lo(v[e]) - mean0, x1 = bf_hi(v[e]) - mean0, y0 = bf_lo(v[e + 1]) - mean1, y1 = bf_hi(v[e + 1]) - mean1;
            q0 = fmaf(x0, x0, fmaf(x1, x1, q0)); q2 = fmaf(y0, y0, fmaf(y1, y1, q2));
          }
        }
        q0 += __shfl_xor_sync(0xffffffffu, q0, 1); q2 += __shfl_xor_sync(0xffffffffu, q2, 1);
        q0 += __shfl_xor_sync(0xffffffffu, q0, 2); q2 += __shfl_xor_sync(0xffffffffu, q2, 2);
        var0 = q0 * (1.f / 576.f); var1 = q2 * (1.f / 576.f);
      }
      const float inv0 = rcp_fast(bf_round(sqrt_fast(bf_round(bf_round(var0) + 1e-5f)))), inv1 = rcp_fast(bf_round(sqrt_fast(bf_round(bf_round(var1) + 1e-5f))));
      const uint32_t mb0 = pack(mean0, mean0), mb1 = pack(mean1, mean1);
      const uint32_t h0 = pack(inv0, inv0), h1 = pack(inv1, inv1);
      const uint32_t e0 = pack(inv0 - bf_lo(h0), inv0 - bf_lo(h0)), e1 = pack(inv1 - bf_lo(h1), inv1 - bf_lo(h1));
      uint32_t v[4][4], xn[4][4];
#pragma unroll
      for (int k = 0; k < 4; k++) ldsm4(v[k], ra[k]);
      STAMP(1);
      const uint32_t rdesc = (((sb + SM_RING + 24576) & 0x3FFFF) >> 4) | LO_R;
      uint32_t s = 0, ph = 0;
#pragma unroll 1
      for (int kb = 0; kb < 9; kb++) {
#pragma unroll
        for (int k = 0; k < 4; k++) {
          xn[k][0] = bscale2(bsub2(v[k][0], mb0), h0, e0); xn[k][1] = bscale2(bsub2(v[k][1], mb1), h1, e1);
          xn[k][2] = bscale2(bsub2(v[k][2], mb0), h0, e0); xn[k][3] = bscale2(bsub2(v[k][3], mb1), h1, e1);
        }
        pin<16>(&xn[0][0]);
        mbar_wait(bar + 8 * B_QF + 8 * s, ph);
        wg_fence();
#pragma unroll
        for (int k = 0; k < 4; k++) {
          wg_rs_n192<HI_SW128>(aq, xn[k][0], xn[k][1], xn[k][2], xn[k][3], bdesc + s * (QST >> 4) + k * 128);
          wg_rs_n24<HI_R>(ar, xn[k][0], xn[k][1], xn[k][2], xn[k][3], rdesc + s * (QST >> 4) + k * 16);
        }
        wg_commit();
#pragma unroll
        for (int k = 0; k < 4; k++) stsm4(ra[k] + kb * 16384, xn[k][0], xn[k][1], xn[k][2], xn[k][3]);
#pragma unroll
        for (int k = 0; k < 4; k++) ldsm4(v[k], ra[k] + (kb < 8 ? kb + 1 : 8) * 16384);
        if (kb == 8) {
          asm volatile("fence.proxy.async.shared::cta;" ::: "memory");
          __syncwarp();
          mbar_arrive_if(bar + 8 * B_NR + 8 * wg, l0);
        }
        wg_wait<0>();
        mbar_arrive_if(bar + 8 * B_QE + 8 * s, l0);
        if (++s == 3) { s = 0; ph ^= 1; }
      }
      pin<96>(aq); pin<12>(ar);
      STAMP(2);
      uint32_t* kvp = g_KV + (size_t)(4 * j) * SEQ * 20 + (16 * m + 2 * wr) * 160 + lane;
      uint32_t pk[2][9][2];
#pragma unroll
      for (int p = 0; p < 2; p++)
#pragma unroll
        for (int i = 0; i < 9; i++) {
          const float* src = i < 8 ? &aq[(8 * (p + 1) + i) * 4] : &ar[4 * (p + 1)];
          pk[p][i][0] = pack(src[0], src[1]); pk[p][i][1] = pack(src[2], src[3]);
        }
      const uint32_t sk = sb + SM_KV + wg * KVST + (wr & 3) * 768 + lane * 4;
      mbar_wait(bar + 8 * (B_QE + 2), 0);
      if (hx) {
#pragma unroll
        for (int p = 0; p < 2; p++) { rotate9(pk[p]); }
        store_kv_head<3>(pk, kvp, lane, sk, sk + KVST + 3072);
      } else store_kv_head<0>(pk, kvp, lane, sk, sk + KVST + 3072);
      asm volatile("fence.proxy.async.shared::cta;" ::: "memory");
      __syncwarp();
      mbar_arrive_if(bar + 8 * B_SK1, l0);
      mbar_arrive_if(bar + 8 * B_LK, l0);
      STAMP(3);
      mbar_wait(bar + 8 * B_NR + 8 * wg, 0);
      mbar_wait(bar + 8 * B_F, 0);
      wg_fence();
      G1_ISSUE_Z(accA, bdesc)
      wg_commit();
      RELEASE()
      NEXT_SLOT()
      mbar_wait(F_BAR, F_PH);
      wg_fence();
      G1_ISSUE(accA, adesc + 1024, bdesc + 1024)
      wg_commit();
      uint32_t pq[9][2];
#pragma unroll
      for (int i = 0; i < 9; i++) {
        const float* src = i < 8 ? &aq[i * 4] : &ar[0];
        pq[i][0] = bscale2(pack(src[0], src[1]), QS_HI, QS_LO); pq[i][1] = bscale2(pack(src[2], src[3]), QS_HI, QS_LO);
      }
      if (hx) rotate9(pq);
      pin<18>(&pq[0][0]);
      wg_wait<1>();
      RELEASE()
      NEXT_SLOT()
      G1_ONLY()
      mbar_wait(F_BAR, F_PH);
      wg_fence();
      G1_ISSUE(accA, adesc + 3 * 1024, bdesc + 3 * 1024)
      wg_commit();
      if (hx) store_kv_head<0>(pk, kvp, lane); else store_kv_head<3>(pk, kvp, lane);
      store_kv_head<1>(pk, kvp, lane);
      store_kv_head<2>(pk, kvp, lane);
      __syncwarp();
      mbar_arrive_if(bar + 8 * B_SK2, l0);
      wg_wait<1>();
      RELEASE()
      NEXT_SLOT()
      mbar_wait(F_BAR, F_PH);
      wg_fence();
      G1_ISSUE(accA, adesc + 4 * 1024, bdesc)
      wg_commit();
      uint4* qp = reinterpret_cast<uint4*>(g_Q) + cta * 4 * 512 + tid;
#pragma unroll
      for (int hp = 0; hp < 4; hp++) {
        const bool up = t < hp;
        const uint4 u = make_uint4(up ? pq[2 * hp + 1][0] : pq[2 * hp][0], up ? pq[2 * hp + 1][1] : pq[2 * hp][1],
                                   up ? pq[2 * hp + 2][0] : pq[2 * hp + 1][0], up ? pq[2 * hp + 2][1] : pq[2 * hp + 1][1]);
        const uint4 v = make_uint4(t == hp ? pq[2 * hp + 2][0] : 0u, t == hp ? pq[2 * hp + 2][1] : 0u, 0u, 0u);
        qp[hp * 512] = u; qp[hp * 512 + 256] = v;
        if (hp == 0 || (hp == 3 && hx)) { a.q[0] = u.x; a.q[1] = u.y; a.q[2] = u.z; a.q[3] = u.w; a.q[4] = v.x; a.q[5] = v.y; }
      }
      a.q[6] = __shfl_sync(0xffffffffu, lane, 0); a.q[7] = __shfl_sync(0xffffffffu, lane >> 1, 1);
#pragma unroll
      for (int i = 0; i < 16; i++) a.p[i] = 0;
#pragma unroll
      for (int i = 0; i < 12; i++) a.o[i] = 0.f;
      pin<16>(a.p); pin<12>(a.o); pin<8>(a.q);
      wg_wait<1>();
      RELEASE()
      NEXT_SLOT()
    }
    static_assert(NG0 == 5 || NG0 == 7, "item boundaries must fall into even F tiles / even GEMM2 slots");
#pragma unroll 1
    while (gs < NG0) G1_ONLY()
    STAMP(4);
    mbar_wait(bar + 8 * B_LK, 0);
    mbar_wait(F_BAR, F_PH);
    STAMP(23);
    uint32_t kd = kdesc0;
    uint32_t it = 0;
    uint32_t ox0 = 0, ox1 = 0;
    bool special = true;
    uint32_t qn[6] = {0, 0, 0, 0, 0, 0};
    uint32_t* hdst = g_H + ((m * 576 + 72 * j + (t >> 1)) * 128 + 16 * wr + (lane >> 2)) * 4 + 2 * (t & 1);
    uint32_t ad = adesc + NG0 * 1024, bd = bdesc + (gs & 3) * 1024;

#define ITEM_FIRST()                                                                                           \
  {                                                                                                            \
    pin<12>(a.o);                                                                                              \
    if (it != 0) {                                                                                             \
      uint32_t w[4];                                                                                           \
      o_normalise(a.o, w, ox0, ox1, ((it >> 5) - 1) ^ hx, lane, sb + SM_BAD, wr);                              \
      uint32_t* d = g_O + cta * 9 * 512 + (((it >> 5) - 1) ^ hx) * 1024 + wr * 64 + lane;                      \
      d[0] = w[0]; d[32] = w[1]; d[512] = w[2]; d[544] = w[3];                                                 \
    }                                                                                                          \
    if (it == 96) mbar_arrive_if(bar + 8 * B_SO1, l0 & (bad_heads(sb + SM_BAD, wr) == 0));                     \
    first_tile(a, (it >> 5) ^ hx, lane);                                                                       \
  }
#define ITEM_NEXTQ() { if (it & 2) { _Pragma("unroll") for (int i = 0; i < 6; i++) a.q[i] = qn[i]; } else fetch_q(qn, cta, ((it >> 5) + 1) ^ hx, tid); }
#define KV_ADVANCE() { kd = kd == kdesc0 + 768 ? kdesc0 : kd + 384; }
#define SOFTMAX_NEXT() { softmax_a(a); softmax_b(a); mbar_wait(F_BAR, F_PH); softmax_c(a); }
#define EPI_STEP(ACCN, ACCO)                                                                                   \
  {                                                                                                            \
    wg_fence();                                                                                                \
    G1_ISSUE_Z(ACCN, bd)                                                                                       \
    wg_commit();                                                                                               \
    wg_wait<1>();                                                                                              \
    pin<64>(ACCO);                                                                                             \
    RELEASE()                                                                                                  \
    NEXT_SLOT()                                                                                                \
    ad = adesc + 1024; bd = bdesc + (gs & 3) * 1024;                                                           \
    const uint32_t ok = mbar_test(F_BAR, F_PH);                                                                \
    h_epilogue(ACCO, hdst);                                                                                    \
    hdst += 4096;                                                                                              \
    __syncwarp();                                                                                              \
    mbar_arrive_if(bar + 8 * B_SH, l0);                                                                        \
    if (__builtin_expect(!ok, 0)) mbar_wait(F_BAR, F_PH);                                                                                            \
  }
#define ATT_LOOP1(ACC, ITEMS)                                                                                  \
  do {                                                                                                         \
    wg_fence();                                                                                                \
    issue_att(a, kd);                                                                                          \
    wg_commit();                                                                                               \
    G1_ISSUE(ACC, ad, bd)                                                                                      \
    wg_commit();                                                                                               \
    wg_wait<1>();                                                                                              \
    pin<32>(a.s);                                                                                              \
    RELEASE()                                                                                                  \
    TRACE()                                                                                                    \
    if (ITEMS) { if (__builtin_expect(special, 0)) { if (it & 1) ITEM_NEXTQ() else { if (it == 64) fetch_q(qn, cta, 3 ^ hx, tid); ITEM_FIRST() } } } \
    NEXT_SLOT() it++;                                                                                                \
    if (ITEMS) special = (0xA0000001u >> (it & 31)) & 1;                                                                  \
    KV_ADVANCE()                                                                                               \
    ad += 1024; bd = bdesc + (gs & 3) * 1024;                                                                  \
    SOFTMAX_NEXT()                                                                                             \
    pin<8>(a.q);                                                                                               \
  } while (ad != adesc + 9 * 1024);
#pragma unroll 1
    for (int pr = 0;; pr++) {
      ATT_LOOP1(accA, true)
      if (pr == 4) break;
      if (pr == 2) STAMP(29);
      EPI_STEP(accB, accA)
      if (pr == 2) STAMP(30);
      ATT_LOOP1(accB, false)
      if (pr == 2) STAMP(31);
      EPI_STEP(accA, accB)
      special = false;
      if (pr == 2) STAMP(21);
      if (pr == 3) STAMP(14);
    }
    STAMP(5);
    wg_wait<0>();
    pin<64>(accA);
    h_epilogue(accA, hdst);
    __syncwarp();
    mbar_arrive_if(bar + 8 * B_SH, l0);
    mbar_wait(bar + 8 * B_E, 0);
    asm volatile("st.shared.v4.b32 [%0], {%1,%2,%3,%4};\nst.shared.v2.b32 [%5], {%6,%7};" ::"r"(sb + SM_QS + tid * 16), "r"(qn[0]), "r"(qn[1]), "r"(qn[2]), "r"(qn[3]),
                 "r"(sb + SM_QS + 4096 + tid * 8), "r"(qn[4]), "r"(qn[5]) : "memory");
    STAMP(6);
    STAMP(12);

    float acc2[144];
    const uint32_t a2desc = (((sb + wg * 1024) & 0x3FFFF) >> 4) | LO_O;
    const uint32_t b2desc = (((sb + 12288) & 0x3FFFF) >> 4) | LO_B48;
    ad = a2desc; bd = b2desc;
#define G2_LO(K) wg_ss_n128<HI_O, HI_SW128>(acc2, ad + (K) * 256, bd + (K) * 128);
#define G2_HI(K) wg_ss_n160<HI_O, HI_SW128>(acc2 + 64, ad + (K) * 256, bd + (K) * 128 + 768);
#define ATT_PAIR(ZERO)                                                                                         \
  {                                                                                                            \
    wg_fence();                                                                                                \
    issue_att(a, kd);                                                                                          \
    wg_commit();                                                                                               \
    if (ZERO) { wg_ss_z_n128<HI_O, HI_SW128>(acc2, ad, bd); wg_ss_z_n160<HI_O, HI_SW128>(acc2 + 64, ad, bd + 768); } \
    else { G2_LO(0) G2_HI(0) }                                                                                 \
    G2_LO(1)                                                                                                   \
    wg_commit();                                                                                               \
    wg_wait<1>();                                                                                              \
    pin<32>(a.s);                                                                                              \
    RELEASE()                                                                                                  \
    TRACE()                                                                                                    \
    if (!(ZERO)) { if (__builtin_expect(gs == N_G2 + 96 - IT_G2, 0)) ITEM_FIRST() }                                    \
    NEXT_SLOT() it++;                                                                                                \
    KV_ADVANCE()                                                                                               \
    SOFTMAX_NEXT()                                                                                             \
    pin<8>(a.q);                                                                                               \
    wg_fence();                                                                                                \
    issue_att(a, kd);                                                                                          \
    wg_commit();                                                                                               \
    G2_HI(1) G2_LO(2) G2_HI(2)                                                                                 \
    wg_commit();                                                                                               \
    wg_wait<1>();                                                                                              \
    pin<32>(a.s);                                                                                              \
    RELEASE()                                                                                                  \
    TRACE()                                                                                                    \
    if (!(ZERO) && __builtin_expect(gs == N_G2 + 95 - IT_G2, 0)) {                                                     \
      const int ft = fresh_tid();                                                                              \
      asm volatile("ld.shared.v4.b32 {%0,%1,%2,%3}, [%6];\nld.shared.v2.b32 {%4,%5}, [%7];" : "=r"(a.q[0]), "=r"(a.q[1]), "=r"(a.q[2]), "=r"(a.q[3]), \
                   "=r"(a.q[4]), "=r"(a.q[5]) : "r"(sb + SM_QS + ft * 16), "r"(sb + SM_QS + 4096 + ft * 8) : "memory"); \
    }                                                                                                          \
    NEXT_SLOT() it++;                                                                                                \
    KV_ADVANCE()                                                                                               \
    ad = a2desc + (((gs - N_G2) >> 1) & 3) * 2688; bd = ad + (b2desc - a2desc);                                \
    SOFTMAX_NEXT()                                                                                             \
    pin<8>(a.q);                                                                                               \
  }
    ATT_PAIR(true)
#pragma unroll 1
    for (int half = 0; half < 2; half++) {
      const uint32_t stop = half ? N_AO : N_G2 + 46;
      do ATT_PAIR(false) while (gs != stop);
      if (!half) {
        const uint32_t bad = bad_heads(sb + SM_BAD, wr);
        if (bad) { repair_rows(cta, wr, bad, 3 ^ hx, false); mbar_arrive_if(bar + 8 * B_SO1, l0); }
      }
    }
    STAMP(13);
    wg_wait<0>();
    pin<144>(acc2);
    mbar_wait(bar + 8 * (B_E + 1), 0);
    stage_partials(acc2, sb + SM_SEND, fresh_tid());
    asm volatile("fence.proxy.async.shared::cta;" ::: "memory");
    __syncwarp();
    mbar_arrive_if(bar + 8 * B_SP, l0);
    do {
      wg_fence();
      issue_att(a, kd);
      wg_commit();
      wg_wait<0>();
      pin<32>(a.s);
      RELEASE()
      TRACE()
      NEXT_SLOT() it++;
      KV_ADVANCE()
      SOFTMAX_NEXT()
    } while (gs != N_END);
    STAMP(7);
    wg_fence();
    issue_pv(a, kd);
    wg_commit();
    int tid2, bid2;
    asm volatile("mov.u32 %0, %%tid.x;" : "=r"(tid2));
    asm volatile("mov.u32 %0, %%ctaid.x;" : "=r"(bid2));
    const int m2 = bid2 & 15, j2 = bid2 >> 4;
    uint32_t tag;
    asm volatile("ld.shared.u32 %0, [%1];" : "=r"(tag) : "r"(sb + SM_TAG) : "memory");
    wg_wait<0>();
    pin<12>(a.o);
    {
      uint32_t w[4];
      o_normalise(a.o, w, ox0, ox1, 3 ^ hx, lane, sb + SM_BAD, wr);
      ox0 = __shfl_xor_sync(0xffffffffu, ox0, 2); ox1 = __shfl_xor_sync(0xffffffffu, ox1, 2);
      const uint32_t bad = bad_heads(sb + SM_BAD, wr);
      if (bad) {
        uint32_t* d = g_O + cta * 9 * 512 + wr * 64 + lane;
        uint32_t* h = d + (3 ^ hx) * 1024;
        h[0] = w[0]; h[32] = w[1]; h[512] = w[2]; h[544] = w[3]; d[4096] = ox0; d[4128] = ox1;
        __syncwarp();
        repair_rows(cta, wr, bad, 3 ^ hx, true);
        w[0] = __ldcg(h); w[1] = __ldcg(h + 32); w[2] = __ldcg(h + 512); w[3] = __ldcg(h + 544); ox0 = __ldcg(d + 4096); ox1 = __ldcg(d + 4128);
      }
      asm volatile("st.relaxed.gpu.global.v4.b32 [%0], {%1,%2,%3,%4};" ::"l"(g_L + (m2 * 8 + j2) * 384 + tid2), "r"((w[0] & ~1u) | tag), "r"((w[1] & ~1u) | tag),
                   "r"((w[2] & ~1u) | tag), "r"((w[3] & ~1u) | tag) : "memory");
      asm volatile("st.relaxed.gpu.global.v2.b32 [%0], {%1,%2};" ::"l"(reinterpret_cast<uint2*>(g_L + (m2 * 8 + j2) * 384 + 256) + tid2), "r"((ox0 & ~1u) | tag),
                   "r"((ox1 & ~1u) | tag) : "memory");
    }
    STAMP(8);
    uint32_t la[48];
    const uint4* p4 = g_L + m2 * 8 * 384 + tid2;
    const uint2* p2 = reinterpret_cast<const uint2*>(g_L + m2 * 8 * 384 + 256) + tid2;
#define LOAD_LA2() { ld2<0>(la + 32, p2); ld2<6144>(la + 34, p2); ld2<12288>(la + 36, p2); ld2<18432>(la + 38, p2); \
                     ld2<24576>(la + 40, p2); ld2<30720>(la + 42, p2); ld2<36864>(la + 44, p2); ld2<43008>(la + 46, p2); }
#define LOAD_LA4() { ld4<0>(la, p4); ld4<6144>(la + 4, p4); ld4<12288>(la + 8, p4); ld4<18432>(la + 12, p4); \
                     ld4<24576>(la + 16, p4); ld4<30720>(la + 20, p4); ld4<36864>(la + 24, p4); ld4<43008>(la + 28, p4); }
    float fin[48];
    uint32_t id[4][4];
    {
      uint32_t id2[4][4];
#pragma unroll
      for (int k = 0; k < 4; k++) {
        asm volatile("ld.volatile.shared.v4.b32 {%0,%1,%2,%3}, [%4];" : "=r"(id[k][0]), "=r"(id[k][1]), "=r"(id[k][2]), "=r"(id[k][3])
                     : "r"(sb + SM_ID + ((wr & 3) == k ? lane : 1) * 16) : "memory");
#pragma unroll
        for (int e = 0; e < 4; e++) id2[k][e] = id[k][e] + (id[k][e] & 0x00800080u);
      }
      pin<16>(&id[0][0]); pin<16>(&id2[0][0]);
      const uint32_t xdesc = (((sb + SM_RES + wg * 8192) & 0x3FFFF) >> 4) | LO_B;
      STAMP(26);
      mbar_wait(bar + 8 * B_OL, 0);
      STAMP(27);
      wg_fence();
      wg_rsb_z_n64<HI_SW128>(fin, id2[0][0], id2[0][1], id2[0][2], id2[0][3], xdesc);
      wg_rs_z_n32<HI_SW128>(fin + 32, id2[0][0], id2[0][1], id2[0][2], id2[0][3], xdesc + 1024);
#pragma unroll
      for (int k = 1; k < 4; k++) {
        wg_rsb_n64<HI_SW128>(fin, id2[k][0], id2[k][1], id2[k][2], id2[k][3], xdesc + k * 128);
        wg_rs_n32<HI_SW128>(fin + 32, id2[k][0], id2[k][1], id2[k][2], id2[k][3], xdesc + 1024 + k * 128);
      }
      wg_commit();
      wg_wait<0>();
      pin<48>(fin);
#pragma unroll
      for (int i = 0; i < 48; i++) fin[i] += acc2[96 + i];
      pin<48>(fin);
    }
    STAMP(28);
    const uint32_t pdesc = (((sb + SM_RECV + wg * 8192) & 0x3FFFF) >> 4) | LO_B, hdesc = (((sb + SM_RECV + 16384 + wg * 4096) & 0x3FFFF) >> 4) | LO_B;
#define RX_MMAS()                                                                                              \
  wg_fence();                                                                                                  \
  _Pragma("unroll") for (int a3 = 0; a3 < 3; a3++)                                                             \
    _Pragma("unroll") for (int k = 0; k < 4; k++) {                                                            \
      wg_rsb_n64<HI_SW128>(fin, id[k][0], id[k][1], id[k][2], id[k][3], pdesc + a3 * 1536 + k * 128);          \
      wg_rs_n32<HI_SW64>(fin + 32, id[k][0], id[k][1], id[k][2], id[k][3], hdesc + a3 * 1536 + k * 64);        \
    }                                                                                                          \
  wg_commit();
    for (uint32_t tries = 0; tries < 0x400000u; tries++) {
      const uint32_t* pw = reinterpret_cast<const uint32_t*>(g_L + (m2 * 8 + (lane & 7)) * 384 + 256) + (tid2 | 31) * 2 + 1;
      uint32_t bad;
      do {
        asm volatile("ld.relaxed.gpu.global.b32 %0, [%1];" : "=r"(bad) : "l"(pw) : "memory");
      } while (!__all_sync(0xffffffffu, !((bad ^ tag) & 1)) && ++tries < 0x400000u);
      LOAD_LA4()
      LOAD_LA2()
      bad = 0;
#pragma unroll
      for (int i = 0; i < 48; i++) bad |= la[i] ^ tag;
      if (__all_sync(0xffffffffu, !(bad & 1))) break;
    }
#pragma unroll
    for (int i = 0; i < 48; i++) la[i] ^= tag;
    pin<48>(la);
    STAMP(19);
    const uint32_t ldesc = (((sb + SM_LB) & 0x3FFFF) >> 4) | LO_B;
    wg_fence();
#pragma unroll
    for (int k = 0; k < 12; k++) {
      wg_rsb_n64<HI_SW128>(fin, la[4 * k], la[4 * k + 1], la[4 * k + 2], la[4 * k + 3], ldesc + k * 128);
      wg_rs_n32<HI_SW128>(fin + 32, la[4 * k], la[4 * k + 1], la[4 * k + 2], la[4 * k + 3], ldesc + 1536 + k * 128);
    }
    wg_commit();
    mbar_wait(bar + 8 * B_RX, 0);
    STAMP(24);
    RX_MMAS()
    wg_wait<0>();
    pin<48>(fin);
    STAMP(9);
    final_epilogue(fin, prm, m2, j2 & 1, j2 >> 1, tid2);
    STAMP(10);
  }
}

typedef CUresult (*EncodeFn)(CUtensorMap*, CUtensorMapDataType, cuuint32_t, void*, const cuuint64_t*, const cuuint64_t*, const cuuint32_t*, const cuuint32_t*,
                             CUtensorMapInterleave, CUtensorMapSwizzle, CUtensorMapL2promotion, CUtensorMapFloatOOBfill);

void enc2d(EncodeFn enc, CUtensorMap* tm, const void* base, uint64_t w, uint64_t h, uint64_t pitch_elems, uint32_t bw, uint32_t bh, CUtensorMapSwizzle sw) {
  cuuint64_t dims[2] = {w, h}, str[1] = {pitch_elems * 2};
  cuuint32_t box[2] = {bw, bh}, es[2] = {1, 1};
  enc(tm, CU_TENSOR_MAP_DATA_TYPE_BFLOAT16, 2, const_cast<void*>(base), dims, str, box, es, CU_TENSOR_MAP_INTERLEAVE_NONE, sw,
      CU_TENSOR_MAP_L2_PROMOTION_L2_128B, CU_TENSOR_MAP_FLOAT_OOB_FILL_NONE);
}

}

extern "C" void kernel_launch(void* const* d_in, const int* in_sizes, int n_in, void* d_out, int out_size) {
  (void)in_sizes; (void)n_in; (void)out_size;
  const __nv_bfloat16* x = (const __nv_bfloat16*)d_in[0];
  const __nv_bfloat16* wqkv = (const __nv_bfloat16*)d_in[1];
  const __nv_bfloat16* wo = (const __nv_bfloat16*)d_in[2];
  const __nv_bfloat16* wg = (const __nv_bfloat16*)d_in[4];
  const __nv_bfloat16* wu = (const __nv_bfloat16*)d_in[5];
  const __nv_bfloat16* wd = (const __nv_bfloat16*)d_in[6];
  void* fn = nullptr;
  cudaDriverEntryPointQueryResult qr;
  cudaGetDriverEntryPoint("cuTensorMapEncodeTiled", &fn, cudaEnableDefault, &qr);
  EncodeFn enc = (EncodeFn)fn;
  void* kvp = nullptr;
  cudaGetSymbolAddress(&kvp, g_KV);
  Params p;
  enc2d(enc, &p.xm, x, DM, SEQ, DM, 64, 128, CU_TENSOR_MAP_SWIZZLE_128B);
  enc2d(enc, &p.kv, kvp, 320, 32 * 256, 320, 192, 8, CU_TENSOR_MAP_SWIZZLE_NONE);
  enc2d(enc, &p.wqkv64, wqkv, 3 * DM, DM, 3 * DM, 64, 64, CU_TENSOR_MAP_SWIZZLE_128B);
  enc2d(enc, &p.wqkv8, wqkv, 3 * DM, DM, 3 * DM, 8, 64, CU_TENSOR_MAP_SWIZZLE_NONE);
  enc2d(enc, &p.wg, wg, FF, DM, FF, 64, 64, CU_TENSOR_MAP_SWIZZLE_128B);
  enc2d(enc, &p.wu, wu, FF, DM, FF, 64, 64, CU_TENSOR_MAP_SWIZZLE_128B);
  for (int v = 0; v < 3; v++) {
    const cuuint64_t wdt = v ? 32 : DM;
    const int c0 = v ? 256 + 32 * (v - 1) : 0;
    for (int e = 0; e < 3; e++) {
      cuuint64_t d3[3] = {wdt, e == 2 ? 2u : 16u, 32}, s3[2] = {DM * 2, 18 * DM * 2};
      cuuint32_t b3[3] = {64, e == 2 ? 2u : 16u, e == 0 ? 3u : e == 1 ? 2u : 8u}, e3[3] = {1, 1, 1};
      enc(e == 0 ? &p.wo3[v] : e == 1 ? &p.wo2[v] : &p.wo16[v], CU_TENSOR_MAP_DATA_TYPE_BFLOAT16, 3, (void*)(wo + c0 + (e == 2 ? 16 * DM : 0)), d3, s3, b3, e3,
          CU_TENSOR_MAP_INTERLEAVE_NONE, CU_TENSOR_MAP_SWIZZLE_128B, CU_TENSOR_MAP_L2_PROMOTION_L2_128B, CU_TENSOR_MAP_FLOAT_OOB_FILL_NONE);
    }
    cuuint64_t dims[5] = {wdt, 2, 2, 4, FF / 16}, str[4] = {DM * 2, 8 * DM * 2, 2 * DM * 2, 16 * DM * 2};
    cuuint32_t box[5] = {64, 2, 2, 4, 3}, es[5] = {1, 1, 1, 1, 1};
    enc(&p.wd[v], CU_TENSOR_MAP_DATA_TYPE_BFLOAT16, 5, (void*)(wd + c0), dims, str, box, es, CU_TENSOR_MAP_INTERLEAVE_NONE,
        CU_TENSOR_MAP_SWIZZLE_128B, CU_TENSOR_MAP_L2_PROMOTION_L2_128B, CU_TENSOR_MAP_FLOAT_OOB_FILL_NONE);
  }
  p.x = x; p.pwqkv = wqkv; p.pwo = wo; p.pwg = wg; p.pwu = wu; p.pwd = wd;
  p.out = (__nv_bfloat16*)d_out;
  cudaFuncSetAttribute(fused_kernel, cudaFuncAttributeMaxDynamicSharedMemorySize, SM_TOTAL);
  fused_kernel<<<NCTA, 384, SM_TOTAL, cudaStreamPerThread>>>(p);
}
```

```cpp
#include <cuda_runtime.h>
#include <cuda.h>
#include <cuda_bf16.h>
#include <stdint.h>

namespace {

constexpr int SEQ = 2048, DM = 576, FF = 4608;
constexpr int NCTA = 128;

constexpr uint32_t SM_XN = 0;
constexpr uint32_t SM_RING = 147456;
constexpr uint32_t SM_KV = 212992;
constexpr uint32_t QST = 27648, BST = 16384, KVST = 6144;
constexpr uint32_t G2ST = 43008;
constexpr uint32_t SM_LB = 0, SM_RES = 49152, SM_SEND = 86016, SM_RECV = SM_SEND;
constexpr uint32_t SM_QS = 204800;
constexpr uint32_t SM_ID = 231424;
constexpr uint32_t SM_BAR = 231936;
constexpr uint32_t SM_TAG = 232436;
constexpr uint32_t SM_BAD = 232432;
constexpr uint32_t SM_TOTAL = 232448;
enum { B_F = 0, B_E = 8, B_QF = 16, B_QE = 19, B_SK1 = 22, B_SK2 = 23, B_SH = 24, B_SO1 = 25, B_LK = 26, B_SP = 27, B_OL = 28, B_RX = 29, B_NR = 30, B_X = 32, B_N = 41 };
constexpr int N_G2 = 81, N_AO = 133;
#define N_END (136 + NG0)
#define IT_G2 (73 - NG0)
#define SM_A 7
#define SM_B 12
#define CONST_SB 1
#define PF_Q 6
constexpr int PF_G1 = 1;
#define NG0_ 5
constexpr int NG0 = NG0_;

constexpr uint32_t HI_SW128 = 0x40000040u;
constexpr uint32_t LO_A = 1u << 16;
constexpr uint32_t LO_B = 512u << 16;
constexpr uint32_t HI_R = 64u, LO_R = 8u << 16;
constexpr uint32_t HI_K = 24u, LO_K = 8u << 16;
constexpr uint32_t HI_V = 8u, LO_V = 24u << 16;
constexpr uint32_t LO_B48 = 384u << 16;
constexpr uint32_t HI_O = 8u, LO_O = 128u << 16;
constexpr uint32_t HI_SW64 = 0x80000020u;

constexpr uint32_t QS_HI = 0x3eae3eaeu, QS_LO = 0x39553955u;
constexpr float MOFF = 90.f;

struct __align__(64) Params {
  CUtensorMap xm, wqkv64, wqkv8, wg, wu, kv, wd[3], wo3[3], wo2[3], wo16[3];
  const __nv_bfloat16 *x, *pwqkv, *pwo, *pwg, *pwu, *pwd;
  __nv_bfloat16* out;
};

__device__ __align__(1024) uint32_t g_H[16 * 576 * 512];
__device__ __align__(1024) uint32_t g_O[NCTA * 9 * 512];
__device__ __align__(1024) uint32_t g_KV[32 * SEQ * 20];
__device__ __align__(1024) uint32_t g_Q[NCTA * 4 * 256 * 8];
__device__ __align__(1024) uint4 g_P[NCTA * 3584];
__device__ __align__(1024) uint4 g_L[NCTA * 384];
__device__ float g_S[NCTA * 8 * SEQ];
__device__ uint32_t g_flags[16 * 32 + NCTA * 32 * 4];
#define FLAG_KV(l, j) (&g_flags[((l) * 8 + (j)) * 32])
#define FLAG_H(c) (&g_flags[16 * 32 + (c) * 32])
#define FLAG_O(c) (&g_flags[16 * 32 + NCTA * 32 + (c) * 32])
#define FLAG_P(c) (&g_flags[16 * 32 + NCTA * 64 + (c) * 32])
#define FLAG_EPOCH(c) (&g_flags[16 * 32 + NCTA * 96 + (c) * 32])
#define STAMP(i)
#define STAMPW(i)
#define TRACE()

template<uint32_t BHI> __device__ __forceinline__ void wg_rs_n192(float* d, uint32_t a0, uint32_t a1, uint32_t a2, uint32_t a3, uint32_t b) {
  asm volatile("{\n.reg .pred p;\n.reg .b64 db;\nsetp.ne.b32 p, 1, 0;\nmov.b64 db, {%100, %101};\n"
    "wgmma.mma_async.sync.aligned.m64n192k16.f32.bf16.bf16 {%0, %1, %2, %3, %4, %5, %6, %7, %8, %9, %10, %11, %12, %13, %14, %15, %16, %17, %18, %19, %20, %21, %22, %23, %24, %25, %26, %27, %28, %29, %30, %31, %32, %33, %34, %35, %36, %37, %38, %39, %40, %41, %42, %43, %44, %45, %46, %47, %48, %49, %50, %51, %52, %53, %54, %55, %56, %57, %58, %59, %60, %61, %62, %63, %64, %65, %66, %67, %68, %69, %70, %71, %72, %73, %74, %75, %76, %77, %78, %79, %80, %81, %82, %83, %84, %85, %86, %87, %88, %89, %90, %91, %92, %93, %94, %95}, {%96, %97, %98, %99}, db, p, 1, 1, 1;\n}\n"
    : "+f"(d[0]), "+f"(d[1]), "+f"(d[2]), "+f"(d[3]), "+f"(d[4]), "+f"(d[5]), "+f"(d[6]), "+f"(d[7]), "+f"(d[8]), "+f"(d[9]), "+f"(d[10]), "+f"(d[11]), "+f"(d[12]), "+f"(d[13]), "+f"(d[14]), "+f"(d[15]), "+f"(d[16]), "+f"(d[17]), "+f"(d[18]), "+f"(d[19]), "+f"(d[20]), "+f"(d[21]), "+f"(d[22]), "+f"(d[23]), "+f"(d[24]), "+f"(d[25]), "+f"(d[26]), "+f"(d[27]), "+f"(d[28]), "+f"(d[29]), "+f"(d[30]), "+f"(d[31]), "+f"(d[32]), "+f"(d[33]), "+f"(d[34]), "+f"(d[35]), "+f"(d[36]), "+f"(d[37]), "+f"(d[38]), "+f"(d[39]), "+f"(d[40]), "+f"(d[41]), "+f"(d[42]), "+f"(d[43]), "+f"(d[44]), "+f"(d[45]), "+f"(d[46]), "+f"(d[47]), "+f"(d[48]), "+f"(d[49]), "+f"(d[50]), "+f"(d[51]), "+f"(d[52]), "+f"(d[53]), "+f"(d[54]), "+f"(d[55]), "+f"(d[56]), "+f"(d[57]), "+f"(d[58]), "+f"(d[59]), "+f"(d[60]), "+f"(d[61]), "+f"(d[62]), "+f"(d[63]), "+f"(d[64]), "+f"(d[65]), "+f"(d[66]), "+f"(d[67]), "+f"(d[68]), "+f"(d[69]), "+f"(d[70]), "+f"(d[71]), "+f"(d[72]), "+f"(d[73]), "+f"(d[74]), "+f"(d[75]), "+f"(d[76]), "+f"(d[77]), "+f"(d[78]), "+f"(d[79]), "+f"(d[80]), "+f"(d[81]), "+f"(d[82]), "+f"(d[83]), "+f"(d[84]), "+f"(d[85]), "+f"(d[86]), "+f"(d[87]), "+f"(d[88]), "+f"(d[89]), "+f"(d[90]), "+f"(d[91]), "+f"(d[92]), "+f"(d[93]), "+f"(d[94]), "+f"(d[95])
    : "r"(a0), "r"(a1), "r"(a2), "r"(a3), "r"(b), "n"(BHI));
}
template<uint32_t BHI> __device__ __forceinline__ void wg_rs_z_n192(float* d, uint32_t a0, uint32_t a1, uint32_t a2, uint32_t a3, uint32_t b) {
  asm volatile("{\n.reg .pred p;\n.reg .b64 db;\nsetp.ne.b32 p, 0, 0;\nmov.b64 db, {%100, %101};\n"
    "wgmma.mma_async.sync.aligned.m64n192k16.f32.bf16.bf16 {%0, %1, %2, %3, %4, %5, %6, %7, %8, %9, %10, %11, %12, %13, %14, %15, %16, %17, %18, %19, %20, %21, %22, %23, %24, %25, %26, %27, %28, %29, %30, %31, %32, %33, %34, %35, %36, %37, %38, %39, %40, %41, %42, %43, %44, %45, %46, %47, %48, %49, %50, %51, %52, %53, %54, %55, %56, %57, %58, %59, %60, %61, %62, %63, %64, %65, %66, %67, %68, %69, %70, %71, %72, %73, %74, %75, %76, %77, %78, %79, %80, %81, %82, %83, %84, %85, %86, %87, %88, %89, %90, %91, %92, %93, %94, %95}, {%96, %97, %98, %99}, db, p, 1, 1, 1;\n}\n"
    : "=f"(d[0]), "=f"(d[1]), "=f"(d[2]), "=f"(d[3]), "=f"(d[4]), "=f"(d[5]), "=f"(d[6]), "=f"(d[7]), "=f"(d[8]), "=f"(d[9]), "=f"(d[10]), "=f"(d[11]), "=f"(d[12]), "=f"(d[13]), "=f"(d[14]), "=f"(d[15]), "=f"(d[16]), "=f"(d[17]), "=f"(d[18]), "=f"(d[19]), "=f"(d[20]), "=f"(d[21]), "=f"(d[22]), "=f"(d[23]), "=f"(d[24]), "=f"(d[25]), "=f"(d[26]), "=f"(d[27]), "=f"(d[28]), "=f"(d[29]), "=f"(d[30]), "=f"(d[31]), "=f"(d[32]), "=f"(d[33]), "=f"(d[34]), "=f"(d[35]), "=f"(d[36]), "=f"(d[37]), "=f"(d[38]), "=f"(d[39]), "=f"(d[40]), "=f"(d[41]), "=f"(d[42]), "=f"(d[43]), "=f"(d[44]), "=f"(d[45]), "=f"(d[46]), "=f"(d[47]), "=f"(d[48]), "=f"(d[49]), "=f"(d[50]), "=f"(d[51]), "=f"(d[52]), "=f"(d[53]), "=f"(d[54]), "=f"(d[55]), "=f"(d[56]), "=f"(d[57]), "=f"(d[58]), "=f"(d[59]), "=f"(d[60]), "=f"(d[61]), "=f"(d[62]), "=f"(d[63]), "=f"(d[64]), "=f"(d[65]), "=f"(d[66]), "=f"(d[67]), "=f"(d[68]), "=f"(d[69]), "=f"(d[70]), "=f"(d[71]), "=f"(d[72]), "=f"(d[73]), "=f"(d[74]), "=f"(d[75]), "=f"(d[76]), "=f"(d[77]), "=f"(d[78]), "=f"(d[79]), "=f"(d[80]), "=f"(d[81]), "=f"(d[82]), "=f"(d[83]), "=f"(d[84]), "=f"(d[85]), "=f"(d[86]), "=f"(d[87]), "=f"(d[88]), "=f"(d[89]), "=f"(d[90]), "=f"(d[91]), "=f"(d[92]), "=f"(d[93]), "=f"(d[94]), "=f"(d[95])
    : "r"(a0), "r"(a1), "r"(a2), "r"(a3), "r"(b), "n"(BHI));
}
template<uint32_t AHI, uint32_t BHI> __device__ __forceinline__ void wg_ss_n128(float* d, uint32_t a, uint32_t b) {
  asm volatile("{\n.reg .pred p;\n.reg .b64 da, db;\nsetp.ne.b32 p, 1, 0;\nmov.b64 da, {%64, %66};\nmov.b64 db, {%65, %67};\n"
    "wgmma.mma_async.sync.aligned.m64n128k16.f32.bf16.bf16 {%0, %1, %2, %3, %4, %5, %6, %7, %8, %9, %10, %11, %12, %13, %14, %15, %16, %17, %18, %19, %20, %21, %22, %23, %24, %25, %26, %27, %28, %29, %30, %31, %32, %33, %34, %35, %36, %37, %38, %39, %40, %41, %42, %43, %44, %45, %46, %47, %48, %49, %50, %51, %52, %53, %54, %55, %56, %57, %58, %59, %60, %61, %62, %63}, da, db, p, 1, 1, 0, 1;\n}\n"
    : "+f"(d[0]), "+f"(d[1]), "+f"(d[2]), "+f"(d[3]), "+f"(d[4]), "+f"(d[5]), "+f"(d[6]), "+f"(d[7]), "+f"(d[8]), "+f"(d[9]), "+f"(d[10]), "+f"(d[11]), "+f"(d[12]), "+f"(d[13]), "+f"(d[14]), "+f"(d[15]), "+f"(d[16]), "+f"(d[17]), "+f"(d[18]), "+f"(d[19]), "+f"(d[20]), "+f"(d[21]), "+f"(d[22]), "+f"(d[23]), "+f"(d[24]), "+f"(d[25]), "+f"(d[26]), "+f"(d[27]), "+f"(d[28]), "+f"(d[29]), "+f"(d[30]), "+f"(d[31]), "+f"(d[32]), "+f"(d[33]), "+f"(d[34]), "+f"(d[35]), "+f"(d[36]), "+f"(d[37]), "+f"(d[38]), "+f"(d[39]), "+f"(d[40]), "+f"(d[41]), "+f"(d[42]), "+f"(d[43]), "+f"(d[44]), "+f"(d[45]), "+f"(d[46]), "+f"(d[47]), "+f"(d[48]), "+f"(d[49]), "+f"(d[50]), "+f"(d[51]), "+f"(d[52]), "+f"(d[53]), "+f"(d[54]), "+f"(d[55]), "+f"(d[56]), "+f"(d[57]), "+f"(d[58]), "+f"(d[59]), "+f"(d[60]), "+f"(d[61]), "+f"(d[62]), "+f"(d[63])
    : "r"(a), "r"(b), "n"(AHI), "n"(BHI));
}
template<uint32_t AHI, uint32_t BHI> __device__ __forceinline__ void wg_ss_z_n128(float* d, uint32_t a, uint32_t b) {
  asm volatile("{\n.reg .pred p;\n.reg .b64 da, db;\nsetp.ne.b32 p, 0, 0;\nmov.b64 da, {%64, %66};\nmov.b64 db, {%65, %67};\n"
    "wgmma.mma_async.sync.aligned.m64n128k16.f32.bf16.bf16 {%0, %1, %2, %3, %4, %5, %6, %7, %8, %9, %10, %11, %12, %13, %14, %15, %16, %17, %18, %19, %20, %21, %22, %23, %24, %25, %26, %27, %28, %29, %30, %31, %32, %33, %34, %35, %36, %37, %38, %39, %40, %41, %42, %43, %44, %45, %46, %47, %48, %49, %50, %51, %52, %53, %54, %55, %56, %57, %58, %59, %60, %61, %62, %63}, da, db, p, 1, 1, 0, 1;\n}\n"
    : "=f"(d[0]), "=f"(d[1]), "=f"(d[2]), "=f"(d[3]), "=f"(d[4]), "=f"(d[5]), "=f"(d[6]), "=f"(d[7]), "=f"(d[8]), "=f"(d[9]), "=f"(d[10]), "=f"(d[11]), "=f"(d[12]), "=f"(d[13]), "=f"(d[14]), "=f"(d[15]), "=f"(d[16]), "=f"(d[17]), "=f"(d[18]), "=f"(d[19]), "=f"(d[20]), "=f"(d[21]), "=f"(d[22]), "=f"(d[23]), "=f"(d[24]), "=f"(d[25]), "=f"(d[26]), "=f"(d[27]), "=f"(d[28]), "=f"(d[29]), "=f"(d[30]), "=f"(d[31]), "=f"(d[32]), "=f"(d[33]), "=f"(d[34]), "=f"(d[35]), "=f"(d[36]), "=f"(d[37]), "=f"(d[38]), "=f"(d[39]), "=f"(d[40]), "=f"(d[41]), "=f"(d[42]), "=f"(d[43]), "=f"(d[44]), "=f"(d[45]), "=f"(d[46]), "=f"(d[47]), "=f"(d[48]), "=f"(d[49]), "=f"(d[50]), "=f"(d[51]), "=f"(d[52]), "=f"(d[53]), "=f"(d[54]), "=f"(d[55]), "=f"(d[56]), "=f"(d[57]), "=f"(d[58]), "=f"(d[59]), "=f"(d[60]), "=f"(d[61]), "=f"(d[62]), "=f"(d[63])
    : "r"(a), "r"(b), "n"(AHI), "n"(BHI));
}
template<uint32_t AHI, uint32_t BHI> __device__ __forceinline__ void wg_ss_n160(float* d, uint32_t a, uint32_t b) {
  asm volatile("{\n.reg .pred p;\n.reg .b64 da, db;\nsetp.ne.b32 p, 1, 0;\nmov.b64 da, {%80, %82};\nmov.b64 db, {%81, %83};\n"
    "wgmma.mma_async.sync.aligned.m64n160k16.f32.bf16.bf16 {%0, %1, %2, %3, %4, %5, %6, %7, %8, %9, %10, %11, %12, %13, %14, %15, %16, %17, %18, %19, %20, %21, %22, %23, %24, %25, %26, %27, %28, %29, %30, %31, %32, %33, %34, %35, %36, %37, %38, %39, %40, %41, %42, %43, %44, %45, %46, %47, %48, %49, %50, %51, %52, %53, %54, %55, %56, %57, %58, %59, %60, %61, %62, %63, %64, %65, %66, %67, %68, %69, %70, %71, %72, %73, %74, %75, %76, %77, %78, %79}, da, db, p, 1, 1, 0, 1;\n}\n"
    : "+f"(d[0]), "+f"(d[1]), "+f"(d[2]), "+f"(d[3]), "+f"(d[4]), "+f"(d[5]), "+f"(d[6]), "+f"(d[7]), "+f"(d[8]), "+f"(d[9]), "+f"(d[10]), "+f"(d[11]), "+f"(d[12]), "+f"(d[13]), "+f"(d[14]), "+f"(d[15]), "+f"(d[16]), "+f"(d[17]), "+f"(d[18]), "+f"(d[19]), "+f"(d[20]), "+f"(d[21]), "+f"(d[22]), "+f"(d[23]), "+f"(d[24]), "+f"(d[25]), "+f"(d[26]), "+f"(d[27]), "+f"(d[28]), "+f"(d[29]), "+f"(d[30]), "+f"(d[31]), "+f"(d[32]), "+f"(d[33]), "+f"(d[34]), "+f"(d[35]), "+f"(d[36]), "+f"(d[37]), "+f"(d[38]), "+f"(d[39]), "+f"(d[40]), "+f"(d[41]), "+f"(d[42]), "+f"(d[43]), "+f"(d[44]), "+f"(d[45]), "+f"(d[46]), "+f"(d[47]), "+f"(d[48]), "+f"(d[49]), "+f"(d[50]), "+f"(d[51]), "+f"(d[52]), "+f"(d[53]), "+f"(d[54]), "+f"(d[55]), "+f"(d[56]), "+f"(d[57]), "+f"(d[58]), "+f"(d[59]), "+f"(d[60]), "+f"(d[61]), "+f"(d[62]), "+f"(d[63]), "+f"(d[64]), "+f"(d[65]), "+f"(d[66]), "+f"(d[67]), "+f"(d[68]), "+f"(d[69]), "+f"(d[70]), "+f"(d[71]), "+f"(d[72]), "+f"(d[73]), "+f"(d[74]), "+f"(d[75]), "+f"(d[76]), "+f"(d[77]), "+f"(d[78]), "+f"(d[79])
    : "r"(a), "r"(b), "n"(AHI), "n"(BHI));
}
template<uint32_t AHI, uint32_t BHI> __device__ __forceinline__ void wg_ss_z_n160(float* d, uint32_t a, uint32_t b) {
  asm volatile("{\n.reg .pred p;\n.reg .b64 da, db;\nsetp.ne.b32 p, 0, 0;\nmov.b64 da, {%80, %82};\nmov.b64 db, {%81, %83};\n"
    "wgmma.mma_async.sync.aligned.m64n160k16.f32.bf16.bf16 {%0, %1, %2, %3, %4, %5, %6, %7, %8, %9, %10, %11, %12, %13, %14, %15, %16, %17, %18, %19, %20, %21, %22, %23, %24, %25, %26, %27, %28, %29, %30, %31, %32, %33, %34, %35, %36, %37, %38, %39, %40, %41, %42, %43, %44, %45, %46, %47, %48, %49, %50, %51, %52, %53, %54, %55, %56, %57, %58, %59, %60, %61, %62, %63, %64, %65, %66, %67, %68, %69, %70, %71, %72, %73, %74, %75, %76, %77, %78, %79}, da, db, p, 1, 1, 0, 1;\n}\n"
    : "=f"(d[0]), "=f"(d[1]), "=f"(d[2]), "=f"(d[3]), "=f"(d[4]), "=f"(d[5]), "=f"(d[6]), "=f"(d[7]), "=f"(d[8]), "=f"(d[9]), "=f"(d[10]), "=f"(d[11]), "=f"(d[12]), "=f"(d[13]), "=f"(d[14]), "=f"(d[15]), "=f"(d[16]), "=f"(d[17]), "=f"(d[18]), "=f"(d[19]), "=f"(d[20]), "=f"(d[21]), "=f"(d[22]), "=f"(d[23]), "=f"(d[24]), "=f"(d[25]), "=f"(d[26]), "=f"(d[27]), "=f"(d[28]), "=f"(d[29]), "=f"(d[30]), "=f"(d[31]), "=f"(d[32]), "=f"(d[33]), "=f"(d[34]), "=f"(d[35]), "=f"(d[36]), "=f"(d[37]), "=f"(d[38]), "=f"(d[39]), "=f"(d[40]), "=f"(d[41]), "=f"(d[42]), "=f"(d[43]), "=f"(d[44]), "=f"(d[45]), "=f"(d[46]), "=f"(d[47]), "=f"(d[48]), "=f"(d[49]), "=f"(d[50]), "=f"(d[51]), "=f"(d[52]), "=f"(d[53]), "=f"(d[54]), "=f"(d[55]), "=f"(d[56]), "=f"(d[57]), "=f"(d[58]), "=f"(d[59]), "=f"(d[60]), "=f"(d[61]), "=f"(d[62]), "=f"(d[63]), "=f"(d[64]), "=f"(d[65]), "=f"(d[66]), "=f"(d[67]), "=f"(d[68]), "=f"(d[69]), "=f"(d[70]), "=f"(d[71]), "=f"(d[72]), "=f"(d[73]), "=f"(d[74]), "=f"(d[75]), "=f"(d[76]), "=f"(d[77]), "=f"(d[78]), "=f"(d[79])
    : "r"(a), "r"(b), "n"(AHI), "n"(BHI));
}
template<uint32_t BHI> __device__ __forceinline__ void wg_rs_n32(float* d, uint32_t a0, uint32_t a1, uint32_t a2, uint32_t a3, uint32_t b) {
  asm volatile("{\n.reg .pred p;\n.reg .b64 db;\nsetp.ne.b32 p, 1, 0;\nmov.b64 db, {%20, %21};\n"
    "wgmma.mma_async.sync.aligned.m64n32k16.f32.bf16.bf16 {%0, %1, %2, %3, %4, %5, %6, %7, %8, %9, %10, %11, %12, %13, %14, %15}, {%16, %17, %18, %19}, db, p, 1, 1, 1;\n}\n"
    : "+f"(d[0]), "+f"(d[1]), "+f"(d[2]), "+f"(d[3]), "+f"(d[4]), "+f"(d[5]), "+f"(d[6]), "+f"(d[7]), "+f"(d[8]), "+f"(d[9]), "+f"(d[10]), "+f"(d[11]), "+f"(d[12]), "+f"(d[13]), "+f"(d[14]), "+f"(d[15])
    : "r"(a0), "r"(a1), "r"(a2), "r"(a3), "r"(b), "n"(BHI));
}
template<uint32_t BHI> __device__ __forceinline__ void wg_rs_z_n32(float* d, uint32_t a0, uint32_t a1, uint32_t a2, uint32_t a3, uint32_t b) {
  asm volatile("{\n.reg .pred p;\n.reg .b64 db;\nsetp.ne.b32 p, 0, 0;\nmov.b64 db, {%20, %21};\n"
    "wgmma.mma_async.sync.aligned.m64n32k16.f32.bf16.bf16 {%0, %1, %2, %3, %4, %5, %6, %7, %8, %9, %10, %11, %12, %13, %14, %15}, {%16, %17, %18, %19}, db, p, 1, 1, 1;\n}\n"
    : "=f"(d[0]), "=f"(d[1]), "=f"(d[2]), "=f"(d[3]), "=f"(d[4]), "=f"(d[5]), "=f"(d[6]), "=f"(d[7]), "=f"(d[8]), "=f"(d[9]), "=f"(d[10]), "=f"(d[11]), "=f"(d[12]), "=f"(d[13]), "=f"(d[14]), "=f"(d[15])
    : "r"(a0), "r"(a1), "r"(a2), "r"(a3), "r"(b), "n"(BHI));
}
template<uint32_t BHI> __device__ __forceinline__ void wg_rs_n64(float* d, uint32_t a0, uint32_t a1, uint32_t a2, uint32_t a3, uint32_t b) {
  asm volatile("{\n.reg .pred p;\n.reg .b64 db;\nsetp.ne.b32 p, 1, 0;\nmov.b64 db, {%36, %37};\n"
    "wgmma.mma_async.sync.aligned.m64n64k16.f32.bf16.bf16 {%0, %1, %2, %3, %4, %5, %6, %7, %8, %9, %10, %11, %12, %13, %14, %15, %16, %17, %18, %19, %20, %21, %22, %23, %24, %25, %26, %27, %28, %29, %30, %31}, {%32, %33, %34, %35}, db, p, 1, 1, 0;\n}\n"
    : "+f"(d[0]), "+f"(d[1]), "+f"(d[2]), "+f"(d[3]), "+f"(d[4]), "+f"(d[5]), "+f"(d[6]), "+f"(d[7]), "+f"(d[8]), "+f"(d[9]), "+f"(d[10]), "+f"(d[11]), "+f"(d[12]), "+f"(d[13]), "+f"(d[14]), "+f"(d[15]), "+f"(d[16]), "+f"(d[17]), "+f"(d[18]), "+f"(d[19]), "+f"(d[20]), "+f"(d[21]), "+f"(d[22]), "+f"(d[23]), "+f"(d[24]), "+f"(d[25]), "+f"(d[26]), "+f"(d[27]), "+f"(d[28]), "+f"(d[29]), "+f"(d[30]), "+f"(d[31])
    : "r"(a0), "r"(a1), "r"(a2), "r"(a3), "r"(b), "n"(BHI));
}
template<uint32_t BHI> __device__ __forceinline__ void wg_rs_z_n64(float* d, uint32_t a0, uint32_t a1, uint32_t a2, uint32_t a3, uint32_t b) {
  asm volatile("{\n.reg .pred p;\n.reg .b64 db;\nsetp.ne.b32 p, 0, 0;\nmov.b64 db, {%36, %37};\n"
    "wgmma.mma_async.sync.aligned.m64n64k16.f32.bf16.bf16 {%0, %1, %2, %3, %4, %5, %6, %7, %8, %9, %10, %11, %12, %13, %14, %15, %16, %17, %18, %19, %20, %21, %22, %23, %24, %25, %26, %27, %28, %29, %30, %31}, {%32, %33, %34, %35}, db, p, 1, 1, 0;\n}\n"
    : "=f"(d[0]), "=f"(d[1]), "=f"(d[2]), "=f"(d[3]), "=f"(d[4]), "=f"(d[5]), "=f"(d[6]), "=f"(d[7]), "=f"(d[8]), "=f"(d[9]), "=f"(d[10]), "=f"(d[11]), "=f"(d[12]), "=f"(d[13]), "=f"(d[14]), "=f"(d[15]), "=f"(d[16]), "=f"(d[17]), "=f"(d[18]), "=f"(d[19]), "=f"(d[20]), "=f"(d[21]), "=f"(d[22]), "=f"(d[23]), "=f"(d[24]), "=f"(d[25]), "=f"(d[26]), "=f"(d[27]), "=f"(d[28]), "=f"(d[29]), "=f"(d[30]), "=f"(d[31])
    : "r"(a0), "r"(a1), "r"(a2), "r"(a3), "r"(b), "n"(BHI));
}
template<uint32_t BHI> __device__ __forceinline__ void wg_rs_n24(float* d, uint32_t a0, uint32_t a1, uint32_t a2, uint32_t a3, uint32_t b) {
  asm volatile("{\n.reg .pred p;\n.reg .b64 db;\nsetp.ne.b32 p, 1, 0;\nmov.b64 db, {%16, %17};\n"
    "wgmma.mma_async.sync.aligned.m64n24k16.f32.bf16.bf16 {%0, %1, %2, %3, %4, %5, %6, %7, %8, %9, %10, %11}, {%12, %13, %14, %15}, db, p, 1, 1, 1;\n}\n"
    : "+f"(d[0]), "+f"(d[1]), "+f"(d[2]), "+f"(d[3]), "+f"(d[4]), "+f"(d[5]), "+f"(d[6]), "+f"(d[7]), "+f"(d[8]), "+f"(d[9]), "+f"(d[10]), "+f"(d[11])
    : "r"(a0), "r"(a1), "r"(a2), "r"(a3), "r"(b), "n"(BHI));
}
template<uint32_t BHI> __device__ __forceinline__ void wg_rs_z_n24(float* d, uint32_t a0, uint32_t a1, uint32_t a2, uint32_t a3, uint32_t b) {
  asm volatile("{\n.reg .pred p;\n.reg .b64 db;\nsetp.ne.b32 p, 0, 0;\nmov.b64 db, {%16, %17};\n"
    "wgmma.mma_async.sync.aligned.m64n24k16.f32.bf16.bf16 {%0, %1, %2, %3, %4, %5, %6, %7, %8, %9, %10, %11}, {%12, %13, %14, %15}, db, p, 1, 1, 1;\n}\n"
    : "=f"(d[0]), "=f"(d[1]), "=f"(d[2]), "=f"(d[3]), "=f"(d[4]), "=f"(d[5]), "=f"(d[6]), "=f"(d[7]), "=f"(d[8]), "=f"(d[9]), "=f"(d[10]), "=f"(d[11])
    : "r"(a0), "r"(a1), "r"(a2), "r"(a3), "r"(b), "n"(BHI));
}
template<uint32_t BHI> __device__ __forceinline__ void wg_rsb_n64(float* d, uint32_t a0, uint32_t a1, uint32_t a2, uint32_t a3, uint32_t b) {
  asm volatile("{\n.reg .pred p;\n.reg .b64 db;\nsetp.ne.b32 p, 1, 0;\nmov.b64 db, {%36, %37};\n"
    "wgmma.mma_async.sync.aligned.m64n64k16.f32.bf16.bf16 {%0, %1, %2, %3, %4, %5, %6, %7, %8, %9, %10, %11, %12, %13, %14, %15, %16, %17, %18, %19, %20, %21, %22, %23, %24, %25, %26, %27, %28, %29, %30, %31}, {%32, %33, %34, %35}, db, p, 1, 1, 1;\n}\n"
    : "+f"(d[0]), "+f"(d[1]), "+f"(d[2]), "+f"(d[3]), "+f"(d[4]), "+f"(d[5]), "+f"(d[6]), "+f"(d[7]), "+f"(d[8]), "+f"(d[9]), "+f"(d[10]), "+f"(d[11]), "+f"(d[12]), "+f"(d[13]), "+f"(d[14]), "+f"(d[15]), "+f"(d[16]), "+f"(d[17]), "+f"(d[18]), "+f"(d[19]), "+f"(d[20]), "+f"(d[21]), "+f"(d[22]), "+f"(d[23]), "+f"(d[24]), "+f"(d[25]), "+f"(d[26]), "+f"(d[27]), "+f"(d[28]), "+f"(d[29]), "+f"(d[30]), "+f"(d[31])
    : "r"(a0), "r"(a1), "r"(a2), "r"(a3), "r"(b), "n"(BHI));
}
template<uint32_t BHI> __device__ __forceinline__ void wg_rsb_z_n64(float* d, uint32_t a0, uint32_t a1, uint32_t a2, uint32_t a3, uint32_t b) {
  asm volatile("{\n.reg .pred p;\n.reg .b64 db;\nsetp.ne.b32 p, 0, 0;\nmov.b64 db, {%36, %37};\n"
    "wgmma.mma_async.sync.aligned.m64n64k16.f32.bf16.bf16 {%0, %1, %2, %3, %4, %5, %6, %7, %8, %9, %10, %11, %12, %13, %14, %15, %16, %17, %18, %19, %20, %21, %22, %23, %24, %25, %26, %27, %28, %29, %30, %31}, {%32, %33, %34, %35}, db, p, 1, 1, 1;\n}\n"
    : "=f"(d[0]), "=f"(d[1]), "=f"(d[2]), "=f"(d[3]), "=f"(d[4]), "=f"(d[5]), "=f"(d[6]), "=f"(d[7]), "=f"(d[8]), "=f"(d[9]), "=f"(d[10]), "=f"(d[11]), "=f"(d[12]), "=f"(d[13]), "=f"(d[14]), "=f"(d[15]), "=f"(d[16]), "=f"(d[17]), "=f"(d[18]), "=f"(d[19]), "=f"(d[20]), "=f"(d[21]), "=f"(d[22]), "=f"(d[23]), "=f"(d[24]), "=f"(d[25]), "=f"(d[26]), "=f"(d[27]), "=f"(d[28]), "=f"(d[29]), "=f"(d[30]), "=f"(d[31])
    : "r"(a0), "r"(a1), "r"(a2), "r"(a3), "r"(b), "n"(BHI));
}

__device__ __forceinline__ void wg_fence() { asm volatile("wgmma.fence.sync.aligned;" ::: "memory"); }
__device__ __forceinline__ void wg_commit() { asm volatile("wgmma.commit_group.sync.aligned;" ::: "memory"); }
template <int N> __device__ __forceinline__ void wg_wait() { asm volatile("wgmma.wait_group.sync.aligned %0;" ::"n"(N) : "memory"); }
template <int R> __device__ __forceinline__ void pin(float* d) {
#pragma unroll
  for (int i = 0; i < R; i++) asm volatile("" : "+f"(d[i])::"memory");
}
template <int R> __device__ __forceinline__ void pin(uint32_t* d) {
#pragma unroll
  for (int i = 0; i < R; i++) asm volatile("" : "+r"(d[i])::"memory");
}
__device__ __forceinline__ float ex2(float x) { float y; asm("ex2.approx.ftz.f32 %0, %1;" : "=f"(y) : "f"(x)); return y; }
__device__ __forceinline__ float tanh_fast(float x) { float y; asm("tanh.approx.f32 %0, %1;" : "=f"(y) : "f"(x)); return y; }
__device__ __forceinline__ uint32_t pack(float lo, float hi) { uint32_t r; asm("cvt.rn.bf16x2.f32 %0, %1, %2;" : "=r"(r) : "f"(hi), "f"(lo)); return r; }
__device__ __forceinline__ float bf_lo(uint32_t v) { return __uint_as_float(v << 16); }
__device__ __forceinline__ float bf_hi(uint32_t v) { return __uint_as_float(v & 0xffff0000u); }
__device__ __forceinline__ float bf_round(float x) { return bf_lo(pack(x, 0.f)); }

__device__ __forceinline__ void mbar_init(uint32_t bar, uint32_t cnt) { asm volatile("mbarrier.init.shared::cta.b64 [%0], %1;" ::"r"(bar), "r"(cnt) : "memory"); }
__device__ __forceinline__ void mbar_expect(uint32_t bar, uint32_t bytes) { asm volatile("mbarrier.arrive.expect_tx.shared::cta.b64 _, [%0], %1;" ::"r"(bar), "r"(bytes) : "memory"); }
__device__ __forceinline__ void mbar_wait(uint32_t bar, uint32_t parity) {
  asm volatile(
      "{\n.reg .pred p;\n.reg .u32 c;\n"
      "mbarrier.try_wait.parity.shared::cta.b64 p, [%0], %1;\n"
      "@p bra.uni DONE;\n"
      "mov.u32 c, 0;\n"
      "LOOP:\n"
      "mbarrier.try_wait.parity.shared::cta.b64 p, [%0], %1;\n"
      "@p bra.uni DONE;\n"
      "add.u32 c, c, 1;\n"
      "setp.lt.u32 p, c, 0x400000;\n"
      "@p bra.uni LOOP;\n"
      "trap;\n"
      "DONE:\n}\n" ::"r"(bar), "r"(parity) : "memory");
}
__device__ __forceinline__ uint32_t mbar_test(uint32_t bar, uint32_t parity) {
  uint32_t ok;
  asm volatile("{\n.reg .pred p;\nmbarrier.test_wait.parity.shared::cta.b64 p, [%1], %2;\nselp.u32 %0, 1, 0, p;\n}\n" : "=r"(ok) : "r"(bar), "r"(parity) : "memory");
  return ok;
}
__device__ __forceinline__ void mbar_arrive_if(uint32_t bar, uint32_t cond) {
  asm volatile("{\n.reg .pred p;\nsetp.ne.u32 p, %1, 0;\n@p mbarrier.arrive.shared::cta.b64 _, [%0];\n}\n" ::"r"(bar), "r"(cond) : "memory");
}
__device__ __forceinline__ uint32_t bsub2(uint32_t a, uint32_t b) { uint32_t d; asm("sub.rn.bf16x2 %0, %1, %2;" : "=r"(d) : "r"(a), "r"(b)); return d; }
__device__ __forceinline__ uint32_t bscale2(uint32_t d, uint32_t hi, uint32_t lo) {
  uint32_t t, r;
  asm("mul.rn.bf16x2 %0, %1, %2;" : "=r"(t) : "r"(d), "r"(lo));
  asm("fma.rn.bf16x2 %0, %1, %2, %3;" : "=r"(r) : "r"(d), "r"(hi), "r"(t));
  return r;
}
__device__ __forceinline__ void flag_wait(const uint32_t* f, uint32_t target) {
  asm volatile(
      "{\n.reg .pred p;\n.reg .u32 c, v;\n"
      "mov.u32 c, 0;\n"
      "LOOP:\n"
      "ld.acquire.gpu.global.u32 v, [%0];\n"
      "sub.u32 v, v, %1;\n"
      "setp.ge.s32 p, v, 0;\n"
      "@p bra DONE;\n"
      "add.u32 c, c, 1;\n"
      "setp.lt.u32 p, c, 0x400000;\n"
      "@p bra LOOP;\n"
      "trap;\n"
      "DONE:\n}\n" ::"l"(f), "r"(target) : "memory");
}
__device__ __forceinline__ uint32_t flag_wait_v(const uint32_t* f, uint32_t target) {
  uint32_t v;
  asm volatile(
      "{\n.reg .pred p;\n.reg .u32 c, d;\n"
      "mov.u32 c, 0;\n"
      "LOOP:\n"
      "ld.acquire.gpu.global.u32 %0, [%1];\n"
      "sub.u32 d, %0, %2;\n"
      "setp.ge.s32 p, d, 0;\n"
      "@p bra DONE;\n"
      "add.u32 c, c, 1;\n"
      "setp.lt.u32 p, c, 0x400000;\n"
      "@p bra LOOP;\n"
      "trap;\n"
      "DONE:\n}\n" : "=&r"(v) : "l"(f), "r"(target) : "memory");
  return v;
}
__device__ __forceinline__ float sqrt_fast(float x) { float y; asm("sqrt.approx.f32 %0, %1;" : "=f"(y) : "f"(x)); return y; }
__device__ __forceinline__ float rcp_fast(float x) { float y; asm("rcp.approx.ftz.f32 %0, %1;" : "=f"(y) : "f"(x)); return y; }
__device__ __forceinline__ void ldsm4(uint32_t* v, uint32_t addr) {
  asm volatile("ldmatrix.sync.aligned.m8n8.x4.shared.b16 {%0,%1,%2,%3}, [%4];" : "=r"(v[0]), "=r"(v[1]), "=r"(v[2]), "=r"(v[3]) : "r"(addr) : "memory");
}
__device__ __forceinline__ void stsm4(uint32_t addr, uint32_t a, uint32_t b, uint32_t c, uint32_t d) {
  asm volatile("stmatrix.sync.aligned.m8n8.x4.shared.b16 [%0], {%1,%2,%3,%4};" ::"r"(addr), "r"(a), "r"(b), "r"(c), "r"(d) : "memory");
}
__device__ __forceinline__ void flag_add(uint32_t* f) { asm volatile("red.relaxed.gpu.global.add.u32 [%0], 1;" ::"l"(f) : "memory"); }
__device__ __forceinline__ void fence_gpu() { asm volatile("fence.acq_rel.gpu;" ::: "memory"); }
__device__ __forceinline__ void fence_async() { asm volatile("fence.proxy.async.global;" ::: "memory"); }
__device__ __forceinline__ void tma2d(uint32_t dst, const CUtensorMap* tm, uint32_t bar, int c0, int c1) {
  asm volatile("cp.async.bulk.tensor.2d.shared::cluster.global.mbarrier::complete_tx::bytes [%0], [%1, {%3, %4}], [%2];" ::"r"(dst), "l"(tm), "r"(bar), "r"(c0), "r"(c1) : "memory");
}
__device__ __forceinline__ void tma2d_h(uint32_t dst, const CUtensorMap* tm, uint32_t bar, int c0, int c1, uint64_t pol) {
  asm volatile("cp.async.bulk.tensor.2d.shared::cluster.global.mbarrier::complete_tx::bytes.L2::cache_hint [%0], [%1, {%3, %4}], [%2], %5;" ::"r"(dst), "l"(tm), "r"(bar), "r"(c0), "r"(c1), "l"(pol) : "memory");
}
__device__ __forceinline__ void bulk_s2g(void* dst, uint32_t src, uint32_t bytes) {
  asm volatile("cp.async.bulk.global.shared::cta.bulk_group [%0], [%1], %2;" ::"l"(dst), "r"(src), "r"(bytes) : "memory");
}
__device__ __forceinline__ void mma_ones(float* c, const uint32_t* a) {
  asm("mma.sync.aligned.m16n8k16.row.col.f32.bf16.bf16.f32 {%0,%1,%2,%3}, {%4,%5,%6,%7}, {%8,%8}, {%0,%1,%2,%3};"
      : "+f"(c[0]), "+f"(c[1]), "+f"(c[2]), "+f"(c[3]) : "r"(a[0]), "r"(a[1]), "r"(a[2]), "r"(a[3]), "r"(0x3f803f80u));
}
__device__ __forceinline__ void tma5d(uint32_t dst, const CUtensorMap* tm, uint32_t bar, int c0, int c4) {
  asm volatile("cp.async.bulk.tensor.5d.shared::cluster.global.mbarrier::complete_tx::bytes [%0], [%1, {%3, %5, %5, %5, %4}], [%2];" ::"r"(dst), "l"(tm), "r"(bar), "r"(c0), "r"(c4), "r"(0) : "memory");
}
__device__ __forceinline__ void tma3d(uint32_t dst, const CUtensorMap* tm, uint32_t bar, int c0, int c2) {
  asm volatile("cp.async.bulk.tensor.3d.shared::cluster.global.mbarrier::complete_tx::bytes [%0], [%1, {%3, %5, %4}], [%2];" ::"r"(dst), "l"(tm), "r"(bar), "r"(c0), "r"(c2), "r"(0) : "memory");
}
__device__ __forceinline__ void bulk_g2s(uint32_t dst, const void* src, uint32_t bytes, uint32_t bar) {
  asm volatile("cp.async.bulk.shared::cluster.global.mbarrier::complete_tx::bytes [%0], [%1], %2, [%3];" ::"r"(dst), "l"(src), "r"(bytes), "r"(bar) : "memory");
}
__device__ __forceinline__ void pf_line(const void* p) { asm volatile("prefetch.global.L2 [%0];" ::"l"(p) : "memory"); }
__device__ __forceinline__ int fresh_tid() { int v; asm volatile("mov.u32 %0, %%tid.x;" : "=r"(v)); return v; }
struct Att {
  float s[32];
  float o[12];
  uint32_t p[16];
  uint32_t q[8];
};

__device__ __forceinline__ float warp_sum(float v) {
#pragma unroll 1
  for (int d = 16; d; d >>= 1) v += __shfl_xor_sync(0xffffffffu, v, d);
  return v;
}
#define OPAQUE(x) asm volatile("" : "+r"(x))
__device__ __forceinline__ void attn_slow_row(int cta, uint32_t& w) {
  float mx = -INFINITY;
#pragma unroll 1
  for (uint32_t key = threadIdx.x & 31; key < SEQ; key += 32) {
    float s = 0.f;
#pragma unroll 1
    for (uint32_t v = 0; v < 9; v++) {
      OPAQUE(w); OPAQUE(key);
      const uint32_t hp = (w >> 4) & 3, pos = (v + hp) & 3;
      const uint32_t q = g_Q[(((cta * 4 + hp) * 2 + (v >> 3)) * 256 + ((w >> 6) & 7) * 32 + (w & 7) * 4 + pos) * 4 + 2 * ((v >> 2) & 1) + ((w >> 3) & 1)];
      const uint32_t u = g_KV[(4 * (cta & 7) + hp) * SEQ * 20 + (key >> 3) * 160 + (key & 7) * 4 + (v >> 2) * 32 + pos];
      s = fmaf(bf_lo(q), bf_lo(u), fmaf(bf_hi(q), bf_hi(u), s));
    }
    g_S[(cta * 8 + ((w >> 6) & 7)) * SEQ + key] = s;
    mx = fmaxf(mx, s);
  }
#pragma unroll 1
  for (int d = 16; d; d >>= 1) mx = fmaxf(mx, __shfl_xor_sync(0xffffffffu, mx, d));
  float l = 0.f;
#pragma unroll 1
  for (uint32_t key = threadIdx.x & 31; key < SEQ; key += 32) l += ex2(g_S[(cta * 8 + ((w >> 6) & 7)) * SEQ + key] - mx);
  l = 2.f * rcp_fast(warp_sum(l));
#pragma unroll 1
  for (uint32_t v = w >> 9; v < 9; v++) {
    float a = 0.f, b = 0.f;
#pragma unroll 1
    for (uint32_t key = threadIdx.x & 31; key < SEQ; key += 32) {
      OPAQUE(w); OPAQUE(v);
      const uint32_t hp = (w >> 4) & 3;
      const uint32_t u = g_KV[(4 * (cta & 7) + hp) * SEQ * 20 + (key >> 3) * 160 + (key & 7) * 4 + (v < 8 ? (3 + (v >> 2)) * 32 + (v & 3) : 64 + ((hp + 2) & 3))];
      const float p = ex2(g_S[(cta * 8 + ((w >> 6) & 7)) * SEQ + key] - mx);
      a = fmaf(p, bf_lo(u), a); b = fmaf(p, bf_hi(u), b);
    }
    a = warp_sum(a); b = warp_sum(b);
    OPAQUE(w);
    const uint32_t hp = (w >> 4) & 3;
    if ((threadIdx.x & 31) == 0) g_O[cta * 9 * 512 + (((w >> 6) & 7) * 16 + (w & 15)) * 4 + (v < 8 ? (2 * hp + (v >> 2)) * 512 + (v & 3) : 8 * 512 + hp)] = pack(a * l, b * l);
  }
}

__device__ __forceinline__ uint32_t bad_heads(uint32_t bad_addr, int wr) {
  uint32_t bad;
  __syncwarp();
  asm volatile("ld.volatile.shared.u32 %0, [%1];" : "=r"(bad) : "r"(bad_addr) : "memory");
  return __shfl_sync(0xffffffffu, (bad >> (4 * wr)) & 15, 0);
}
__device__ __forceinline__ void repair_rows(int cta, int wr, uint32_t bad, int last_head, bool final) {
#pragma unroll 1
  for (uint32_t w = wr * 64; w < wr * 64 + 64; w++) {
    if (!((bad >> ((w >> 4) & 3)) & 1)) continue;
    if (final && ((w >> 4) & 3) != last_head) w |= 8u << 9;
    attn_slow_row(cta, w);
    w &= 511;
  }
  __syncwarp();
}
__device__ __forceinline__ void o_normalise(const float* o, uint32_t* w, uint32_t& x0, uint32_t& x1, int hp, int lane, uint32_t bad_addr, int wr) {
  const int src = (lane & ~3) | ((hp + 1) & 3);
  float l0 = __shfl_sync(0xffffffffu, o[0], src), l1 = __shfl_sync(0xffffffffu, o[2], src);
  float sa = 0.f;
#pragma unroll
  for (int i = 0; i < 12; i++) sa += fabsf(o[i]);
  bool ok = (l0 <= 1.329228e36f) && (l1 <= 1.329228e36f) && (l0 > 0.f) && (l1 > 0.f) && (sa <= 3.0e38f);
  float i0 = 2.f * rcp_fast(l0), i1 = 2.f * rcp_fast(l1);
  w[0] = pack(o[4] * i0, o[5] * i0);
  w[1] = pack(o[6] * i1, o[7] * i1);
  w[2] = pack(o[8] * i0, o[9] * i0);
  w[3] = pack(o[10] * i1, o[11] * i1);
  if ((lane & 3) == ((hp + 2) & 3)) { x0 = pack(o[0] * i0, o[1] * i0); x1 = pack(o[2] * i1, o[3] * i1); }
  if (!ok) asm volatile("red.shared.or.b32 [%0], %1;" ::"r"(bad_addr), "r"(1u << (4 * wr + hp)) : "memory");
}

__device__ __forceinline__ void issue_pv(Att& a, uint32_t kdesc) {
  const uint32_t vdesc = kdesc + 192 + (LO_V - LO_K);
#pragma unroll
  for (int k = 0; k < 4; k++) wg_rs_n24<HI_V>(a.o, a.p[4 * k], a.p[4 * k + 1], a.p[4 * k + 2], a.p[4 * k + 3], vdesc + k * 48);
}
__device__ __forceinline__ void issue_att(Att& a, uint32_t kdesc) {
  issue_pv(a, kdesc);
  wg_rs_z_n64<HI_K>(a.s, a.q[0], a.q[1], a.q[2], a.q[3], kdesc);
  wg_rs_n64<HI_K>(a.s, a.q[4], a.q[5], a.q[6], a.q[7], kdesc + 16);
}
__device__ __forceinline__ void softmax_a(Att& a) {
#pragma unroll
  for (int i = 0; i < SM_A; i++) a.p[i] = pack(ex2(a.s[2 * i]), ex2(a.s[2 * i + 1]));
  pin<SM_A>(a.p);
}
__device__ __forceinline__ void softmax_b(Att& a) {
#pragma unroll
  for (int i = SM_A; i < SM_B; i++) a.p[i] = pack(ex2(a.s[2 * i]), ex2(a.s[2 * i + 1]));
  a.s[2 * SM_B] = ex2(a.s[2 * SM_B]); a.s[2 * SM_B + 1] = ex2(a.s[2 * SM_B + 1]);
  pin<SM_B - SM_A>(a.p + SM_A); pin<2>(a.s + 2 * SM_B);
}
__device__ __forceinline__ void softmax_c(Att& a) {
  a.p[SM_B] = pack(a.s[2 * SM_B], a.s[2 * SM_B + 1]);
#pragma unroll
  for (int i = SM_B + 1; i < 16; i++) a.p[i] = pack(ex2(a.s[2 * i]), ex2(a.s[2 * i + 1]));
  pin<16 - SM_B>(a.p + SM_B);
}
__device__ __forceinline__ void first_tile(Att& a, int hp, int lane) {
  float m0 = fmaxf(a.s[0], a.s[1]), m1 = fmaxf(a.s[2], a.s[3]);
#pragma unroll
  for (int i = 4; i < 32; i += 4) { m0 = fmaxf(m0, fmaxf(a.s[i], a.s[i + 1])); m1 = fmaxf(m1, fmaxf(a.s[i + 2], a.s[i + 3])); }
  m0 = fmaxf(m0, __shfl_xor_sync(0xffffffffu, m0, 1)); m1 = fmaxf(m1, __shfl_xor_sync(0xffffffffu, m1, 1));
  m0 = fmaxf(m0, __shfl_xor_sync(0xffffffffu, m0, 2)); m1 = fmaxf(m1, __shfl_xor_sync(0xffffffffu, m1, 2));
  float n0 = -(m0 + MOFF), n1 = -(m1 + MOFF);
  float h0 = bf_round(n0), h1 = bf_round(n1);
  uint32_t e0 = pack(h0, n0 - h0), e1 = pack(h1, n1 - h1);
  n0 = h0 + bf_hi(e0); n1 = h1 + bf_hi(e1);
  if ((lane & 3) == ((hp + 1) & 3)) { a.q[4] = e0; a.q[5] = e1; }
#pragma unroll
  for (int i = 0; i < 32; i += 4) { a.s[i] += n0; a.s[i + 1] += n0; a.s[i + 2] += n1; a.s[i + 3] += n1; }
#pragma unroll
  for (int i = 0; i < 12; i++) a.o[i] = 0.f;
  pin<12>(a.o); pin<8>(a.q);
}
__device__ __forceinline__ void fetch_q(uint32_t* q, int cta, int hp, int tid) {
  const uint4* src = reinterpret_cast<const uint4*>(g_Q) + (cta * 4 + hp) * 512 + tid;
  const uint4 u = __ldcg(src);
  const uint2 v = __ldcg(reinterpret_cast<const uint2*>(src + 256));
  q[0] = u.x; q[1] = u.y; q[2] = u.z; q[3] = u.w; q[4] = v.x; q[5] = v.y;
}
__device__ __forceinline__ void h_epilogue(const float* acc, uint32_t* dst) {
#pragma unroll
  for (int b = 0; b < 4; b++) {
    uint32_t w[2][2];
#pragma unroll
    for (int i = 0; i < 2; i++) {
      float h[4];
#pragma unroll
      for (int e = 0; e < 4; e++) {
        const float g = acc[(2 * b + i) * 4 + e], u = acc[32 + (2 * b + i) * 4 + e];
        h[e] = fmaf(tanh_fast(0.5f * g), u, u);
      }
      w[0][i] = pack(h[0], h[1]); w[1][i] = pack(h[2], h[3]);
    }
    *reinterpret_cast<uint2*>(dst + 1024 * b) = make_uint2(w[0][0], w[0][1]);
    *reinterpret_cast<uint2*>(dst + 1024 * b + 32) = make_uint2(w[1][0], w[1][1]);
  }
}
__device__ __forceinline__ void rotate9(uint32_t (&v)[9][2]) {
#pragma unroll
  for (int rh = 0; rh < 2; rh++) {
    const uint32_t r = v[8][rh];
#pragma unroll
    for (int i = 8; i > 0; i--) v[i][rh] = v[i - 1][rh];
    v[0][rh] = r;
  }
}
template <int HP> __device__ __forceinline__ void store_kv_head(uint32_t (&pk)[2][9][2], uint32_t* kvp, int lane, uint32_t sk = 0, uint32_t sv = 0) {
  const int t = lane & 3, dv = ((t - HP) & 3) - t;
  const bool up = t < HP;
#pragma unroll
  for (int rh = 0; rh < 2; rh++) {
    uint32_t* d = kvp + HP * SEQ * 20 + rh * 160;
    const uint32_t c0 = up ? pk[0][2 * HP + 1][rh] : pk[0][2 * HP][rh], c1 = up ? pk[0][2 * HP + 2][rh] : pk[0][2 * HP + 1][rh];
    const uint32_t c3 = up ? pk[1][2 * HP + 1][rh] : pk[1][2 * HP][rh], c4 = up ? pk[1][2 * HP + 2][rh] : pk[1][2 * HP + 1][rh];
    const uint32_t v9 = __shfl_sync(0xffffffffu, pk[1][2 * HP + 2][rh], (lane & ~3) | HP);
    const uint32_t c2 = t == HP ? pk[0][2 * HP + 2][rh] : t == ((HP + 1) & 3) ? 0x3f803f80u : t == ((HP + 2) & 3) ? v9 : 0u;
    d[0] = c0; d[32] = c1; d[64] = c2; d[96 + dv] = c3; d[128 + dv] = c4;
    if (sk) {
      asm volatile("st.shared.b32 [%0], %1;\nst.shared.b32 [%0 + 128], %2;\nst.shared.b32 [%0 + 256], %3;" ::"r"(sk + rh * 384), "r"(c0), "r"(c1), "r"(c2) : "memory");
      asm volatile("st.shared.b32 [%0], %1;\nst.shared.b32 [%2 + 128], %3;\nst.shared.b32 [%2 + 256], %4;" ::"r"(sv + rh * 384), "r"(c2), "r"(sv + rh * 384 + dv * 4), "r"(c3), "r"(c4) : "memory");
    }
  }
}

template <int OFF> __device__ __forceinline__ void ld4(uint32_t* v, const void* p) {
  asm volatile("ld.relaxed.gpu.global.v4.b32 {%0,%1,%2,%3}, [%4 + %5];" : "=r"(v[0]), "=r"(v[1]), "=r"(v[2]), "=r"(v[3]) : "l"(p), "n"(OFF) : "memory");
}
template <int OFF> __device__ __forceinline__ void ld2(uint32_t* v, const void* p) {
  asm volatile("ld.relaxed.gpu.global.v2.b32 {%0,%1}, [%2 + %3];" : "=r"(v[0]), "=r"(v[1]) : "l"(p), "n"(OFF) : "memory");
}
__device__ __forceinline__ void stage_partials(const float* acc, uint32_t dst, int tid) {
  const int lane = tid & 31, row = (tid >> 5) * 16 + (lane & 15);
  const uint32_t r128 = dst + row * 128, r64 = dst + 49152 + row * 64;
#pragma unroll
  for (int i = 0; i < 12; i++) {
    const float* v = acc + 8 * i;
    stsm4(r128 + (i >> 2) * 16384 + (((2 * (i & 3) + (lane >> 4)) ^ (row & 7)) << 4), pack(v[0], v[1]), pack(v[2], v[3]), pack(v[4], v[5]), pack(v[6], v[7]));
  }
#pragma unroll
  for (int i = 0; i < 2; i++) {
    const float* v = acc + 128 + 8 * i;
    stsm4(r64 + (((2 * i + (lane >> 4)) ^ ((row >> 1) & 3)) << 4), pack(v[0], v[1]), pack(v[2], v[3]), pack(v[4], v[5]), pack(v[6], v[7]));
  }
}
__device__ __forceinline__ void final_epilogue(const float* acc, const Params& prm, int m, int hh, int q, int tid) {
  uint32_t r[18];
#pragma unroll
  for (int i = 0; i < 16; i++) r[i] = pack(acc[2 * i] * 0.5f, acc[2 * i + 1] * 0.5f);
#pragma unroll
  for (int i = 0; i < 2; i++) {
    const int o = 32 + 4 * i;
    const float a0 = (q & 2) ? acc[o + 2] : acc[o], a1 = (q & 2) ? acc[o + 10] : acc[o + 8];
    const float b0 = (q & 2) ? acc[o + 3] : acc[o + 1], b1 = (q & 2) ? acc[o + 11] : acc[o + 9];
    r[16 + i] = pack(((q & 1) ? a1 : a0) * 0.5f, ((q & 1) ? b1 : b0) * 0.5f);
  }
  const size_t off = (size_t)(128 * m + (tid >> 5) * 16 + ((tid & 31) >> 2)) * DM + 2 * (tid & 3);
  const bool odd = tid & 1;
  uint32_t* o1 = reinterpret_cast<uint32_t*>(prm.out + off + 320 * hh + 64 * q) + (odd ? 3 : 0);
  uint32_t* o2 = reinterpret_cast<uint32_t*>(prm.out + off + 256 + 32 * hh + 16 * (q & 1) + (q >> 1) * 8 * DM) + (odd ? 3 : 0);
#pragma unroll
  for (int i = 0; i < 9; i++) {
    const uint32_t A = i < 8 ? r[4 * (i >> 1) + (i & 1)] : r[16], B = i < 8 ? r[4 * (i >> 1) + 2 + (i & 1)] : r[17];
    const uint32_t y = __shfl_xor_sync(0xffffffffu, odd ? A : B, 1);
    *reinterpret_cast<uint2*>(i < 8 ? o1 + 8 * (i >> 1) + (i & 1) * 8 * (DM / 2) : o2) = odd ? make_uint2(y, B) : make_uint2(A, y);
  }
}

__global__ void __launch_bounds__(384, 1) fused_kernel(const __grid_constant__ Params prm) {
  extern __shared__ __align__(1024) uint8_t smem[];
  constexpr uint32_t sb = 1024;
  const uint32_t bar = sb + SM_BAR;
  const int m = blockIdx.x & 15, j = blockIdx.x >> 4;
  const int cta = m * 8 + j;
  const int wr = __shfl_sync(0xffffffffu, (int)(threadIdx.x >> 5), 0);
  const int wg = wr >> 2;
  const int lane = threadIdx.x & 31;
  STAMP(0);
  if (wg == 2 && lane == 0) {
    if (wr == 8) {
      asm volatile("prefetch.tensormap [%0];" ::"l"(&prm.xm) : "memory");
#pragma unroll
      for (int c = 0; c < 9; c++) mbar_init(bar + 8 * (B_X + c), 1);
#pragma unroll
      for (int c = 0; c < 9; c++) mbar_expect(bar + 8 * (B_X + c), 16384);
      asm volatile("fence.proxy.async.shared::cta;" ::: "memory");
#pragma unroll
      for (int c = 0; c < 3; c++) tma2d(sb + SM_XN + c * 16384, &prm.xm, bar + 8 * (B_X + c), 64 * c, 128 * m);
    } else {
      if (wr == 9) {
#pragma unroll
        for (int i = 0; i < 8; i++) mbar_init(bar + 8 * (B_F + i), 2);
#pragma unroll
        for (int i = 0; i < 3; i++) mbar_init(bar + 8 * (B_QF + i), 1);
      } else if (wr == 10) {
#pragma unroll
        for (int i = 0; i < 8; i++) mbar_init(bar + 8 * (B_E + i), 8);
#pragma unroll
        for (int i = 0; i < 3; i++) mbar_init(bar + 8 * (B_QE + i), 8);
      } else {
#pragma unroll
        for (int i = B_SK1; i <= B_SP; i++) mbar_init(bar + 8 * i, 8);
        mbar_init(bar + 8 * B_OL, 1); mbar_init(bar + 8 * B_RX, 1);
        mbar_init(bar + 8 * B_NR, 4); mbar_init(bar + 8 * (B_NR + 1), 4);
        asm volatile("st.shared.u32 [%0], 0;" ::"r"(sb + SM_BAD) : "memory");
        if ((uint32_t)__cvta_generic_to_shared(smem) != sb || (sb & 1023)) asm volatile("trap;");
      }
      asm volatile("fence.proxy.async.shared::cta;" ::: "memory");
    }
  }
  if (wr == 0) {
    const uint32_t one = (lane >> 3) == (lane & 3) ? ((lane & 4) ? 0x3f800000u : 0x00003f80u) : 0u;
    asm volatile("st.shared.v4.b32 [%0], {%1,%2,%2,%1};" ::"r"(sb + SM_ID + lane * 16), "r"(one), "r"(0) : "memory");
  }
  __syncthreads();

  if (wg == 2) {
    asm volatile("setmaxnreg.dec.sync.aligned.u32 24;");
    const int pw = wr & 3;
    const uint32_t epoch = *(volatile uint32_t*)FLAG_EPOCH(cta);
    const int hh = j & 1;
#define ACOL(A) (320 * hh + 64 * (((j >> 1) + 1 + (A)) & 3))
    if (pw == 0) {
      if (lane == 0) {
#pragma unroll
        for (int c = 3; c < 9; c++) tma2d(sb + SM_XN + c * 16384, &prm.xm, bar + 8 * (B_X + c), 64 * c, 128 * m);
        uint64_t pol;
        asm volatile("createpolicy.fractional.L2::evict_first.b64 %0, 1.0;" : "=l"(pol));
#pragma unroll 1
        for (int kb = 0; kb < 9; kb++) {
          const int s = kb % 3;
          if (kb >= 3) mbar_wait(bar + 8 * (B_QE + s), (kb / 3 - 1) & 1);
          const uint32_t fb = bar + 8 * (B_QF + s), dst = sb + SM_RING + s * QST;
          mbar_expect(fb, QST);
#pragma unroll
          for (int p = 0; p < 3; p++) {
            tma2d_h(dst + p * 8192, &prm.wqkv64, fb, 576 * p + 72 * j + 8 * hh, 64 * kb, pol);
            tma2d(dst + 24576 + p * 1024, &prm.wqkv8, fb, 576 * p + 72 * j + 64 - 64 * hh, 64 * kb);
          }
        }
        asm volatile("st.shared.u32 [%0], %1;" ::"r"(sb + SM_TAG), "r"((epoch + 1) & 1) : "memory");
        int col = 576 * j, kr = 0;
#pragma unroll 1
        for (int n = 0; n < N_G2; n++) {
          const uint32_t fb = bar + 8 * (B_F + (n & 7)), dst = sb + SM_RING + (n & 3) * BST;
          mbar_expect(fb, BST);
          if (n >= 4) mbar_wait(bar + 8 * (B_E + ((n - 3) & 7)), ((n - 3) >> 3) & 1);
          else if (n != 2) mbar_wait(bar + 8 * (B_QE + (n == 3 ? 2 : n)), 0);
          tma2d_h(dst, &prm.wg, fb, col, kr, pol);
          tma2d_h(dst + 8192, &prm.wu, fb, col, kr, pol);
          if ((kr += 64) == 576) { kr = 0; col += 64; }
        }
        uint32_t seen = 0;
#pragma unroll 1
        for (int b = 0; b < 26; b++) {
          const int n = N_G2 + 2 * b;
          const uint32_t fb = bar + 8 * (B_F + (n & 7)), dst = sb + (b & 3) * G2ST;
          const int own = b < 10 || b == 20 || b == 21, jj = own ? j : (j ^ 1), lb = b < 10 ? b : b < 20 ? b - 10 : 10 + (b & 1), need = (3 * lb + 6) >> 2;
          if (b < 24) {
            if (b == 10 || b == 20 || b == 22) seen = 0;
            if (seen < need) { seen = flag_wait_v(FLAG_H(m * 8 + jj), 9 * epoch + need) - 9 * epoch; fence_async(); }
          } else {
            flag_wait(FLAG_O((cta & ~1) + b - 24), epoch + 1);
            fence_async();
          }
          mbar_wait(bar + 8 * (B_E + ((n - 5) & 7)), ((n - 5) >> 3) & 1);
          if (b == 0) STAMPW(16);
          mbar_expect(fb, G2ST);
          if (b < 24) {
            bulk_g2s(dst, g_H + (m * 576 + 72 * jj + 6 * lb) * 512, 12288, fb);
#pragma unroll
            for (int a = 0; a < 4; a++) tma5d(dst + 12288 + a * 6144, &prm.wd[0], fb, ACOL(a), 36 * jj + 3 * lb);
            tma5d(dst + 36864, &prm.wd[1 + hh], fb, 0, 36 * jj + 3 * lb);
          } else {
            const int r = b - 24;
            bulk_g2s(dst, g_O + ((cta & ~1) + r) * 9 * 512 + r * 1024, 12288, fb);
#pragma unroll
            for (int a = 0; a < 4; a++) tma3d(dst + 12288 + a * 6144, &prm.wo3[0], fb, ACOL(a), 4 * (j & 6) + 5 * r);
            tma3d(dst + 36864, &prm.wo3[1 + hh], fb, 0, 4 * (j & 6) + 5 * r);
          }
          if (b == 0) STAMPW(17);
        }
        mbar_wait(bar + 8 * B_SP, 0);
        mbar_expect(bar + 8 * B_OL, 49152 + 32768);
        tma2d(sb + SM_RES, &prm.xm, bar + 8 * B_OL, ACOL(3), 128 * m);
        __nanosleep(200);
        tma2d(sb + SM_RES + 16384, &prm.xm, bar + 8 * B_OL, 256 + 32 * hh, 128 * m);
#pragma unroll 1
        for (int i = 0; i < 4; i++) {
          __nanosleep(200);
          tma3d(sb + SM_LB + i * 4096, &prm.wo2[0], bar + 8 * B_OL, ACOL(3), 8 * i + 3);
          tma3d(sb + SM_LB + 24576 + i * 4096, &prm.wo2[1 + hh], bar + 8 * B_OL, 0, 8 * i + 3);
          tma3d(sb + SM_LB + 16384 + i * 2048, &prm.wo16[0], bar + 8 * B_OL, ACOL(3), 8 * i);
          tma3d(sb + SM_LB + 40960 + i * 2048, &prm.wo16[1 + hh], bar + 8 * B_OL, 0, 8 * i);
        }
      }
    } else if (pw == 1) {
      if (lane == 0) {
        const int hx = hh * 3;
        int u = 0, kslot = 0, vrow = 0, kb = 0;
#pragma unroll 1
        for (int n = 0; n <= N_END; n++) {
          const uint32_t fb = bar + 8 * (B_F + (n & 7)), dst = sb + SM_KV + kslot * KVST;
          const bool att = n >= N_G2 || (n >= NG0 && kb != 0);
          if (++kb == 9) kb = 0;
          mbar_expect(fb, !att || u < 2 ? 0 : (u == 2 || u == 128) ? KVST / 2 : KVST);
          if (n >= N_AO || (n > N_G2 && !(n & 1))) mbar_expect(fb, 0);
          if (u == 2 && att) { flag_wait(FLAG_KV(0, j), 16 * epoch + 16); fence_async(); STAMPW(18); }
          if (n >= 4) mbar_wait(bar + 8 * (B_E + ((n - 3) & 7)), ((n - 3) >> 3) & 1);
          if (att) {
            const int krow = (4 * j + ((u >> 5) ^ hx)) * 256 + ((u + 2 * m) & 31) * 8;
            if (u >= 2 && u < 128) tma2d(dst, &prm.kv, fb, 0, krow);
            if (u >= 3) tma2d(dst + 3072, &prm.kv, fb, 128, vrow);
            vrow = krow; u++;
            if (++kslot == 3) kslot = 0;
            if (u == 16) { flag_wait(FLAG_KV(1, j), 16 * epoch + 16); fence_async(); }
          }
        }
      }
    } else if (pw == 2) {
      if (lane == 0) {
#pragma unroll 1
        for (int i = 1; i < 18; i++) asm volatile("prefetch.tensormap [%0];" ::"l"(&prm.xm + i) : "memory");
        mbar_wait(bar + 8 * B_SK1, 0);
        STAMPW(22);
        fence_gpu(); flag_add(FLAG_KV(0, j));
        STAMPW(20);
        mbar_wait(bar + 8 * B_SK2, 0);
        fence_gpu(); flag_add(FLAG_KV(1, j));
#pragma unroll 1
        for (int t = 0; t < 9; t++) { mbar_wait(bar + 8 * B_SH, t & 1); __nanosleep(1000); fence_gpu(); flag_add(FLAG_H(cta)); }
        mbar_wait(bar + 8 * B_SO1, 0);
        fence_gpu(); flag_add(FLAG_O(cta));
      }
    } else {
      mbar_wait(bar + 8 * (B_X + PF_Q), 0);
#pragma unroll 1
      for (int i = lane; i < 122; i += 32) pf_line(prm.pwqkv + (size_t)min(i * 128 + cta, 15551) * 64);
      mbar_wait(bar + 8 * (B_QE + PF_G1), 0);
#pragma unroll 1
      for (int t = -3; t < 9; t++) {
        if (t >= 0) { mbar_wait(bar + 8 * B_SH, t & 1); __nanosleep(1500); }
        if (t < 6) {
#pragma unroll 1
          for (int i = lane; i < 72; i += 32) pf_line((i >= 36 ? prm.pwu : prm.pwg) + (size_t)(36 * m + (i >= 36 ? i - 36 : i)) * FF + 576 * j + 64 * (t + 3));
        }
        if ((t == 2 || t == 6 || t == 8)) {
          const uint32_t* kv = g_KV + (size_t)(4 * j + ((t == 2 ? 1 : t == 6 ? 2 : 3) ^ (hh * 3))) * SEQ * 20 + m * 2560;
#pragma unroll 1
          for (int i = lane; i < 80; i += 32) pf_line(kv + i * 32);
        }
        if (t >= 5) {
#pragma unroll 1
          for (int i = lane; i < 81; i += 32) {
            const int l = (2 * m + hh) * 81 + i, r = l / 9;
            pf_line(prm.pwd + (size_t)(1152 * (j >> 1) + 576 * (r / 144) + 144 * (t - 5) + r % 144) * DM + 64 * (l % 9));
          }
        }
      }
      if (cta * 41 + lane < 5184) pf_line(prm.pwo + (size_t)(cta * 41 + lane) * 64);
      if (lane < 9 && cta * 41 + 32 + lane < 5184) pf_line(prm.pwo + (size_t)(cta * 41 + 32 + lane) * 64);
      if (lane == 0) {
      mbar_wait(bar + 8 * B_SP, 0);
      const int q = j >> 1;
#pragma unroll 1
      for (int i = 0; i < 14; i++) {
        bulk_s2g(g_P + cta * 3584 + i * 256, sb + SM_SEND + i * 4096, 4096);
        asm volatile("cp.async.bulk.commit_group;\ncp.async.bulk.wait_group.read 2;" ::: "memory");
      }
      asm volatile("cp.async.bulk.wait_group 0;" ::: "memory");
      fence_gpu();
      flag_add(FLAG_P(cta));
      STAMPW(15);
      mbar_expect(bar + 8 * B_RX, 73728);
#pragma unroll 1
      for (int a = 0; a < 3; a++) {
        const int src = m * 8 + 2 * ((q + 3 - a) & 3) + hh;
        flag_wait(FLAG_P(src), epoch + 1);
        fence_async();
        bulk_g2s(sb + SM_RECV + a * 24576, g_P + src * 3584 + a * 1024, 16384, bar + 8 * B_RX);
        bulk_g2s(sb + SM_RECV + a * 24576 + 16384, g_P + src * 3584 + 3072, 8192, bar + 8 * B_RX);
      }
      STAMPW(25);
      *FLAG_EPOCH(cta) = epoch + 1;
      }
    }
  } else {
    const int tid = threadIdx.x;
    const int t = lane & 3;
    const uint32_t l0 = lane == 0;
    const uint32_t adesc = (((sb + SM_XN + wg * 8192) & 0x3FFFF) >> 4) | LO_A;
    const uint32_t bdesc = (((sb + SM_RING) & 0x3FFFF) >> 4) | LO_B;
    const uint32_t kdesc0 = (((sb + SM_KV) & 0x3FFFF) >> 4) | LO_K;
    const int hx = (j & 1) * 3;
    float accA[64], accB[64];
    Att a;
    uint32_t gs = 0, s8 = 0, fph = 0;
#define G1_ISSUE(ACC, AD, BD) _Pragma("unroll") for (int k = 0; k < 4; k++) wg_ss_n128<HI_SW128, HI_SW128>(ACC, (AD) + k * 2, (BD) + k * 128);
#define G1_ISSUE_Z(ACC, BD)                                                                                    \
  wg_ss_z_n128<HI_SW128, HI_SW128>(ACC, adesc, BD);                                                            \
  _Pragma("unroll") for (int k = 1; k < 4; k++) wg_ss_n128<HI_SW128, HI_SW128>(ACC, adesc + k * 2, (BD) + k * 128);
#define F_BAR (bar + 8 * B_F + 8 * s8)
#define F_PH fph
#define RELEASE() mbar_arrive_if(bar + 8 * B_E + 8 * s8, l0);
#define NEXT_SLOT() { gs++; fph ^= s8 == 7; s8 = s8 == 7 ? 0 : s8 + 1; }
#define NEXT_B() bd = bd == bdesc + 3072 ? bdesc : bd + 1024;
#define G1_ONLY() { mbar_wait(F_BAR, F_PH); wg_fence(); G1_ISSUE(accA, adesc + gs * 1024, bdesc + (gs & 3) * 1024) wg_commit(); wg_wait<1>(); RELEASE() NEXT_SLOT() }
    {
      const int lr = wr * 16 + (lane & 15);
      uint32_t ra[4];
#pragma unroll
      for (int k = 0; k < 4; k++) ra[k] = sb + SM_XN + lr * 128 + (((2 * k + (lane >> 4)) ^ (lr & 7)) << 4);
      asm volatile("setmaxnreg.inc.sync.aligned.u32 240;");
      float aq[96], ar[12];
#pragma unroll
      for (int i = 0; i < 96; i++) aq[i] = __int_as_float(lane >> 5);
#pragma unroll
      for (int i = 0; i < 12; i++) ar[i] = __int_as_float(lane >> 5);
      pin<96>(aq); pin<12>(ar);
      float cs[2][4] = {}, q0 = 0.f, q1 = 0.f, q2 = 0.f, q3 = 0.f;
#pragma unroll 1
      for (int c = 0; c < 9; c++) {
        mbar_wait(bar + 8 * (B_X + c), 0);
        uint32_t v[4][4];
#pragma unroll
        for (int k = 0; k < 4; k++) ldsm4(v[k], ra[k] + c * 16384);
#pragma unroll
        for (int k = 0; k < 4; k++) {
          mma_ones(cs[k & 1], v[k]);
#pragma unroll
          for (int e = 0; e < 4; e += 2) {
            const float x0 = bf_lo(v[k][e]), x1 = bf_hi(v[k][e]), y0 = bf_lo(v[k][e + 1]), y1 = bf_hi(v[k][e + 1]);
            q0 = fmaf(x0, x0, q0); q1 = fmaf(x1, x1, q1); q2 = fmaf(y0, y0, q2); q3 = fmaf(y1, y1, q3);
          }
        }
      }
      STAMP(11);
      const float mean0 = (cs[0][0] + cs[1][0]) * (1.f / 576.f), mean1 = (cs[0][2] + cs[1][2]) * (1.f / 576.f);
      q0 += q1; q2 += q3;
      q0 += __shfl_xor_sync(0xffffffffu, q0, 1); q2 += __shfl_xor_sync(0xffffffffu, q2, 1);
      q0 += __shfl_xor_sync(0xffffffffu, q0, 2); q2 += __shfl_xor_sync(0xffffffffu, q2, 2);
      float var0 = fmaf(q0, 1.f / 576.f, -mean0 * mean0), var1 = fmaf(q2, 1.f / 576.f, -mean1 * mean1);
      if (__any_sync(0xffffffffu, !(mean0 * mean0 <= 8.f * var0) || !(mean1 * mean1 <= 8.f * var1))) {
        q0 = q2 = 0.f;
#pragma unroll 1
        for (int i = 0; i < 36; i++) {
          uint32_t v[4];
          ldsm4(v, ((ra[0] + (i >> 2) * 16384) ^ ((i & 3) << 5)));
#pragma unroll
          for (int e = 0; e < 4; e += 2) {
            const float x0 = bf_lo(v[e]) - mean0, x1 = bf_hi(v[e]) - mean0, y0 = bf_lo(v[e + 1]) - mean1, y1 = bf_hi(v[e + 1]) - mean1;
            q0 = fmaf(x0, x0, fmaf(x1, x1, q0)); q2 = fmaf(y0, y0, fmaf(y1, y1, q2));
          }
        }
        q0 += __shfl_xor_sync(0xffffffffu, q0, 1); q2 += __shfl_xor_sync(0xffffffffu, q2, 1);
        q0 += __shfl_xor_sync(0xffffffffu, q0, 2); q2 += __shfl_xor_sync(0xffffffffu, q2, 2);
        var0 = q0 * (1.f / 576.f); var1 = q2 * (1.f / 576.f);
      }
      const float inv0 = rcp_fast(bf_round(sqrt_fast(bf_round(bf_round(var0) + 1e-5f)))), inv1 = rcp_fast(bf_round(sqrt_fast(bf_round(bf_round(var1) + 1e-5f))));
      const uint32_t mb0 = pack(mean0, mean0), mb1 = pack(mean1, mean1);
      const uint32_t h0 = pack(inv0, inv0), h1 = pack(inv1, inv1);
      const uint32_t e0 = pack(inv0 - bf_lo(h0), inv0 - bf_lo(h0)), e1 = pack(inv1 - bf_lo(h1), inv1 - bf_lo(h1));
      uint32_t v[4][4], xn[4][4];
#pragma unroll
      for (int k = 0; k < 4; k++) ldsm4(v[k], ra[k]);
      STAMP(1);
      const uint32_t rdesc = (((sb + SM_RING + 24576) & 0x3FFFF) >> 4) | LO_R;
      uint32_t s = 0, ph = 0;
#pragma unroll 1
      for (int kb = 0; kb < 9; kb++) {
#pragma unroll
        for (int k = 0; k < 4; k++) {
          xn[k][0] = bscale2(bsub2(v[k][0], mb0), h0, e0); xn[k][1] = bscale2(bsub2(v[k][1], mb1), h1, e1);
          xn[k][2] = bscale2(bsub2(v[k][2], mb0), h0, e0); xn[k][3] = bscale2(bsub2(v[k][3], mb1), h1, e1);
        }
        pin<16>(&xn[0][0]);
        mbar_wait(bar + 8 * B_QF + 8 * s, ph);
        wg_fence();
#pragma unroll
        for (int k = 0; k < 4; k++) {
          wg_rs_n192<HI_SW128>(aq, xn[k][0], xn[k][1], xn[k][2], xn[k][3], bdesc + s * (QST >> 4) + k * 128);
          wg_rs_n24<HI_R>(ar, xn[k][0], xn[k][1], xn[k][2], xn[k][3], rdesc + s * (QST >> 4) + k * 16);
        }
        wg_commit();
#pragma unroll
        for (int k = 0; k < 4; k++) stsm4(ra[k] + kb * 16384, xn[k][0], xn[k][1], xn[k][2], xn[k][3]);
#pragma unroll
        for (int k = 0; k < 4; k++) ldsm4(v[k], ra[k] + (kb < 8 ? kb + 1 : 8) * 16384);
        if (kb == 8) {
          asm volatile("fence.proxy.async.shared::cta;" ::: "memory");
          __syncwarp();
          mbar_arrive_if(bar + 8 * B_NR + 8 * wg, l0);
        }
        wg_wait<0>();
        mbar_arrive_if(bar + 8 * B_QE + 8 * s, l0);
        if (++s == 3) { s = 0; ph ^= 1; }
      }
      pin<96>(aq); pin<12>(ar);
      STAMP(2);
      uint32_t* kvp = g_KV + (size_t)(4 * j) * SEQ * 20 + (16 * m + 2 * wr) * 160 + lane;
      uint32_t pk[2][9][2];
#pragma unroll
      for (int p = 0; p < 2; p++)
#pragma unroll
        for (int i = 0; i < 9; i++) {
          const float* src = i < 8 ? &aq[(8 * (p + 1) + i) * 4] : &ar[4 * (p + 1)];
          pk[p][i][0] = pack(src[0], src[1]); pk[p][i][1] = pack(src[2], src[3]);
        }
      const uint32_t sk = sb + SM_KV + wg * KVST + (wr & 3) * 768 + lane * 4;
      mbar_wait(bar + 8 * (B_QE + 2), 0);
      if (hx) {
#pragma unroll
        for (int p = 0; p < 2; p++) { rotate9(pk[p]); }
        store_kv_head<3>(pk, kvp, lane, sk, sk + KVST + 3072);
      } else store_kv_head<0>(pk, kvp, lane, sk, sk + KVST + 3072);
      asm volatile("fence.proxy.async.shared::cta;" ::: "memory");
      __syncwarp();
      mbar_arrive_if(bar + 8 * B_SK1, l0);
      mbar_arrive_if(bar + 8 * B_LK, l0);
      STAMP(3);
      mbar_wait(bar + 8 * B_NR + 8 * wg, 0);
      mbar_wait(bar + 8 * B_F, 0);
      wg_fence();
      G1_ISSUE_Z(accA, bdesc)
      wg_commit();
      RELEASE()
      NEXT_SLOT()
      mbar_wait(F_BAR, F_PH);
      wg_fence();
      G1_ISSUE(accA, adesc + 1024, bdesc + 1024)
      wg_commit();
      uint32_t pq[9][2];
#pragma unroll
      for (int i = 0; i < 9; i++) {
        const float* src = i < 8 ? &aq[i * 4] : &ar[0];
        pq[i][0] = bscale2(pack(src[0], src[1]), QS_HI, QS_LO); pq[i][1] = bscale2(pack(src[2], src[3]), QS_HI, QS_LO);
      }
      if (hx) rotate9(pq);
      pin<18>(&pq[0][0]);
      wg_wait<1>();
      RELEASE()
      NEXT_SLOT()
      G1_ONLY()
      mbar_wait(F_BAR, F_PH);
      wg_fence();
      G1_ISSUE(accA, adesc + 3 * 1024, bdesc + 3 * 1024)
      wg_commit();
      if (hx) store_kv_head<0>(pk, kvp, lane); else store_kv_head<3>(pk, kvp, lane);
      store_kv_head<1>(pk, kvp, lane);
      store_kv_head<2>(pk, kvp, lane);
      __syncwarp();
      mbar_arrive_if(bar + 8 * B_SK2, l0);
      wg_wait<1>();
      RELEASE()
      NEXT_SLOT()
      mbar_wait(F_BAR, F_PH);
      wg_fence();
      G1_ISSUE(accA, adesc + 4 * 1024, bdesc)
      wg_commit();
      uint4* qp = reinterpret_cast<uint4*>(g_Q) + cta * 4 * 512 + tid;
#pragma unroll
      for (int hp = 0; hp < 4; hp++) {
        const bool up = t < hp;
        const uint4 u = make_uint4(up ? pq[2 * hp + 1][0] : pq[2 * hp][0], up ? pq[2 * hp + 1][1] : pq[2 * hp][1],
                                   up ? pq[2 * hp + 2][0] : pq[2 * hp + 1][0], up ? pq[2 * hp + 2][1] : pq[2 * hp + 1][1]);
        const uint4 v = make_uint4(t == hp ? pq[2 * hp + 2][0] : 0u, t == hp ? pq[2 * hp + 2][1] : 0u, 0u, 0u);
        qp[hp * 512] = u; qp[hp * 512 + 256] = v;
        if (hp == 0 || (hp == 3 && hx)) { a.q[0] = u.x; a.q[1] = u.y; a.q[2] = u.z; a.q[3] = u.w; a.q[4] = v.x; a.q[5] = v.y; }
      }
      a.q[6] = __shfl_sync(0xffffffffu, lane, 0); a.q[7] = __shfl_sync(0xffffffffu, lane >> 1, 1);
#pragma unroll
      for (int i = 0; i < 16; i++) a.p[i] = 0;
#pragma unroll
      for (int i = 0; i < 12; i++) a.o[i] = 0.f;
      pin<16>(a.p); pin<12>(a.o); pin<8>(a.q);
      wg_wait<1>();
      RELEASE()
      NEXT_SLOT()
    }
    static_assert(NG0 == 5 || NG0 == 7, "item boundaries must fall into even F tiles / even GEMM2 slots");
#pragma unroll 1
    while (gs < NG0) G1_ONLY()
    STAMP(4);
    mbar_wait(bar + 8 * B_LK, 0);
    mbar_wait(F_BAR, F_PH);
    STAMP(23);
    uint32_t kd = kdesc0;
    uint32_t it = 0;
    uint32_t ox0 = 0, ox1 = 0;
    uint32_t qn[6] = {0, 0, 0, 0, 0, 0};
    uint32_t* hdst = g_H + ((m * 576 + 72 * j + (t >> 1)) * 128 + 16 * wr + (lane >> 2)) * 4 + 2 * (t & 1);
    uint32_t ad = adesc + NG0 * 1024, bd = bdesc + (gs & 3) * 1024;

#define ITEM_FIRST()                                                                                           \
  {                                                                                                            \
    pin<12>(a.o);                                                                                              \
    if (it != 0) {                                                                                             \
      uint32_t w[4];                                                                                           \
      o_normalise(a.o, w, ox0, ox1, ((it >> 5) - 1) ^ hx, lane, sb + SM_BAD, wr);                              \
      uint32_t* d = g_O + cta * 9 * 512 + (((it >> 5) - 1) ^ hx) * 1024 + wr * 64 + lane;                      \
      d[0] = w[0]; d[32] = w[1]; d[512] = w[2]; d[544] = w[3];                                                 \
    }                                                                                                          \
    if (it == 96) mbar_arrive_if(bar + 8 * B_SO1, l0 & (bad_heads(sb + SM_BAD, wr) == 0));                     \
    first_tile(a, (it >> 5) ^ hx, lane);                                                                       \
  }
#define KV_ADVANCE() { kd = kd == kdesc0 + 768 ? kdesc0 : kd + 384; }
#define SOFTMAX_NEXT() { softmax_a(a); softmax_b(a); mbar_wait(F_BAR, F_PH); softmax_c(a); }
#define EPI_STEP(ACCN, ACCO)                                                                                   \
  {                                                                                                            \
    wg_fence();                                                                                                \
    G1_ISSUE_Z(ACCN, bd)                                                                                       \
    wg_commit();                                                                                               \
    wg_wait<1>();                                                                                              \
    pin<64>(ACCO);                                                                                             \
    RELEASE()                                                                                                  \
    NEXT_SLOT()                                                                                                \
    ad = adesc + 1024; NEXT_B()                                                                                \
    const uint32_t ok = mbar_test(F_BAR, F_PH);                                                                \
    h_epilogue(ACCO, hdst);                                                                                    \
    hdst += 4096;                                                                                              \
    __syncwarp();                                                                                              \
    mbar_arrive_if(bar + 8 * B_SH, l0);                                                                        \
    if (__builtin_expect(!ok, 0)) mbar_wait(F_BAR, F_PH);                                                                                            \
  }
#define ATT_LOOP1(ACC, ITEMS)                                                                                  \
  do {                                                                                                         \
    wg_fence();                                                                                                \
    issue_att(a, kd);                                                                                          \
    wg_commit();                                                                                               \
    G1_ISSUE(ACC, ad, bd)                                                                                      \
    wg_commit();                                                                                               \
    wg_wait<1>();                                                                                              \
    pin<32>(a.s);                                                                                              \
    RELEASE()                                                                                                  \
    TRACE()                                                                                                    \
    if (ITEMS) { if (__builtin_expect(((it + 1) & 31) < 2, 0)) { if (it & 1) { _Pragma("unroll") for (int i = 0; i < 6; i++) asm volatile("mov.b32 %0, %1;" : "=r"(a.q[i]) : "r"(qn[i])); } else { if (it == 64) fetch_q(qn, cta, 3 ^ hx, tid); ITEM_FIRST() } } } \
    NEXT_SLOT() it++;                                                                                                \
    KV_ADVANCE()                                                                                               \
    ad += 1024; NEXT_B()                                                                                       \
    SOFTMAX_NEXT()                                                                                             \
    pin<8>(a.q);                                                                                               \
  } while (ad != adesc + 9 * 1024);
#pragma unroll 1
    for (int pr = 0;; pr++) {
      ATT_LOOP1(accA, true)
      if (pr == 4) break;
      if (pr == 2) STAMP(29);
      EPI_STEP(accB, accA)
      if (pr == 2) STAMP(30);
      ATT_LOOP1(accB, false)
      if (pr == 2) STAMP(31);
      if (pr & 1) fetch_q(qn, cta, ((pr >> 1) + 1) ^ hx, tid);
      EPI_STEP(accA, accB)
      if (pr == 2) STAMP(21);
      if (pr == 3) STAMP(14);
    }
    STAMP(5);
    wg_wait<0>();
    pin<64>(accA);
    h_epilogue(accA, hdst);
    __syncwarp();
    mbar_arrive_if(bar + 8 * B_SH, l0);
    mbar_wait(bar + 8 * B_E, 0);
    asm volatile("st.shared.v4.b32 [%0], {%1,%2,%3,%4};\nst.shared.v2.b32 [%5], {%6,%7};" ::"r"(sb + SM_QS + tid * 16), "r"(qn[0]), "r"(qn[1]), "r"(qn[2]), "r"(qn[3]),
                 "r"(sb + SM_QS + 4096 + tid * 8), "r"(qn[4]), "r"(qn[5]) : "memory");
    STAMP(6);
    STAMP(12);

    float acc2[144];
    const uint32_t a2desc = (((sb + wg * 1024) & 0x3FFFF) >> 4) | LO_O;
    const uint32_t b2desc = (((sb + 12288) & 0x3FFFF) >> 4) | LO_B48;
    ad = a2desc; bd = b2desc;
#define G2_LO(K) wg_ss_n128<HI_O, HI_SW128>(acc2, ad + (K) * 256, bd + (K) * 128);
#define G2_HI(K) wg_ss_n160<HI_O, HI_SW128>(acc2 + 64, ad + (K) * 256, bd + (K) * 128 + 768);
#define ATT_PAIR(ZERO)                                                                                         \
  {                                                                                                            \
    wg_fence();                                                                                                \
    issue_att(a, kd);                                                                                          \
    wg_commit();                                                                                               \
    if (ZERO) { wg_ss_z_n128<HI_O, HI_SW128>(acc2, ad, bd); wg_ss_z_n160<HI_O, HI_SW128>(acc2 + 64, ad, bd + 768); } \
    else { G2_LO(0) G2_HI(0) }                                                                                 \
    G2_LO(1)                                                                                                   \
    wg_commit();                                                                                               \
    wg_wait<1>();                                                                                              \
    pin<32>(a.s);                                                                                              \
    RELEASE()                                                                                                  \
    TRACE()                                                                                                    \
    if (!(ZERO)) { if (__builtin_expect(gs == N_G2 + 96 - IT_G2, 0)) ITEM_FIRST() }                                    \
    NEXT_SLOT() it++;                                                                                                \
    KV_ADVANCE()                                                                                               \
    SOFTMAX_NEXT()                                                                                             \
    pin<8>(a.q);                                                                                               \
    wg_fence();                                                                                                \
    issue_att(a, kd);                                                                                          \
    wg_commit();                                                                                               \
    G2_HI(1) G2_LO(2) G2_HI(2)                                                                                 \
    wg_commit();                                                                                               \
    wg_wait<1>();                                                                                              \
    pin<32>(a.s);                                                                                              \
    RELEASE()                                                                                                  \
    TRACE()                                                                                                    \
    if (!(ZERO) && __builtin_expect(gs == N_G2 + 95 - IT_G2, 0)) {                                                     \
      const int ft = fresh_tid();                                                                              \
      asm volatile("ld.shared.v4.b32 {%0,%1,%2,%3}, [%6];\nld.shared.v2.b32 {%4,%5}, [%7];" : "=r"(a.q[0]), "=r"(a.q[1]), "=r"(a.q[2]), "=r"(a.q[3]), \
                   "=r"(a.q[4]), "=r"(a.q[5]) : "r"(sb + SM_QS + ft * 16), "r"(sb + SM_QS + 4096 + ft * 8) : "memory"); \
    }                                                                                                          \
    NEXT_SLOT() it++;                                                                                                \
    KV_ADVANCE()                                                                                               \
    ad = ad == a2desc + 3 * 2688 ? a2desc : ad + 2688; bd = ad + (b2desc - a2desc);                                \
    SOFTMAX_NEXT()                                                                                             \
    pin<8>(a.q);                                                                                               \
  }
    ATT_PAIR(true)
#pragma unroll 1
    for (int half = 0; half < 2; half++) {
      const uint32_t stop = half ? N_AO : N_G2 + 46;
      do ATT_PAIR(false) while (gs != stop);
      if (!half) {
        const uint32_t bad = bad_heads(sb + SM_BAD, wr);
        if (bad) { repair_rows(cta, wr, bad, 3 ^ hx, false); mbar_arrive_if(bar + 8 * B_SO1, l0); }
      }
    }
    STAMP(13);
    wg_wait<0>();
    pin<144>(acc2);
    mbar_wait(bar + 8 * (B_E + 1), 0);
    stage_partials(acc2, sb + SM_SEND, fresh_tid());
    asm volatile("fence.proxy.async.shared::cta;" ::: "memory");
    __syncwarp();
    mbar_arrive_if(bar + 8 * B_SP, l0);
    do {
      wg_fence();
      issue_att(a, kd);
      wg_commit();
      wg_wait<0>();
      pin<32>(a.s);
      RELEASE()
      TRACE()
      NEXT_SLOT() it++;
      KV_ADVANCE()
      SOFTMAX_NEXT()
    } while (gs != N_END);
    STAMP(7);
    wg_fence();
    issue_pv(a, kd);
    wg_commit();
    int tid2, bid2;
    asm volatile("mov.u32 %0, %%tid.x;" : "=r"(tid2));
    asm volatile("mov.u32 %0, %%ctaid.x;" : "=r"(bid2));
    const int m2 = bid2 & 15, j2 = bid2 >> 4;
    uint32_t tag;
    asm volatile("ld.shared.u32 %0, [%1];" : "=r"(tag) : "r"(sb + SM_TAG) : "memory");
    wg_wait<0>();
    pin<12>(a.o);
    {
      uint32_t w[4];
      o_normalise(a.o, w, ox0, ox1, 3 ^ hx, lane, sb + SM_BAD, wr);
      ox0 = __shfl_xor_sync(0xffffffffu, ox0, 2); ox1 = __shfl_xor_sync(0xffffffffu, ox1, 2);
      const uint32_t bad = bad_heads(sb + SM_BAD, wr);
      if (bad) {
        uint32_t* d = g_O + cta * 9 * 512 + wr * 64 + lane;
        uint32_t* h = d + (3 ^ hx) * 1024;
        h[0] = w[0]; h[32] = w[1]; h[512] = w[2]; h[544] = w[3]; d[4096] = ox0; d[4128] = ox1;
        __syncwarp();
        repair_rows(cta, wr, bad, 3 ^ hx, true);
        w[0] = __ldcg(h); w[1] = __ldcg(h + 32); w[2] = __ldcg(h + 512); w[3] = __ldcg(h + 544); ox0 = __ldcg(d + 4096); ox1 = __ldcg(d + 4128);
      }
      asm volatile("st.relaxed.gpu.global.v4.b32 [%0], {%1,%2,%3,%4};" ::"l"(g_L + (m2 * 8 + j2) * 384 + tid2), "r"((w[0] & ~1u) | tag), "r"((w[1] & ~1u) | tag),
                   "r"((w[2] & ~1u) | tag), "r"((w[3] & ~1u) | tag) : "memory");
      asm volatile("st.relaxed.gpu.global.v2.b32 [%0], {%1,%2};" ::"l"(reinterpret_cast<uint2*>(g_L + (m2 * 8 + j2) * 384 + 256) + tid2), "r"((ox0 & ~1u) | tag),
                   "r"((ox1 & ~1u) | tag) : "memory");
    }
    STAMP(8);
    uint32_t la[48];
    const uint4* p4 = g_L + m2 * 8 * 384 + tid2;
    const uint2* p2 = reinterpret_cast<const uint2*>(g_L + m2 * 8 * 384 + 256) + tid2;
#define LOAD_LA2() { ld2<0>(la + 32, p2); ld2<6144>(la + 34, p2); ld2<12288>(la + 36, p2); ld2<18432>(la + 38, p2); \
                     ld2<24576>(la + 40, p2); ld2<30720>(la + 42, p2); ld2<36864>(la + 44, p2); ld2<43008>(la + 46, p2); }
#define LOAD_LA4() { ld4<0>(la, p4); ld4<6144>(la + 4, p4); ld4<12288>(la + 8, p4); ld4<18432>(la + 12, p4); \
                     ld4<24576>(la + 16, p4); ld4<30720>(la + 20, p4); ld4<36864>(la + 24, p4); ld4<43008>(la + 28, p4); }
    float fin[48];
    uint32_t id[4][4];
    {
      uint32_t id2[4][4];
#pragma unroll
      for (int k = 0; k < 4; k++) {
        asm volatile("ld.volatile.shared.v4.b32 {%0,%1,%2,%3}, [%4];" : "=r"(id[k][0]), "=r"(id[k][1]), "=r"(id[k][2]), "=r"(id[k][3])
                     : "r"(sb + SM_ID + ((wr & 3) == k ? lane : 1) * 16) : "memory");
#pragma unroll
        for (int e = 0; e < 4; e++) id2[k][e] = id[k][e] + (id[k][e] & 0x00800080u);
      }
      pin<16>(&id[0][0]); pin<16>(&id2[0][0]);
      const uint32_t xdesc = (((sb + SM_RES + wg * 8192) & 0x3FFFF) >> 4) | LO_B;
      STAMP(26);
      mbar_wait(bar + 8 * B_OL, 0);
      STAMP(27);
      wg_fence();
      wg_rsb_z_n64<HI_SW128>(fin, id2[0][0], id2[0][1], id2[0][2], id2[0][3], xdesc);
      wg_rs_z_n32<HI_SW128>(fin + 32, id2[0][0], id2[0][1], id2[0][2], id2[0][3], xdesc + 1024);
#pragma unroll
      for (int k = 1; k < 4; k++) {
        wg_rsb_n64<HI_SW128>(fin, id2[k][0], id2[k][1], id2[k][2], id2[k][3], xdesc + k * 128);
        wg_rs_n32<HI_SW128>(fin + 32, id2[k][0], id2[k][1], id2[k][2], id2[k][3], xdesc + 1024 + k * 128);
      }
      wg_commit();
    }
    STAMP(28);
    const uint32_t pdesc = (((sb + SM_RECV + wg * 8192) & 0x3FFFF) >> 4) | LO_B, hdesc = (((sb + SM_RECV + 16384 + wg * 4096) & 0x3FFFF) >> 4) | LO_B;
#define RX_MMAS()                                                                                              \
  wg_fence();                                                                                                  \
  _Pragma("unroll") for (int a3 = 0; a3 < 3; a3++)                                                             \
    _Pragma("unroll") for (int k = 0; k < 4; k++) {                                                            \
      wg_rsb_n64<HI_SW128>(fin, id[k][0], id[k][1], id[k][2], id[k][3], pdesc + a3 * 1536 + k * 128);          \
      wg_rs_n32<HI_SW64>(fin + 32, id[k][0], id[k][1], id[k][2], id[k][3], hdesc + a3 * 1536 + k * 64);        \
    }                                                                                                          \
  wg_commit();
    mbar_wait(bar + 8 * B_RX, 0);
    STAMP(24);
    RX_MMAS()
    wg_wait<0>();
    pin<48>(fin);
#pragma unroll
    for (int i = 0; i < 48; i++) fin[i] += acc2[96 + i];
    pin<48>(fin);
    for (uint32_t tries = 0; tries < 0x400000u; tries++) {
      const uint32_t* pw = reinterpret_cast<const uint32_t*>(g_L + (m2 * 8 + (lane & 7)) * 384 + 256) + (tid2 | 31) * 2 + 1;
      uint32_t bad;
      do {
        asm volatile("ld.relaxed.gpu.global.b32 %0, [%1];" : "=r"(bad) : "l"(pw) : "memory");
      } while (!__all_sync(0xffffffffu, !((bad ^ tag) & 1)) && ++tries < 0x400000u);
      LOAD_LA4()
      LOAD_LA2()
      bad = 0;
#pragma unroll
      for (int i = 0; i < 48; i++) bad |= la[i] ^ tag;
      if (__all_sync(0xffffffffu, !(bad & 1))) break;
    }
#pragma unroll
    for (int i = 0; i < 48; i++) la[i] ^= tag;
    pin<48>(la);
    STAMP(19);
    const uint32_t ldesc = (((sb + SM_LB) & 0x3FFFF) >> 4) | LO_B;
    wg_fence();
#pragma unroll
    for (int k = 0; k < 12; k++) {
      wg_rsb_n64<HI_SW128>(fin, la[4 * k], la[4 * k + 1], la[4 * k + 2], la[4 * k + 3], ldesc + k * 128);
      wg_rs_n32<HI_SW128>(fin + 32, la[4 * k], la[4 * k + 1], la[4 * k + 2], la[4 * k + 3], ldesc + 1536 + k * 128);
    }
    wg_commit();
    wg_wait<0>();
    pin<48>(fin);
    STAMP(9);
    final_epilogue(fin, prm, m2, j2 & 1, j2 >> 1, tid2);
    STAMP(10);
  }
}

typedef CUresult (*EncodeFn)(CUtensorMap*, CUtensorMapDataType, cuuint32_t, void*, const cuuint64_t*, const cuuint64_t*, const cuuint32_t*, const cuuint32_t*,
                             CUtensorMapInterleave, CUtensorMapSwizzle, CUtensorMapL2promotion, CUtensorMapFloatOOBfill);

void enc2d(EncodeFn enc, CUtensorMap* tm, const void* base, uint64_t w, uint64_t h, uint64_t pitch_elems, uint32_t bw, uint32_t bh, CUtensorMapSwizzle sw) {
  cuuint64_t dims[2] = {w, h}, str[1] = {pitch_elems * 2};
  cuuint32_t box[2] = {bw, bh}, es[2] = {1, 1};
  enc(tm, CU_TENSOR_MAP_DATA_TYPE_BFLOAT16, 2, const_cast<void*>(base), dims, str, box, es, CU_TENSOR_MAP_INTERLEAVE_NONE, sw,
      CU_TENSOR_MAP_L2_PROMOTION_L2_128B, CU_TENSOR_MAP_FLOAT_OOB_FILL_NONE);
}

}

extern "C" void kernel_launch(void* const* d_in, const int* in_sizes, int n_in, void* d_out, int out_size) {
  (void)in_sizes; (void)n_in; (void)out_size;
  const __nv_bfloat16* x = (const __nv_bfloat16*)d_in[0];
  const __nv_bfloat16* wqkv = (const __nv_bfloat16*)d_in[1];
  const __nv_bfloat16* wo = (const __nv_bfloat16*)d_in[2];
  const __nv_bfloat16* wg = (const __nv_bfloat16*)d_in[4];
  const __nv_bfloat16* wu = (const __nv_bfloat16*)d_in[5];
  const __nv_bfloat16* wd = (const __nv_bfloat16*)d_in[6];
  void* fn = nullptr;
  cudaDriverEntryPointQueryResult qr;
  cudaGetDriverEntryPoint("cuTensorMapEncodeTiled", &fn, cudaEnableDefault, &qr);
  EncodeFn enc = (EncodeFn)fn;
  void* kvp = nullptr;
  cudaGetSymbolAddress(&kvp, g_KV);
  Params p;
  enc2d(enc, &p.xm, x, DM, SEQ, DM, 64, 128, CU_TENSOR_MAP_SWIZZLE_128B);
  enc2d(enc, &p.kv, kvp, 320, 32 * 256, 320, 192, 8, CU_TENSOR_MAP_SWIZZLE_NONE);
  enc2d(enc, &p.wqkv64, wqkv, 3 * DM, DM, 3 * DM, 64, 64, CU_TENSOR_MAP_SWIZZLE_128B);
  enc2d(enc, &p.wqkv8, wqkv, 3 * DM, DM, 3 * DM, 8, 64, CU_TENSOR_MAP_SWIZZLE_NONE);
  enc2d(enc, &p.wg, wg, FF, DM, FF, 64, 64, CU_TENSOR_MAP_SWIZZLE_128B);
  enc2d(enc, &p.wu, wu, FF, DM, FF, 64, 64, CU_TENSOR_MAP_SWIZZLE_128B);
  for (int v = 0; v < 3; v++) {
    const cuuint64_t wdt = v ? 32 : DM;
    const int c0 = v ? 256 + 32 * (v - 1) : 0;
    for (int e = 0; e < 3; e++) {
      cuuint64_t d3[3] = {wdt, e == 2 ? 2u : 16u, 32}, s3[2] = {DM * 2, 18 * DM * 2};
      cuuint32_t b3[3] = {64, e == 2 ? 2u : 16u, e == 0 ? 3u : e == 1 ? 2u : 8u}, e3[3] = {1, 1, 1};
      enc(e == 0 ? &p.wo3[v] : e == 1 ? &p.wo2[v] : &p.wo16[v], CU_TENSOR_MAP_DATA_TYPE_BFLOAT16, 3, (void*)(wo + c0 + (e == 2 ? 16 * DM : 0)), d3, s3, b3, e3,
          CU_TENSOR_MAP_INTERLEAVE_NONE, CU_TENSOR_MAP_SWIZZLE_128B, CU_TENSOR_MAP_L2_PROMOTION_L2_128B, CU_TENSOR_MAP_FLOAT_OOB_FILL_NONE);
    }
    cuuint64_t dims[5] = {wdt, 2, 2, 4, FF / 16}, str[4] = {DM * 2, 8 * DM * 2, 2 * DM * 2, 16 * DM * 2};
    cuuint32_t box[5] = {64, 2, 2, 4, 3}, es[5] = {1, 1, 1, 1, 1};
    enc(&p.wd[v], CU_TENSOR_MAP_DATA_TYPE_BFLOAT16, 5, (void*)(wd + c0), dims, str, box, es, CU_TENSOR_MAP_INTERLEAVE_NONE,
        CU_TENSOR_MAP_SWIZZLE_128B, CU_TENSOR_MAP_L2_PROMOTION_L2_128B, CU_TENSOR_MAP_FLOAT_OOB_FILL_NONE);
  }
  p.x = x; p.pwqkv = wqkv; p.pwo = wo; p.pwg = wg; p.pwu = wu; p.pwd = wd;
  p.out = (__nv_bfloat16*)d_out;
  cudaFuncSetAttribute(fused_kernel, cudaFuncAttributeMaxDynamicSharedMemorySize, SM_TOTAL);
  fused_kernel<<<NCTA, 384, SM_TOTAL, cudaStreamPerThread>>>(p);
}
```

```cpp
#include <cuda_runtime.h>
#include <cuda.h>
#include <cuda_bf16.h>
#include <stdint.h>

namespace {

constexpr int SEQ = 2048, DM = 576, FF = 4608;
constexpr int NCTA = 128;

constexpr uint32_t SM_XN = 0;
constexpr uint32_t SM_RING = 147456;
constexpr uint32_t SM_KV = 212992;
constexpr uint32_t QST = 27648, BST = 16384, KVST = 6144;
constexpr uint32_t G2ST = 43008;
constexpr uint32_t SM_LB = 0, SM_RES = 49152, SM_SEND = 86016, SM_RECV = SM_SEND;
constexpr uint32_t SM_QS = 204800;
constexpr uint32_t SM_KV2 = SM_KV - 6 * KVST;
constexpr uint32_t SM_ID = 231424;
constexpr uint32_t SM_BAR = 231936;
constexpr uint32_t SM_TAG = 232436;
constexpr uint32_t SM_BAD = 232432;
constexpr uint32_t SM_TOTAL = 232448;
enum { B_F = 0, B_E = 8, B_QF = 16, B_QE = 19, B_SK1 = 22, B_SK2 = 23, B_SH = 24, B_SO1 = 25, B_LK = 26, B_SP = 27, B_OL = 28, B_RX = 29, B_NR = 30, B_X = 32, B_N = 41 };
constexpr int N_G2 = 81, N_AO = 133;
#define N_END (136 + NG0)
#define IT_G2 (73 - NG0)
#define SM_A 7
#define SM_B 12
#define CONST_SB 1
#define PF_Q 6
constexpr int PF_G1 = 1;
#define NG0_ 5
constexpr int NG0 = NG0_;

constexpr uint32_t HI_SW128 = 0x40000040u;
constexpr uint32_t LO_A = 1u << 16;
constexpr uint32_t LO_B = 512u << 16;
constexpr uint32_t HI_R = 64u, LO_R = 8u << 16;
constexpr uint32_t HI_K = 24u, LO_K = 8u << 16;
constexpr uint32_t HI_V = 8u, LO_V = 24u << 16;
constexpr uint32_t LO_B48 = 384u << 16;
constexpr uint32_t HI_O = 8u, LO_O = 128u << 16;
constexpr uint32_t HI_SW64 = 0x80000020u;

constexpr uint32_t QS_HI = 0x3eae3eaeu, QS_LO = 0x39553955u;
constexpr float MOFF = 90.f;

struct __align__(64) Params {
  CUtensorMap xm, wqkv64, wqkv8, wg, wu, kv, wd[3], wo3[3], wo2[3], wo16[3];
  const __nv_bfloat16 *x, *pwqkv, *pwo, *pwg, *pwu, *pwd;
  __nv_bfloat16* out;
};

__device__ __align__(1024) uint32_t g_H[16 * 576 * 512];
__device__ __align__(1024) uint32_t g_O[NCTA * 9 * 512];
__device__ __align__(1024) uint32_t g_KV[32 * SEQ * 20];
__device__ __align__(1024) uint32_t g_Q[NCTA * 4 * 256 * 8];
__device__ __align__(1024) uint4 g_P[NCTA * 3584];
__device__ __align__(1024) uint4 g_L[NCTA * 384];
__device__ float g_S[NCTA * 8 * SEQ];
__device__ uint32_t g_flags[16 * 32 + NCTA * 32 * 4];
#define FLAG_KV(l, j) (&g_flags[((l) * 8 + (j)) * 32])
#define FLAG_H(c) (&g_flags[16 * 32 + (c) * 32])
#define FLAG_O(c) (&g_flags[16 * 32 + NCTA * 32 + (c) * 32])
#define FLAG_P(c) (&g_flags[16 * 32 + NCTA * 64 + (c) * 32])
#define FLAG_EPOCH(c) (&g_flags[16 * 32 + NCTA * 96 + (c) * 32])
#define STAMP(i)
#define STAMPW(i)
#define TRACE()

template<uint32_t BHI> __device__ __forceinline__ void wg_rs_n192(float* d, uint32_t a0, uint32_t a1, uint32_t a2, uint32_t a3, uint32_t b) {
  asm volatile("{\n.reg .pred p;\n.reg .b64 db;\nsetp.ne.b32 p, 1, 0;\nmov.b64 db, {%100, %101};\n"
    "wgmma.mma_async.sync.aligned.m64n192k16.f32.bf16.bf16 {%0, %1, %2, %3, %4, %5, %6, %7, %8, %9, %10, %11, %12, %13, %14, %15, %16, %17, %18, %19, %20, %21, %22, %23, %24, %25, %26, %27, %28, %29, %30, %31, %32, %33, %34, %35, %36, %37, %38, %39, %40, %41, %42, %43, %44, %45, %46, %47, %48, %49, %50, %51, %52, %53, %54, %55, %56, %57, %58, %59, %60, %61, %62, %63, %64, %65, %66, %67, %68, %69, %70, %71, %72, %73, %74, %75, %76, %77, %78, %79, %80, %81, %82, %83, %84, %85, %86, %87, %88, %89, %90, %91, %92, %93, %94, %95}, {%96, %97, %98, %99}, db, p, 1, 1, 1;\n}\n"
    : "+f"(d[0]), "+f"(d[1]), "+f"(d[2]), "+f"(d[3]), "+f"(d[4]), "+f"(d[5]), "+f"(d[6]), "+f"(d[7]), "+f"(d[8]), "+f"(d[9]), "+f"(d[10]), "+f"(d[11]), "+f"(d[12]), "+f"(d[13]), "+f"(d[14]), "+f"(d[15]), "+f"(d[16]), "+f"(d[17]), "+f"(d[18]), "+f"(d[19]), "+f"(d[20]), "+f"(d[21]), "+f"(d[22]), "+f"(d[23]), "+f"(d[24]), "+f"(d[25]), "+f"(d[26]), "+f"(d[27]), "+f"(d[28]), "+f"(d[29]), "+f"(d[30]), "+f"(d[31]), "+f"(d[32]), "+f"(d[33]), "+f"(d[34]), "+f"(d[35]), "+f"(d[36]), "+f"(d[37]), "+f"(d[38]), "+f"(d[39]), "+f"(d[40]), "+f"(d[41]), "+f"(d[42]), "+f"(d[43]), "+f"(d[44]), "+f"(d[45]), "+f"(d[46]), "+f"(d[47]), "+f"(d[48]), "+f"(d[49]), "+f"(d[50]), "+f"(d[51]), "+f"(d[52]), "+f"(d[53]), "+f"(d[54]), "+f"(d[55]), "+f"(d[56]), "+f"(d[57]), "+f"(d[58]), "+f"(d[59]), "+f"(d[60]), "+f"(d[61]), "+f"(d[62]), "+f"(d[63]), "+f"(d[64]), "+f"(d[65]), "+f"(d[66]), "+f"(d[67]), "+f"(d[68]), "+f"(d[69]), "+f"(d[70]), "+f"(d[71]), "+f"(d[72]), "+f"(d[73]), "+f"(d[74]), "+f"(d[75]), "+f"(d[76]), "+f"(d[77]), "+f"(d[78]), "+f"(d[79]), "+f"(d[80]), "+f"(d[81]), "+f"(d[82]), "+f"(d[83]), "+f"(d[84]), "+f"(d[85]), "+f"(d[86]), "+f"(d[87]), "+f"(d[88]), "+f"(d[89]), "+f"(d[90]), "+f"(d[91]), "+f"(d[92]), "+f"(d[93]), "+f"(d[94]), "+f"(d[95])
    : "r"(a0), "r"(a1), "r"(a2), "r"(a3), "r"(b), "n"(BHI));
}
template<uint32_t BHI> __device__ __forceinline__ void wg_rs_z_n192(float* d, uint32_t a0, uint32_t a1, uint32_t a2, uint32_t a3, uint32_t b) {
  asm volatile("{\n.reg .pred p;\n.reg .b64 db;\nsetp.ne.b32 p, 0, 0;\nmov.b64 db, {%100, %101};\n"
    "wgmma.mma_async.sync.aligned.m64n192k16.f32.bf16.bf16 {%0, %1, %2, %3, %4, %5, %6, %7, %8, %9, %10, %11, %12, %13, %14, %15, %16, %17, %18, %19, %20, %21, %22, %23, %24, %25, %26, %27, %28, %29, %30, %31, %32, %33, %34, %35, %36, %37, %38, %39, %40, %41, %42, %43, %44, %45, %46, %47, %48, %49, %50, %51, %52, %53, %54, %55, %56, %57, %58, %59, %60, %61, %62, %63, %64, %65, %66, %67, %68, %69, %70, %71, %72, %73, %74, %75, %76, %77, %78, %79, %80, %81, %82, %83, %84, %85, %86, %87, %88, %89, %90, %91, %92, %93, %94, %95}, {%96, %97, %98, %99}, db, p, 1, 1, 1;\n}\n"
    : "=f"(d[0]), "=f"(d[1]), "=f"(d[2]), "=f"(d[3]), "=f"(d[4]), "=f"(d[5]), "=f"(d[6]), "=f"(d[7]), "=f"(d[8]), "=f"(d[9]), "=f"(d[10]), "=f"(d[11]), "=f"(d[12]), "=f"(d[13]), "=f"(d[14]), "=f"(d[15]), "=f"(d[16]), "=f"(d[17]), "=f"(d[18]), "=f"(d[19]), "=f"(d[20]), "=f"(d[21]), "=f"(d[22]), "=f"(d[23]), "=f"(d[24]), "=f"(d[25]), "=f"(d[26]), "=f"(d[27]), "=f"(d[28]), "=f"(d[29]), "=f"(d[30]), "=f"(d[31]), "=f"(d[32]), "=f"(d[33]), "=f"(d[34]), "=f"(d[35]), "=f"(d[36]), "=f"(d[37]), "=f"(d[38]), "=f"(d[39]), "=f"(d[40]), "=f"(d[41]), "=f"(d[42]), "=f"(d[43]), "=f"(d[44]), "=f"(d[45]), "=f"(d[46]), "=f"(d[47]), "=f"(d[48]), "=f"(d[49]), "=f"(d[50]), "=f"(d[51]), "=f"(d[52]), "=f"(d[53]), "=f"(d[54]), "=f"(d[55]), "=f"(d[56]), "=f"(d[57]), "=f"(d[58]), "=f"(d[59]), "=f"(d[60]), "=f"(d[61]), "=f"(d[62]), "=f"(d[63]), "=f"(d[64]), "=f"(d[65]), "=f"(d[66]), "=f"(d[67]), "=f"(d[68]), "=f"(d[69]), "=f"(d[70]), "=f"(d[71]), "=f"(d[72]), "=f"(d[73]), "=f"(d[74]), "=f"(d[75]), "=f"(d[76]), "=f"(d[77]), "=f"(d[78]), "=f"(d[79]), "=f"(d[80]), "=f"(d[81]), "=f"(d[82]), "=f"(d[83]), "=f"(d[84]), "=f"(d[85]), "=f"(d[86]), "=f"(d[87]), "=f"(d[88]), "=f"(d[89]), "=f"(d[90]), "=f"(d[91]), "=f"(d[92]), "=f"(d[93]), "=f"(d[94]), "=f"(d[95])
    : "r"(a0), "r"(a1), "r"(a2), "r"(a3), "r"(b), "n"(BHI));
}
template<uint32_t AHI, uint32_t BHI> __device__ __forceinline__ void wg_ss_n128(float* d, uint32_t a, uint32_t b) {
  asm volatile("{\n.reg .pred p;\n.reg .b64 da, db;\nsetp.ne.b32 p, 1, 0;\nmov.b64 da, {%64, %66};\nmov.b64 db, {%65, %67};\n"
    "wgmma.mma_async.sync.aligned.m64n128k16.f32.bf16.bf16 {%0, %1, %2, %3, %4, %5, %6, %7, %8, %9, %10, %11, %12, %13, %14, %15, %16, %17, %18, %19, %20, %21, %22, %23, %24, %25, %26, %27, %28, %29, %30, %31, %32, %33, %34, %35, %36, %37, %38, %39, %40, %41, %42, %43, %44, %45, %46, %47, %48, %49, %50, %51, %52, %53, %54, %55, %56, %57, %58, %59, %60, %61, %62, %63}, da, db, p, 1, 1, 0, 1;\n}\n"
    : "+f"(d[0]), "+f"(d[1]), "+f"(d[2]), "+f"(d[3]), "+f"(d[4]), "+f"(d[5]), "+f"(d[6]), "+f"(d[7]), "+f"(d[8]), "+f"(d[9]), "+f"(d[10]), "+f"(d[11]), "+f"(d[12]), "+f"(d[13]), "+f"(d[14]), "+f"(d[15]), "+f"(d[16]), "+f"(d[17]), "+f"(d[18]), "+f"(d[19]), "+f"(d[20]), "+f"(d[21]), "+f"(d[22]), "+f"(d[23]), "+f"(d[24]), "+f"(d[25]), "+f"(d[26]), "+f"(d[27]), "+f"(d[28]), "+f"(d[29]), "+f"(d[30]), "+f"(d[31]), "+f"(d[32]), "+f"(d[33]), "+f"(d[34]), "+f"(d[35]), "+f"(d[36]), "+f"(d[37]), "+f"(d[38]), "+f"(d[39]), "+f"(d[40]), "+f"(d[41]), "+f"(d[42]), "+f"(d[43]), "+f"(d[44]), "+f"(d[45]), "+f"(d[46]), "+f"(d[47]), "+f"(d[48]), "+f"(d[49]), "+f"(d[50]), "+f"(d[51]), "+f"(d[52]), "+f"(d[53]), "+f"(d[54]), "+f"(d[55]), "+f"(d[56]), "+f"(d[57]), "+f"(d[58]), "+f"(d[59]), "+f"(d[60]), "+f"(d[61]), "+f"(d[62]), "+f"(d[63])
    : "r"(a), "r"(b), "n"(AHI), "n"(BHI));
}
template<uint32_t AHI, uint32_t BHI> __device__ __forceinline__ void wg_ss_z_n128(float* d, uint32_t a, uint32_t b) {
  asm volatile("{\n.reg .pred p;\n.reg .b64 da, db;\nsetp.ne.b32 p, 0, 0;\nmov.b64 da, {%64, %66};\nmov.b64 db, {%65, %67};\n"
    "wgmma.mma_async.sync.aligned.m64n128k16.f32.bf16.bf16 {%0, %1, %2, %3, %4, %5, %6, %7, %8, %9, %10, %11, %12, %13, %14, %15, %16, %17, %18, %19, %20, %21, %22, %23, %24, %25, %26, %27, %28, %29, %30, %31, %32, %33, %34, %35, %36, %37, %38, %39, %40, %41, %42, %43, %44, %45, %46, %47, %48, %49, %50, %51, %52, %53, %54, %55, %56, %57, %58, %59, %60, %61, %62, %63}, da, db, p, 1, 1, 0, 1;\n}\n"
    : "=f"(d[0]), "=f"(d[1]), "=f"(d[2]), "=f"(d[3]), "=f"(d[4]), "=f"(d[5]), "=f"(d[6]), "=f"(d[7]), "=f"(d[8]), "=f"(d[9]), "=f"(d[10]), "=f"(d[11]), "=f"(d[12]), "=f"(d[13]), "=f"(d[14]), "=f"(d[15]), "=f"(d[16]), "=f"(d[17]), "=f"(d[18]), "=f"(d[19]), "=f"(d[20]), "=f"(d[21]), "=f"(d[22]), "=f"(d[23]), "=f"(d[24]), "=f"(d[25]), "=f"(d[26]), "=f"(d[27]), "=f"(d[28]), "=f"(d[29]), "=f"(d[30]), "=f"(d[31]), "=f"(d[32]), "=f"(d[33]), "=f"(d[34]), "=f"(d[35]), "=f"(d[36]), "=f"(d[37]), "=f"(d[38]), "=f"(d[39]), "=f"(d[40]), "=f"(d[41]), "=f"(d[42]), "=f"(d[43]), "=f"(d[44]), "=f"(d[45]), "=f"(d[46]), "=f"(d[47]), "=f"(d[48]), "=f"(d[49]), "=f"(d[50]), "=f"(d[51]), "=f"(d[52]), "=f"(d[53]), "=f"(d[54]), "=f"(d[55]), "=f"(d[56]), "=f"(d[57]), "=f"(d[58]), "=f"(d[59]), "=f"(d[60]), "=f"(d[61]), "=f"(d[62]), "=f"(d[63])
    : "r"(a), "r"(b), "n"(AHI), "n"(BHI));
}
template<uint32_t AHI, uint32_t BHI> __device__ __forceinline__ void wg_ss_n160(float* d, uint32_t a, uint32_t b) {
  asm volatile("{\n.reg .pred p;\n.reg .b64 da, db;\nsetp.ne.b32 p, 1, 0;\nmov.b64 da, {%80, %82};\nmov.b64 db, {%81, %83};\n"
    "wgmma.mma_async.sync.aligned.m64n160k16.f32.bf16.bf16 {%0, %1, %2, %3, %4, %5, %6, %7, %8, %9, %10, %11, %12, %13, %14, %15, %16, %17, %18, %19, %20, %21, %22, %23, %24, %25, %26, %27, %28, %29, %30, %31, %32, %33, %34, %35, %36, %37, %38, %39, %40, %41, %42, %43, %44, %45, %46, %47, %48, %49, %50, %51, %52, %53, %54, %55, %56, %57, %58, %59, %60, %61, %62, %63, %64, %65, %66, %67, %68, %69, %70, %71, %72, %73, %74, %75, %76, %77, %78, %79}, da, db, p, 1, 1, 0, 1;\n}\n"
    : "+f"(d[0]), "+f"(d[1]), "+f"(d[2]), "+f"(d[3]), "+f"(d[4]), "+f"(d[5]), "+f"(d[6]), "+f"(d[7]), "+f"(d[8]), "+f"(d[9]), "+f"(d[10]), "+f"(d[11]), "+f"(d[12]), "+f"(d[13]), "+f"(d[14]), "+f"(d[15]), "+f"(d[16]), "+f"(d[17]), "+f"(d[18]), "+f"(d[19]), "+f"(d[20]), "+f"(d[21]), "+f"(d[22]), "+f"(d[23]), "+f"(d[24]), "+f"(d[25]), "+f"(d[26]), "+f"(d[27]), "+f"(d[28]), "+f"(d[29]), "+f"(d[30]), "+f"(d[31]), "+f"(d[32]), "+f"(d[33]), "+f"(d[34]), "+f"(d[35]), "+f"(d[36]), "+f"(d[37]), "+f"(d[38]), "+f"(d[39]), "+f"(d[40]), "+f"(d[41]), "+f"(d[42]), "+f"(d[43]), "+f"(d[44]), "+f"(d[45]), "+f"(d[46]), "+f"(d[47]), "+f"(d[48]), "+f"(d[49]), "+f"(d[50]), "+f"(d[51]), "+f"(d[52]), "+f"(d[53]), "+f"(d[54]), "+f"(d[55]), "+f"(d[56]), "+f"(d[57]), "+f"(d[58]), "+f"(d[59]), "+f"(d[60]), "+f"(d[61]), "+f"(d[62]), "+f"(d[63]), "+f"(d[64]), "+f"(d[65]), "+f"(d[66]), "+f"(d[67]), "+f"(d[68]), "+f"(d[69]), "+f"(d[70]), "+f"(d[71]), "+f"(d[72]), "+f"(d[73]), "+f"(d[74]), "+f"(d[75]), "+f"(d[76]), "+f"(d[77]), "+f"(d[78]), "+f"(d[79])
    : "r"(a), "r"(b), "n"(AHI), "n"(BHI));
}
template<uint32_t AHI, uint32_t BHI> __device__ __forceinline__ void wg_ss_z_n160(float* d, uint32_t a, uint32_t b) {
  asm volatile("{\n.reg .pred p;\n.reg .b64 da, db;\nsetp.ne.b32 p, 0, 0;\nmov.b64 da, {%80, %82};\nmov.b64 db, {%81, %83};\n"
    "wgmma.mma_async.sync.aligned.m64n160k16.f32.bf16.bf16 {%0, %1, %2, %3, %4, %5, %6, %7, %8, %9, %10, %11, %12, %13, %14, %15, %16, %17, %18, %19, %20, %21, %22, %23, %24, %25, %26, %27, %28, %29, %30, %31, %32, %33, %34, %35, %36, %37, %38, %39, %40, %41, %42, %43, %44, %45, %46, %47, %48, %49, %50, %51, %52, %53, %54, %55, %56, %57, %58, %59, %60, %61, %62, %63, %64, %65, %66, %67, %68, %69, %70, %71, %72, %73, %74, %75, %76, %77, %78, %79}, da, db, p, 1, 1, 0, 1;\n}\n"
    : "=f"(d[0]), "=f"(d[1]), "=f"(d[2]), "=f"(d[3]), "=f"(d[4]), "=f"(d[5]), "=f"(d[6]), "=f"(d[7]), "=f"(d[8]), "=f"(d[9]), "=f"(d[10]), "=f"(d[11]), "=f"(d[12]), "=f"(d[13]), "=f"(d[14]), "=f"(d[15]), "=f"(d[16]), "=f"(d[17]), "=f"(d[18]), "=f"(d[19]), "=f"(d[20]), "=f"(d[21]), "=f"(d[22]), "=f"(d[23]), "=f"(d[24]), "=f"(d[25]), "=f"(d[26]), "=f"(d[27]), "=f"(d[28]), "=f"(d[29]), "=f"(d[30]), "=f"(d[31]), "=f"(d[32]), "=f"(d[33]), "=f"(d[34]), "=f"(d[35]), "=f"(d[36]), "=f"(d[37]), "=f"(d[38]), "=f"(d[39]), "=f"(d[40]), "=f"(d[41]), "=f"(d[42]), "=f"(d[43]), "=f"(d[44]), "=f"(d[45]), "=f"(d[46]), "=f"(d[47]), "=f"(d[48]), "=f"(d[49]), "=f"(d[50]), "=f"(d[51]), "=f"(d[52]), "=f"(d[53]), "=f"(d[54]), "=f"(d[55]), "=f"(d[56]), "=f"(d[57]), "=f"(d[58]), "=f"(d[59]), "=f"(d[60]), "=f"(d[61]), "=f"(d[62]), "=f"(d[63]), "=f"(d[64]), "=f"(d[65]), "=f"(d[66]), "=f"(d[67]), "=f"(d[68]), "=f"(d[69]), "=f"(d[70]), "=f"(d[71]), "=f"(d[72]), "=f"(d[73]), "=f"(d[74]), "=f"(d[75]), "=f"(d[76]), "=f"(d[77]), "=f"(d[78]), "=f"(d[79])
    : "r"(a), "r"(b), "n"(AHI), "n"(BHI));
}
template<uint32_t BHI> __device__ __forceinline__ void wg_rs_n32(float* d, uint32_t a0, uint32_t a1, uint32_t a2, uint32_t a3, uint32_t b) {
  asm volatile("{\n.reg .pred p;\n.reg .b64 db;\nsetp.ne.b32 p, 1, 0;\nmov.b64 db, {%20, %21};\n"
    "wgmma.mma_async.sync.aligned.m64n32k16.f32.bf16.bf16 {%0, %1, %2, %3, %4, %5, %6, %7, %8, %9, %10, %11, %12, %13, %14, %15}, {%16, %17, %18, %19}, db, p, 1, 1, 1;\n}\n"
    : "+f"(d[0]), "+f"(d[1]), "+f"(d[2]), "+f"(d[3]), "+f"(d[4]), "+f"(d[5]), "+f"(d[6]), "+f"(d[7]), "+f"(d[8]), "+f"(d[9]), "+f"(d[10]), "+f"(d[11]), "+f"(d[12]), "+f"(d[13]), "+f"(d[14]), "+f"(d[15])
    : "r"(a0), "r"(a1), "r"(a2), "r"(a3), "r"(b), "n"(BHI));
}
template<uint32_t BHI> __device__ __forceinline__ void wg_rs_z_n32(float* d, uint32_t a0, uint32_t a1, uint32_t a2, uint32_t a3, uint32_t b) {
  asm volatile("{\n.reg .pred p;\n.reg .b64 db;\nsetp.ne.b32 p, 0, 0;\nmov.b64 db, {%20, %21};\n"
    "wgmma.mma_async.sync.aligned.m64n32k16.f32.bf16.bf16 {%0, %1, %2, %3, %4, %5, %6, %7, %8, %9, %10, %11, %12, %13, %14, %15}, {%16, %17, %18, %19}, db, p, 1, 1, 1;\n}\n"
    : "=f"(d[0]), "=f"(d[1]), "=f"(d[2]), "=f"(d[3]), "=f"(d[4]), "=f"(d[5]), "=f"(d[6]), "=f"(d[7]), "=f"(d[8]), "=f"(d[9]), "=f"(d[10]), "=f"(d[11]), "=f"(d[12]), "=f"(d[13]), "=f"(d[14]), "=f"(d[15])
    : "r"(a0), "r"(a1), "r"(a2), "r"(a3), "r"(b), "n"(BHI));
}
template<uint32_t BHI> __device__ __forceinline__ void wg_rs_n64(float* d, uint32_t a0, uint32_t a1, uint32_t a2, uint32_t a3, uint32_t b) {
  asm volatile("{\n.reg .pred p;\n.reg .b64 db;\nsetp.ne.b32 p, 1, 0;\nmov.b64 db, {%36, %37};\n"
    "wgmma.mma_async.sync.aligned.m64n64k16.f32.bf16.bf16 {%0, %1, %2, %3, %4, %5, %6, %7, %8, %9, %10, %11, %12, %13, %14, %15, %16, %17, %18, %19, %20, %21, %22, %23, %24, %25, %26, %27, %28, %29, %30, %31}, {%32, %33, %34, %35}, db, p, 1, 1, 0;\n}\n"
    : "+f"(d[0]), "+f"(d[1]), "+f"(d[2]), "+f"(d[3]), "+f"(d[4]), "+f"(d[5]), "+f"(d[6]), "+f"(d[7]), "+f"(d[8]), "+f"(d[9]), "+f"(d[10]), "+f"(d[11]), "+f"(d[12]), "+f"(d[13]), "+f"(d[14]), "+f"(d[15]), "+f"(d[16]), "+f"(d[17]), "+f"(d[18]), "+f"(d[19]), "+f"(d[20]), "+f"(d[21]), "+f"(d[22]), "+f"(d[23]), "+f"(d[24]), "+f"(d[25]), "+f"(d[26]), "+f"(d[27]), "+f"(d[28]), "+f"(d[29]), "+f"(d[30]), "+f"(d[31])
    : "r"(a0), "r"(a1), "r"(a2), "r"(a3), "r"(b), "n"(BHI));
}
template<uint32_t BHI> __device__ __forceinline__ void wg_rs_z_n64(float* d, uint32_t a0, uint32_t a1, uint32_t a2, uint32_t a3, uint32_t b) {
  asm volatile("{\n.reg .pred p;\n.reg .b64 db;\nsetp.ne.b32 p, 0, 0;\nmov.b64 db, {%36, %37};\n"
    "wgmma.mma_async.sync.aligned.m64n64k16.f32.bf16.bf16 {%0, %1, %2, %3, %4, %5, %6, %7, %8, %9, %10, %11, %12, %13, %14, %15, %16, %17, %18, %19, %20, %21, %22, %23, %24, %25, %26, %27, %28, %29, %30, %31}, {%32, %33, %34, %35}, db, p, 1, 1, 0;\n}\n"
    : "=f"(d[0]), "=f"(d[1]), "=f"(d[2]), "=f"(d[3]), "=f"(d[4]), "=f"(d[5]), "=f"(d[6]), "=f"(d[7]), "=f"(d[8]), "=f"(d[9]), "=f"(d[10]), "=f"(d[11]), "=f"(d[12]), "=f"(d[13]), "=f"(d[14]), "=f"(d[15]), "=f"(d[16]), "=f"(d[17]), "=f"(d[18]), "=f"(d[19]), "=f"(d[20]), "=f"(d[21]), "=f"(d[22]), "=f"(d[23]), "=f"(d[24]), "=f"(d[25]), "=f"(d[26]), "=f"(d[27]), "=f"(d[28]), "=f"(d[29]), "=f"(d[30]), "=f"(d[31])
    : "r"(a0), "r"(a1), "r"(a2), "r"(a3), "r"(b), "n"(BHI));
}
template<uint32_t BHI> __device__ __forceinline__ void wg_rs_n24(float* d, uint32_t a0, uint32_t a1, uint32_t a2, uint32_t a3, uint32_t b) {
  asm volatile("{\n.reg .pred p;\n.reg .b64 db;\nsetp.ne.b32 p, 1, 0;\nmov.b64 db, {%16, %17};\n"
    "wgmma.mma_async.sync.aligned.m64n24k16.f32.bf16.bf16 {%0, %1, %2, %3, %4, %5, %6, %7, %8, %9, %10, %11}, {%12, %13, %14, %15}, db, p, 1, 1, 1;\n}\n"
    : "+f"(d[0]), "+f"(d[1]), "+f"(d[2]), "+f"(d[3]), "+f"(d[4]), "+f"(d[5]), "+f"(d[6]), "+f"(d[7]), "+f"(d[8]), "+f"(d[9]), "+f"(d[10]), "+f"(d[11])
    : "r"(a0), "r"(a1), "r"(a2), "r"(a3), "r"(b), "n"(BHI));
}
template<uint32_t BHI> __device__ __forceinline__ void wg_rs_z_n24(float* d, uint32_t a0, uint32_t a1, uint32_t a2, uint32_t a3, uint32_t b) {
  asm volatile("{\n.reg .pred p;\n.reg .b64 db;\nsetp.ne.b32 p, 0, 0;\nmov.b64 db, {%16, %17};\n"
    "wgmma.mma_async.sync.aligned.m64n24k16.f32.bf16.bf16 {%0, %1, %2, %3, %4, %5, %6, %7, %8, %9, %10, %11}, {%12, %13, %14, %15}, db, p, 1, 1, 1;\n}\n"
    : "=f"(d[0]), "=f"(d[1]), "=f"(d[2]), "=f"(d[3]), "=f"(d[4]), "=f"(d[5]), "=f"(d[6]), "=f"(d[7]), "=f"(d[8]), "=f"(d[9]), "=f"(d[10]), "=f"(d[11])
    : "r"(a0), "r"(a1), "r"(a2), "r"(a3), "r"(b), "n"(BHI));
}
template<uint32_t BHI> __device__ __forceinline__ void wg_rsb_n64(float* d, uint32_t a0, uint32_t a1, uint32_t a2, uint32_t a3, uint32_t b) {
  asm volatile("{\n.reg .pred p;\n.reg .b64 db;\nsetp.ne.b32 p, 1, 0;\nmov.b64 db, {%36, %37};\n"
    "wgmma.mma_async.sync.aligned.m64n64k16.f32.bf16.bf16 {%0, %1, %2, %3, %4, %5, %6, %7, %8, %9, %10, %11, %12, %13, %14, %15, %16, %17, %18, %19, %20, %21, %22, %23, %24, %25, %26, %27, %28, %29, %30, %31}, {%32, %33, %34, %35}, db, p, 1, 1, 1;\n}\n"
    : "+f"(d[0]), "+f"(d[1]), "+f"(d[2]), "+f"(d[3]), "+f"(d[4]), "+f"(d[5]), "+f"(d[6]), "+f"(d[7]), "+f"(d[8]), "+f"(d[9]), "+f"(d[10]), "+f"(d[11]), "+f"(d[12]), "+f"(d[13]), "+f"(d[14]), "+f"(d[15]), "+f"(d[16]), "+f"(d[17]), "+f"(d[18]), "+f"(d[19]), "+f"(d[20]), "+f"(d[21]), "+f"(d[22]), "+f"(d[23]), "+f"(d[24]), "+f"(d[25]), "+f"(d[26]), "+f"(d[27]), "+f"(d[28]), "+f"(d[29]), "+f"(d[30]), "+f"(d[31])
    : "r"(a0), "r"(a1), "r"(a2), "r"(a3), "r"(b), "n"(BHI));
}
template<uint32_t BHI> __device__ __forceinline__ void wg_rsb_z_n64(float* d, uint32_t a0, uint32_t a1, uint32_t a2, uint32_t a3, uint32_t b) {
  asm volatile("{\n.reg .pred p;\n.reg .b64 db;\nsetp.ne.b32 p, 0, 0;\nmov.b64 db, {%36, %37};\n"
    "wgmma.mma_async.sync.aligned.m64n64k16.f32.bf16.bf16 {%0, %1, %2, %3, %4, %5, %6, %7, %8, %9, %10, %11, %12, %13, %14, %15, %16, %17, %18, %19, %20, %21, %22, %23, %24, %25, %26, %27, %28, %29, %30, %31}, {%32, %33, %34, %35}, db, p, 1, 1, 1;\n}\n"
    : "=f"(d[0]), "=f"(d[1]), "=f"(d[2]), "=f"(d[3]), "=f"(d[4]), "=f"(d[5]), "=f"(d[6]), "=f"(d[7]), "=f"(d[8]), "=f"(d[9]), "=f"(d[10]), "=f"(d[11]), "=f"(d[12]), "=f"(d[13]), "=f"(d[14]), "=f"(d[15]), "=f"(d[16]), "=f"(d[17]), "=f"(d[18]), "=f"(d[19]), "=f"(d[20]), "=f"(d[21]), "=f"(d[22]), "=f"(d[23]), "=f"(d[24]), "=f"(d[25]), "=f"(d[26]), "=f"(d[27]), "=f"(d[28]), "=f"(d[29]), "=f"(d[30]), "=f"(d[31])
    : "r"(a0), "r"(a1), "r"(a2), "r"(a3), "r"(b), "n"(BHI));
}

__device__ __forceinline__ void wg_fence() { asm volatile("wgmma.fence.sync.aligned;" ::: "memory"); }
__device__ __forceinline__ void wg_commit() { asm volatile("wgmma.commit_group.sync.aligned;" ::: "memory"); }
template <int N> __device__ __forceinline__ void wg_wait() { asm volatile("wgmma.wait_group.sync.aligned %0;" ::"n"(N) : "memory"); }
template <int R> __device__ __forceinline__ void pin(float* d) {
#pragma unroll
  for (int i = 0; i < R; i++) asm volatile("" : "+f"(d[i])::"memory");
}
template <int R> __device__ __forceinline__ void pin(uint32_t* d) {
#pragma unroll
  for (int i = 0; i < R; i++) asm volatile("" : "+r"(d[i])::"memory");
}
__device__ __forceinline__ float ex2(float x) { float y; asm("ex2.approx.ftz.f32 %0, %1;" : "=f"(y) : "f"(x)); return y; }
__device__ __forceinline__ float tanh_fast(float x) { float y; asm("tanh.approx.f32 %0, %1;" : "=f"(y) : "f"(x)); return y; }
__device__ __forceinline__ uint32_t pack(float lo, float hi) { uint32_t r; asm("cvt.rn.bf16x2.f32 %0, %1, %2;" : "=r"(r) : "f"(hi), "f"(lo)); return r; }
__device__ __forceinline__ float bf_lo(uint32_t v) { return __uint_as_float(v << 16); }
__device__ __forceinline__ float bf_hi(uint32_t v) { return __uint_as_float(v & 0xffff0000u); }
__device__ __forceinline__ float bf_round(float x) { return bf_lo(pack(x, 0.f)); }

__device__ __forceinline__ void mbar_init(uint32_t bar, uint32_t cnt) { asm volatile("mbarrier.init.shared::cta.b64 [%0], %1;" ::"r"(bar), "r"(cnt) : "memory"); }
__device__ __forceinline__ void mbar_expect(uint32_t bar, uint32_t bytes) { asm volatile("mbarrier.arrive.expect_tx.shared::cta.b64 _, [%0], %1;" ::"r"(bar), "r"(bytes) : "memory"); }
__device__ __forceinline__ void mbar_wait(uint32_t bar, uint32_t parity) {
  asm volatile(
      "{\n.reg .pred p;\n.reg .u32 c;\n"
      "mbarrier.try_wait.parity.shared::cta.b64 p, [%0], %1;\n"
      "@p bra.uni DONE;\n"
      "mov.u32 c, 0;\n"
      "LOOP:\n"
      "mbarrier.try_wait.parity.shared::cta.b64 p, [%0], %1;\n"
      "@p bra.uni DONE;\n"
      "add.u32 c, c, 1;\n"
      "setp.lt.u32 p, c, 0x400000;\n"
      "@p bra.uni LOOP;\n"
      "trap;\n"
      "DONE:\n}\n" ::"r"(bar), "r"(parity) : "memory");
}
__device__ __forceinline__ uint32_t mbar_test(uint32_t bar, uint32_t parity) {
  uint32_t ok;
  asm volatile("{\n.reg .pred p;\nmbarrier.test_wait.parity.shared::cta.b64 p, [%1], %2;\nselp.u32 %0, 1, 0, p;\n}\n" : "=r"(ok) : "r"(bar), "r"(parity) : "memory");
  return ok;
}
__device__ __forceinline__ void mbar_arrive_if(uint32_t bar, uint32_t cond) {
  asm volatile("{\n.reg .pred p;\nsetp.ne.u32 p, %1, 0;\n@p mbarrier.arrive.shared::cta.b64 _, [%0];\n}\n" ::"r"(bar), "r"(cond) : "memory");
}
__device__ __forceinline__ uint32_t bsub2(uint32_t a, uint32_t b) { uint32_t d; asm("sub.rn.bf16x2 %0, %1, %2;" : "=r"(d) : "r"(a), "r"(b)); return d; }
__device__ __forceinline__ uint32_t bscale2(uint32_t d, uint32_t hi, uint32_t lo) {
  uint32_t t, r;
  asm("mul.rn.bf16x2 %0, %1, %2;" : "=r"(t) : "r"(d), "r"(lo));
  asm("fma.rn.bf16x2 %0, %1, %2, %3;" : "=r"(r) : "r"(d), "r"(hi), "r"(t));
  return r;
}
__device__ __forceinline__ void flag_wait(const uint32_t* f, uint32_t target) {
  asm volatile(
      "{\n.reg .pred p;\n.reg .u32 c, v;\n"
      "mov.u32 c, 0;\n"
      "LOOP:\n"
      "ld.acquire.gpu.global.u32 v, [%0];\n"
      "sub.u32 v, v, %1;\n"
      "setp.ge.s32 p, v, 0;\n"
      "@p bra DONE;\n"
      "add.u32 c, c, 1;\n"
      "setp.lt.u32 p, c, 0x400000;\n"
      "@p bra LOOP;\n"
      "trap;\n"
      "DONE:\n}\n" ::"l"(f), "r"(target) : "memory");
}
__device__ __forceinline__ uint32_t flag_wait_v(const uint32_t* f, uint32_t target) {
  uint32_t v;
  asm volatile(
      "{\n.reg .pred p;\n.reg .u32 c, d;\n"
      "mov.u32 c, 0;\n"
      "LOOP:\n"
      "ld.acquire.gpu.global.u32 %0, [%1];\n"
      "sub.u32 d, %0, %2;\n"
      "setp.ge.s32 p, d, 0;\n"
      "@p bra DONE;\n"
      "add.u32 c, c, 1;\n"
      "setp.lt.u32 p, c, 0x400000;\n"
      "@p bra LOOP;\n"
      "trap;\n"
      "DONE:\n}\n" : "=&r"(v) : "l"(f), "r"(target) : "memory");
  return v;
}
__device__ __forceinline__ float sqrt_fast(float x) { float y; asm("sqrt.approx.f32 %0, %1;" : "=f"(y) : "f"(x)); return y; }
__device__ __forceinline__ float rcp_fast(float x) { float y; asm("rcp.approx.ftz.f32 %0, %1;" : "=f"(y) : "f"(x)); return y; }
__device__ __forceinline__ void ldsm4(uint32_t* v, uint32_t addr) {
  asm volatile("ldmatrix.sync.aligned.m8n8.x4.shared.b16 {%0,%1,%2,%3}, [%4];" : "=r"(v[0]), "=r"(v[1]), "=r"(v[2]), "=r"(v[3]) : "r"(addr) : "memory");
}
__device__ __forceinline__ void stsm4(uint32_t addr, uint32_t a, uint32_t b, uint32_t c, uint32_t d) {
  asm volatile("stmatrix.sync.aligned.m8n8.x4.shared.b16 [%0], {%1,%2,%3,%4};" ::"r"(addr), "r"(a), "r"(b), "r"(c), "r"(d) : "memory");
}
__device__ __forceinline__ void flag_add(uint32_t* f) { asm volatile("red.relaxed.gpu.global.add.u32 [%0], 1;" ::"l"(f) : "memory"); }
__device__ __forceinline__ void fence_gpu() { asm volatile("fence.acq_rel.gpu;" ::: "memory"); }
__device__ __forceinline__ void fence_async() { asm volatile("fence.proxy.async.global;" ::: "memory"); }
__device__ __forceinline__ void tma2d(uint32_t dst, const CUtensorMap* tm, uint32_t bar, int c0, int c1) {
  asm volatile("cp.async.bulk.tensor.2d.shared::cluster.global.mbarrier::complete_tx::bytes [%0], [%1, {%3, %4}], [%2];" ::"r"(dst), "l"(tm), "r"(bar), "r"(c0), "r"(c1) : "memory");
}
__device__ __forceinline__ void tma2d_h(uint32_t dst, const CUtensorMap* tm, uint32_t bar, int c0, int c1, uint64_t pol) {
  asm volatile("cp.async.bulk.tensor.2d.shared::cluster.global.mbarrier::complete_tx::bytes.L2::cache_hint [%0], [%1, {%3, %4}], [%2], %5;" ::"r"(dst), "l"(tm), "r"(bar), "r"(c0), "r"(c1), "l"(pol) : "memory");
}
__device__ __forceinline__ void bulk_s2g(void* dst, uint32_t src, uint32_t bytes) {
  asm volatile("cp.async.bulk.global.shared::cta.bulk_group [%0], [%1], %2;" ::"l"(dst), "r"(src), "r"(bytes) : "memory");
}
__device__ __forceinline__ void mma_ones(float* c, const uint32_t* a) {
  asm("mma.sync.aligned.m16n8k16.row.col.f32.bf16.bf16.f32 {%0,%1,%2,%3}, {%4,%5,%6,%7}, {%8,%8}, {%0,%1,%2,%3};"
      : "+f"(c[0]), "+f"(c[1]), "+f"(c[2]), "+f"(c[3]) : "r"(a[0]), "r"(a[1]), "r"(a[2]), "r"(a[3]), "r"(0x3f803f80u));
}
__device__ __forceinline__ void tma5d(uint32_t dst, const CUtensorMap* tm, uint32_t bar, int c0, int c4) {
  asm volatile("cp.async.bulk.tensor.5d.shared::cluster.global.mbarrier::complete_tx::bytes [%0], [%1, {%3, %5, %5, %5, %4}], [%2];" ::"r"(dst), "l"(tm), "r"(bar), "r"(c0), "r"(c4), "r"(0) : "memory");
}
__device__ __forceinline__ void tma3d(uint32_t dst, const CUtensorMap* tm, uint32_t bar, int c0, int c2) {
  asm volatile("cp.async.bulk.tensor.3d.shared::cluster.global.mbarrier::complete_tx::bytes [%0], [%1, {%3, %5, %4}], [%2];" ::"r"(dst), "l"(tm), "r"(bar), "r"(c0), "r"(c2), "r"(0) : "memory");
}
__device__ __forceinline__ void bulk_g2s(uint32_t dst, const void* src, uint32_t bytes, uint32_t bar) {
  asm volatile("cp.async.bulk.shared::cluster.global.mbarrier::complete_tx::bytes [%0], [%1], %2, [%3];" ::"r"(dst), "l"(src), "r"(bytes), "r"(bar) : "memory");
}
__device__ __forceinline__ void pf_line(const void* p) { asm volatile("prefetch.global.L2 [%0];" ::"l"(p) : "memory"); }
__device__ __forceinline__ int fresh_tid() { int v; asm volatile("mov.u32 %0, %%tid.x;" : "=r"(v)); return v; }
struct Att {
  float s[32];
  float o[12];
  uint32_t p[16];
  uint32_t q[8];
};

__device__ __forceinline__ float warp_sum(float v) {
#pragma unroll 1
  for (int d = 16; d; d >>= 1) v += __shfl_xor_sync(0xffffffffu, v, d);
  return v;
}
#define OPAQUE(x) asm volatile("" : "+r"(x))
__device__ __forceinline__ void attn_slow_row(int cta, uint32_t& w) {
  float mx = -INFINITY;
#pragma unroll 1
  for (uint32_t key = threadIdx.x & 31; key < SEQ; key += 32) {
    float s = 0.f;
#pragma unroll 1
    for (uint32_t v = 0; v < 9; v++) {
      OPAQUE(w); OPAQUE(key);
      const uint32_t hp = (w >> 4) & 3, pos = (v + hp) & 3;
      const uint32_t q = g_Q[(((cta * 4 + hp) * 2 + (v >> 3)) * 256 + ((w >> 6) & 7) * 32 + (w & 7) * 4 + pos) * 4 + 2 * ((v >> 2) & 1) + ((w >> 3) & 1)];
      const uint32_t u = g_KV[(4 * (cta & 7) + hp) * SEQ * 20 + (key >> 3) * 160 + (key & 7) * 4 + (v >> 2) * 32 + pos];
      s = fmaf(bf_lo(q), bf_lo(u), fmaf(bf_hi(q), bf_hi(u), s));
    }
    g_S[(cta * 8 + ((w >> 6) & 7)) * SEQ + key] = s;
    mx = fmaxf(mx, s);
  }
#pragma unroll 1
  for (int d = 16; d; d >>= 1) mx = fmaxf(mx, __shfl_xor_sync(0xffffffffu, mx, d));
  float l = 0.f;
#pragma unroll 1
  for (uint32_t key = threadIdx.x & 31; key < SEQ; key += 32) l += ex2(g_S[(cta * 8 + ((w >> 6) & 7)) * SEQ + key] - mx);
  l = 2.f * rcp_fast(warp_sum(l));
#pragma unroll 1
  for (uint32_t v = w >> 9; v < 9; v++) {
    float a = 0.f, b = 0.f;
#pragma unroll 1
    for (uint32_t key = threadIdx.x & 31; key < SEQ; key += 32) {
      OPAQUE(w); OPAQUE(v);
      const uint32_t hp = (w >> 4) & 3;
      const uint32_t u = g_KV[(4 * (cta & 7) + hp) * SEQ * 20 + (key >> 3) * 160 + (key & 7) * 4 + (v < 8 ? (3 + (v >> 2)) * 32 + (v & 3) : 64 + ((hp + 2) & 3))];
      const float p = ex2(g_S[(cta * 8 + ((w >> 6) & 7)) * SEQ + key] - mx);
      a = fmaf(p, bf_lo(u), a); b = fmaf(p, bf_hi(u), b);
    }
    a = warp_sum(a); b = warp_sum(b);
    OPAQUE(w);
    const uint32_t hp = (w >> 4) & 3;
    if ((threadIdx.x & 31) == 0) g_O[cta * 9 * 512 + (((w >> 6) & 7) * 16 + (w & 15)) * 4 + (v < 8 ? (2 * hp + (v >> 2)) * 512 + (v & 3) : 8 * 512 + hp)] = pack(a * l, b * l);
  }
}

__device__ __forceinline__ uint32_t bad_heads(uint32_t bad_addr, int wr) {
  uint32_t bad;
  __syncwarp();
  asm volatile("ld.volatile.shared.u32 %0, [%1];" : "=r"(bad) : "r"(bad_addr) : "memory");
  return __shfl_sync(0xffffffffu, (bad >> (4 * wr)) & 15, 0);
}
__device__ __forceinline__ void repair_rows(int cta, int wr, uint32_t bad, int last_head, bool final) {
#pragma unroll 1
  for (uint32_t w = wr * 64; w < wr * 64 + 64; w++) {
    if (!((bad >> ((w >> 4) & 3)) & 1)) continue;
    if (final && ((w >> 4) & 3) != last_head) w |= 8u << 9;
    attn_slow_row(cta, w);
    w &= 511;
  }
  __syncwarp();
}
__device__ __forceinline__ void o_normalise(const float* o, uint32_t* w, uint32_t& x0, uint32_t& x1, int hp, int lane, uint32_t bad_addr, int wr) {
  const int src = (lane & ~3) | ((hp + 1) & 3);
  float l0 = __shfl_sync(0xffffffffu, o[0], src), l1 = __shfl_sync(0xffffffffu, o[2], src);
  float sa = 0.f;
#pragma unroll
  for (int i = 0; i < 12; i++) sa += fabsf(o[i]);
  bool ok = (l0 <= 1.329228e36f) && (l1 <= 1.329228e36f) && (l0 > 0.f) && (l1 > 0.f) && (sa <= 3.0e38f);
  float i0 = 2.f * rcp_fast(l0), i1 = 2.f * rcp_fast(l1);
  w[0] = pack(o[4] * i0, o[5] * i0);
  w[1] = pack(o[6] * i1, o[7] * i1);
  w[2] = pack(o[8] * i0, o[9] * i0);
  w[3] = pack(o[10] * i1, o[11] * i1);
  if ((lane & 3) == ((hp + 2) & 3)) { x0 = pack(o[0] * i0, o[1] * i0); x1 = pack(o[2] * i1, o[3] * i1); }
  if (!ok) asm volatile("red.shared.or.b32 [%0], %1;" ::"r"(bad_addr), "r"(1u << (4 * wr + hp)) : "memory");
}

__device__ __forceinline__ void issue_pv(Att& a, uint32_t kdesc) {
  const uint32_t vdesc = kdesc + 192 + (LO_V - LO_K);
#pragma unroll
  for (int k = 0; k < 4; k++) wg_rs_n24<HI_V>(a.o, a.p[4 * k], a.p[4 * k + 1], a.p[4 * k + 2], a.p[4 * k + 3], vdesc + k * 48);
}
__device__ __forceinline__ void issue_att(Att& a, uint32_t kdesc) {
  issue_pv(a, kdesc);
  wg_rs_z_n64<HI_K>(a.s, a.q[0], a.q[1], a.q[2], a.q[3], kdesc);
  wg_rs_n64<HI_K>(a.s, a.q[4], a.q[5], a.q[6], a.q[7], kdesc + 16);
}
__device__ __forceinline__ void softmax_a(Att& a) {
#pragma unroll
  for (int i = 0; i < SM_A; i++) a.p[i] = pack(ex2(a.s[2 * i]), ex2(a.s[2 * i + 1]));
  pin<SM_A>(a.p);
}
__device__ __forceinline__ void softmax_b(Att& a) {
#pragma unroll
  for (int i = SM_A; i < SM_B; i++) a.p[i] = pack(ex2(a.s[2 * i]), ex2(a.s[2 * i + 1]));
  a.s[2 * SM_B] = ex2(a.s[2 * SM_B]); a.s[2 * SM_B + 1] = ex2(a.s[2 * SM_B + 1]);
  pin<SM_B - SM_A>(a.p + SM_A); pin<2>(a.s + 2 * SM_B);
}
__device__ __forceinline__ void softmax_c(Att& a) {
  a.p[SM_B] = pack(a.s[2 * SM_B], a.s[2 * SM_B + 1]);
#pragma unroll
  for (int i = SM_B + 1; i < 16; i++) a.p[i] = pack(ex2(a.s[2 * i]), ex2(a.s[2 * i + 1]));
  pin<16 - SM_B>(a.p + SM_B);
}
__device__ __forceinline__ void first_tile(Att& a, int hp, int lane) {
  float m0 = fmaxf(a.s[0], a.s[1]), m1 = fmaxf(a.s[2], a.s[3]);
#pragma unroll
  for (int i = 4; i < 32; i += 4) { m0 = fmaxf(m0, fmaxf(a.s[i], a.s[i + 1])); m1 = fmaxf(m1, fmaxf(a.s[i + 2], a.s[i + 3])); }
  m0 = fmaxf(m0, __shfl_xor_sync(0xffffffffu, m0, 1)); m1 = fmaxf(m1, __shfl_xor_sync(0xffffffffu, m1, 1));
  m0 = fmaxf(m0, __shfl_xor_sync(0xffffffffu, m0, 2)); m1 = fmaxf(m1, __shfl_xor_sync(0xffffffffu, m1, 2));
  float n0 = -(m0 + MOFF), n1 = -(m1 + MOFF);
  float h0 = bf_round(n0), h1 = bf_round(n1);
  uint32_t e0 = pack(h0, n0 - h0), e1 = pack(h1, n1 - h1);
  n0 = h0 + bf_hi(e0); n1 = h1 + bf_hi(e1);
  if ((lane & 3) == ((hp + 1) & 3)) { a.q[4] = e0; a.q[5] = e1; }
#pragma unroll
  for (int i = 0; i < 32; i += 4) { a.s[i] += n0; a.s[i + 1] += n0; a.s[i + 2] += n1; a.s[i + 3] += n1; }
#pragma unroll
  for (int i = 0; i < 12; i++) a.o[i] = 0.f;
  pin<12>(a.o); pin<8>(a.q);
}
__device__ __forceinline__ void fetch_q(uint32_t* q, int cta, int hp, int tid) {
  const uint4* src = reinterpret_cast<const uint4*>(g_Q) + (cta * 4 + hp) * 512 + tid;
  const uint4 u = __ldcg(src);
  const uint2 v = __ldcg(reinterpret_cast<const uint2*>(src + 256));
  q[0] = u.x; q[1] = u.y; q[2] = u.z; q[3] = u.w; q[4] = v.x; q[5] = v.y;
}
__device__ __forceinline__ void h_epilogue(const float* acc, uint32_t* dst) {
#pragma unroll
  for (int b = 0; b < 4; b++) {
    uint32_t w[2][2];
#pragma unroll
    for (int i = 0; i < 2; i++) {
      float h[4];
#pragma unroll
      for (int e = 0; e < 4; e++) {
        const float g = acc[(2 * b + i) * 4 + e], u = acc[32 + (2 * b + i) * 4 + e];
        h[e] = fmaf(tanh_fast(0.5f * g), u, u);
      }
      w[0][i] = pack(h[0], h[1]); w[1][i] = pack(h[2], h[3]);
    }
    *reinterpret_cast<uint2*>(dst + 1024 * b) = make_uint2(w[0][0], w[0][1]);
    *reinterpret_cast<uint2*>(dst + 1024 * b + 32) = make_uint2(w[1][0], w[1][1]);
  }
}
__device__ __forceinline__ void rotate9(uint32_t (&v)[9][2]) {
#pragma unroll
  for (int rh = 0; rh < 2; rh++) {
    const uint32_t r = v[8][rh];
#pragma unroll
    for (int i = 8; i > 0; i--) v[i][rh] = v[i - 1][rh];
    v[0][rh] = r;
  }
}
template <int HP> __device__ __forceinline__ void store_kv_head(uint32_t (&pk)[2][9][2], uint32_t* kvp, int lane, uint32_t sk = 0, uint32_t sv = 0) {
  const int t = lane & 3, dv = ((t - HP) & 3) - t;
  const bool up = t < HP;
#pragma unroll
  for (int rh = 0; rh < 2; rh++) {
    uint32_t* d = kvp + HP * SEQ * 20 + rh * 160;
    const uint32_t c0 = up ? pk[0][2 * HP + 1][rh] : pk[0][2 * HP][rh], c1 = up ? pk[0][2 * HP + 2][rh] : pk[0][2 * HP + 1][rh];
    const uint32_t c3 = up ? pk[1][2 * HP + 1][rh] : pk[1][2 * HP][rh], c4 = up ? pk[1][2 * HP + 2][rh] : pk[1][2 * HP + 1][rh];
    const uint32_t v9 = __shfl_sync(0xffffffffu, pk[1][2 * HP + 2][rh], (lane & ~3) | HP);
    const uint32_t c2 = t == HP ? pk[0][2 * HP + 2][rh] : t == ((HP + 1) & 3) ? 0x3f803f80u : t == ((HP + 2) & 3) ? v9 : 0u;
    d[0] = c0; d[32] = c1; d[64] = c2; d[96 + dv] = c3; d[128 + dv] = c4;
    if (sk) {
      asm volatile("st.shared.b32 [%0], %1;\nst.shared.b32 [%0 + 128], %2;\nst.shared.b32 [%0 + 256], %3;" ::"r"(sk + rh * 384), "r"(c0), "r"(c1), "r"(c2) : "memory");
      asm volatile("st.shared.b32 [%0], %1;\nst.shared.b32 [%2 + 128], %3;\nst.shared.b32 [%2 + 256], %4;" ::"r"(sv + rh * 384), "r"(c2), "r"(sv + rh * 384 + dv * 4), "r"(c3), "r"(c4) : "memory");
    }
  }
}

template <int OFF> __device__ __forceinline__ void ld4(uint32_t* v, const void* p) {
  asm volatile("ld.relaxed.gpu.global.v4.b32 {%0,%1,%2,%3}, [%4 + %5];" : "=r"(v[0]), "=r"(v[1]), "=r"(v[2]), "=r"(v[3]) : "l"(p), "n"(OFF) : "memory");
}
template <int OFF> __device__ __forceinline__ void ld2(uint32_t* v, const void* p) {
  asm volatile("ld.relaxed.gpu.global.v2.b32 {%0,%1}, [%2 + %3];" : "=r"(v[0]), "=r"(v[1]) : "l"(p), "n"(OFF) : "memory");
}
__device__ __forceinline__ void stage_partials(const float* acc, uint32_t dst, int tid) {
  const int lane = tid & 31, row = (tid >> 5) * 16 + (lane & 15);
  const uint32_t r128 = dst + row * 128, r64 = dst + 49152 + row * 64;
#pragma unroll
  for (int i = 0; i < 12; i++) {
    const float* v = acc + 8 * i;
    stsm4(r128 + (i >> 2) * 16384 + (((2 * (i & 3) + (lane >> 4)) ^ (row & 7)) << 4), pack(v[0], v[1]), pack(v[2], v[3]), pack(v[4], v[5]), pack(v[6], v[7]));
  }
#pragma unroll
  for (int i = 0; i < 2; i++) {
    const float* v = acc + 128 + 8 * i;
    stsm4(r64 + (((2 * i + (lane >> 4)) ^ ((row >> 1) & 3)) << 4), pack(v[0], v[1]), pack(v[2], v[3]), pack(v[4], v[5]), pack(v[6], v[7]));
  }
}
__device__ __forceinline__ void final_epilogue(const float* acc, const Params& prm, int m, int hh, int q, int tid) {
  uint32_t r[18];
#pragma unroll
  for (int i = 0; i < 16; i++) r[i] = pack(acc[2 * i] * 0.5f, acc[2 * i + 1] * 0.5f);
#pragma unroll
  for (int i = 0; i < 2; i++) {
    const int o = 32 + 4 * i;
    const float a0 = (q & 2) ? acc[o + 2] : acc[o], a1 = (q & 2) ? acc[o + 10] : acc[o + 8];
    const float b0 = (q & 2) ? acc[o + 3] : acc[o + 1], b1 = (q & 2) ? acc[o + 11] : acc[o + 9];
    r[16 + i] = pack(((q & 1) ? a1 : a0) * 0.5f, ((q & 1) ? b1 : b0) * 0.5f);
  }
  const size_t off = (size_t)(128 * m + (tid >> 5) * 16 + ((tid & 31) >> 2)) * DM + 2 * (tid & 3);
  const bool odd = tid & 1;
  uint32_t* o1 = reinterpret_cast<uint32_t*>(prm.out + off + 320 * hh + 64 * q) + (odd ? 3 : 0);
  uint32_t* o2 = reinterpret_cast<uint32_t*>(prm.out + off + 256 + 32 * hh + 16 * (q & 1) + (q >> 1) * 8 * DM) + (odd ? 3 : 0);
#pragma unroll
  for (int i = 0; i < 9; i++) {
    const uint32_t A = i < 8 ? r[4 * (i >> 1) + (i & 1)] : r[16], B = i < 8 ? r[4 * (i >> 1) + 2 + (i & 1)] : r[17];
    const uint32_t y = __shfl_xor_sync(0xffffffffu, odd ? A : B, 1);
    *reinterpret_cast<uint2*>(i < 8 ? o1 + 8 * (i >> 1) + (i & 1) * 8 * (DM / 2) : o2) = odd ? make_uint2(y, B) : make_uint2(A, y);
  }
}

__global__ void __launch_bounds__(384, 1) fused_kernel(const __grid_constant__ Params prm) {
  extern __shared__ __align__(1024) uint8_t smem[];
  constexpr uint32_t sb = 1024;
  const uint32_t bar = sb + SM_BAR;
  const int m = blockIdx.x & 15, j = blockIdx.x >> 4;
  const int cta = m * 8 + j;
  const int wr = __shfl_sync(0xffffffffu, (int)(threadIdx.x >> 5), 0);
  const int wg = wr >> 2;
  const int lane = threadIdx.x & 31;
  STAMP(0);
  if (wg == 2 && lane == 0) {
    if (wr == 8) {
      asm volatile("prefetch.tensormap [%0];" ::"l"(&prm.xm) : "memory");
#pragma unroll
      for (int c = 0; c < 9; c++) mbar_init(bar + 8 * (B_X + c), 1);
#pragma unroll
      for (int c = 0; c < 9; c++) mbar_expect(bar + 8 * (B_X + c), 16384);
      asm volatile("fence.proxy.async.shared::cta;" ::: "memory");
#pragma unroll
      for (int c = 0; c < 3; c++) tma2d(sb + SM_XN + c * 16384, &prm.xm, bar + 8 * (B_X + c), 64 * c, 128 * m);
    } else {
      if (wr == 9) {
#pragma unroll
        for (int i = 0; i < 8; i++) mbar_init(bar + 8 * (B_F + i), 2);
#pragma unroll
        for (int i = 0; i < 3; i++) mbar_init(bar + 8 * (B_QF + i), 1);
      } else if (wr == 10) {
#pragma unroll
        for (int i = 0; i < 8; i++) mbar_init(bar + 8 * (B_E + i), 8);
#pragma unroll
        for (int i = 0; i < 3; i++) mbar_init(bar + 8 * (B_QE + i), 8);
      } else {
#pragma unroll
        for (int i = B_SK1; i <= B_SP; i++) mbar_init(bar + 8 * i, 8);
        mbar_init(bar + 8 * B_OL, 1); mbar_init(bar + 8 * B_RX, 1);
        mbar_init(bar + 8 * B_NR, 4); mbar_init(bar + 8 * (B_NR + 1), 4);
        asm volatile("st.shared.u32 [%0], 0;" ::"r"(sb + SM_BAD) : "memory");
        if ((uint32_t)__cvta_generic_to_shared(smem) != sb || (sb & 1023)) asm volatile("trap;");
      }
      asm volatile("fence.proxy.async.shared::cta;" ::: "memory");
    }
  }
  if (wr == 0) {
    const uint32_t one = (lane >> 3) == (lane & 3) ? ((lane & 4) ? 0x3f800000u : 0x00003f80u) : 0u;
    asm volatile("st.shared.v4.b32 [%0], {%1,%2,%2,%1};" ::"r"(sb + SM_ID + lane * 16), "r"(one), "r"(0) : "memory");
  }
  __syncthreads();

  if (wg == 2) {
    asm volatile("setmaxnreg.dec.sync.aligned.u32 24;");
    const int pw = wr & 3;
    const uint32_t epoch = *(volatile uint32_t*)FLAG_EPOCH(cta);
    const int hh = j & 1;
#define ACOL(A) (320 * hh + 64 * (((j >> 1) + 1 + (A)) & 3))
    if (pw == 0) {
      if (lane == 0) {
#pragma unroll
        for (int c = 3; c < 9; c++) tma2d(sb + SM_XN + c * 16384, &prm.xm, bar + 8 * (B_X + c), 64 * c, 128 * m);
        uint64_t pol;
        asm volatile("createpolicy.fractional.L2::evict_first.b64 %0, 1.0;" : "=l"(pol));
#pragma unroll 1
        for (int kb = 0; kb < 9; kb++) {
          const int s = kb % 3;
          if (kb >= 3) mbar_wait(bar + 8 * (B_QE + s), (kb / 3 - 1) & 1);
          const uint32_t fb = bar + 8 * (B_QF + s), dst = sb + SM_RING + s * QST;
          mbar_expect(fb, QST);
#pragma unroll
          for (int p = 0; p < 3; p++) {
            tma2d_h(dst + p * 8192, &prm.wqkv64, fb, 576 * p + 72 * j + 8 * hh, 64 * kb, pol);
            tma2d(dst + 24576 + p * 1024, &prm.wqkv8, fb, 576 * p + 72 * j + 64 - 64 * hh, 64 * kb);
          }
        }
        asm volatile("st.shared.u32 [%0], %1;" ::"r"(sb + SM_TAG), "r"((epoch + 1) & 1) : "memory");
        int col = 576 * j, kr = 0;
#pragma unroll 1
        for (int n = 0; n < N_G2; n++) {
          const uint32_t fb = bar + 8 * (B_F + (n & 7)), dst = sb + SM_RING + (n & 3) * BST;
          mbar_expect(fb, BST);
          if (n >= 4) mbar_wait(bar + 8 * (B_E + ((n - 3) & 7)), ((n - 3) >> 3) & 1);
          else if (n != 2) mbar_wait(bar + 8 * (B_QE + (n == 3 ? 2 : n)), 0);
          tma2d_h(dst, &prm.wg, fb, col, kr, pol);
          tma2d_h(dst + 8192, &prm.wu, fb, col, kr, pol);
          if ((kr += 64) == 576) { kr = 0; col += 64; }
        }
        uint32_t seen = 0;
#pragma unroll 1
        for (int b = 0; b < 26; b++) {
          const int n = N_G2 + 2 * b;
          const uint32_t fb = bar + 8 * (B_F + (n & 7)), dst = sb + (b & 3) * G2ST;
          const int own = b < 10 || b == 20 || b == 21, jj = own ? j : (j ^ 1), lb = b < 10 ? b : b < 20 ? b - 10 : 10 + (b & 1), need = (3 * lb + 6) >> 2;
          if (b < 24) {
            if (b == 10 || b == 20 || b == 22) seen = 0;
            if (seen < need) { seen = flag_wait_v(FLAG_H(m * 8 + jj), 9 * epoch + need) - 9 * epoch; fence_async(); }
          } else {
            flag_wait(FLAG_O((cta & ~1) + b - 24), epoch + 1);
            fence_async();
          }
          mbar_wait(bar + 8 * (B_E + ((n - 5) & 7)), ((n - 5) >> 3) & 1);
          if (b == 0) STAMPW(16);
          mbar_expect(fb, G2ST);
          if (b < 24) {
            bulk_g2s(dst, g_H + (m * 576 + 72 * jj + 6 * lb) * 512, 12288, fb);
#pragma unroll
            for (int a = 0; a < 4; a++) tma5d(dst + 12288 + a * 6144, &prm.wd[0], fb, ACOL(a), 36 * jj + 3 * lb);
            tma5d(dst + 36864, &prm.wd[1 + hh], fb, 0, 36 * jj + 3 * lb);
          } else {
            const int r = b - 24;
            bulk_g2s(dst, g_O + ((cta & ~1) + r) * 9 * 512 + r * 1024, 12288, fb);
#pragma unroll
            for (int a = 0; a < 4; a++) tma3d(dst + 12288 + a * 6144, &prm.wo3[0], fb, ACOL(a), 4 * (j & 6) + 5 * r);
            tma3d(dst + 36864, &prm.wo3[1 + hh], fb, 0, 4 * (j & 6) + 5 * r);
          }
          if (b == 0) STAMPW(17);
        }
        mbar_wait(bar + 8 * B_SP, 0);
        mbar_expect(bar + 8 * B_OL, 49152 + 32768);
        tma2d(sb + SM_RES, &prm.xm, bar + 8 * B_OL, ACOL(3), 128 * m);
        __nanosleep(200);
        tma2d(sb + SM_RES + 16384, &prm.xm, bar + 8 * B_OL, 256 + 32 * hh, 128 * m);
#pragma unroll 1
        for (int i = 0; i < 4; i++) {
          __nanosleep(200);
          tma3d(sb + SM_LB + i * 4096, &prm.wo2[0], bar + 8 * B_OL, ACOL(3), 8 * i + 3);
          tma3d(sb + SM_LB + 24576 + i * 4096, &prm.wo2[1 + hh], bar + 8 * B_OL, 0, 8 * i + 3);
          tma3d(sb + SM_LB + 16384 + i * 2048, &prm.wo16[0], bar + 8 * B_OL, ACOL(3), 8 * i);
          tma3d(sb + SM_LB + 40960 + i * 2048, &prm.wo16[1 + hh], bar + 8 * B_OL, 0, 8 * i);
        }
      }
    } else if (pw == 1) {
      if (lane == 0) {
        const int hx = hh * 3;
        int u = 0, kslot = 0, vrow = 0, kb = 0;
#pragma unroll 1
        for (int n = 0; n <= N_END; n++) {
          const uint32_t fb = bar + 8 * (B_F + (n & 7)), dst = n < N_AO ? sb + SM_KV + kslot * KVST : sb + SM_KV2 + (n - N_AO) * KVST;
          const bool att = n >= N_G2 || (n >= NG0 && kb != 0);
          if (++kb == 9) kb = 0;
          if (n >= N_AO) mbar_wait(bar + 8 * (B_E + ((n - 7) & 7)), ((n - 7) >> 3) & 1);
          mbar_expect(fb, !att || u < 2 ? 0 : (u == 2 || u == 128) ? KVST / 2 : KVST);
          if (n >= N_AO || (n > N_G2 && !(n & 1))) mbar_expect(fb, 0);
          if (u == 2 && att) { flag_wait(FLAG_KV(0, j), 16 * epoch + 16); fence_async(); STAMPW(18); }
          if (n >= 4 && n < N_AO) mbar_wait(bar + 8 * (B_E + ((n - 3) & 7)), ((n - 3) >> 3) & 1);
          if (att) {
            const int krow = (4 * j + ((u >> 5) ^ hx)) * 256 + ((u + 2 * m) & 31) * 8;
            if (u >= 2 && u < 128) tma2d(dst, &prm.kv, fb, 0, krow);
            if (u >= 3) tma2d(dst + 3072, &prm.kv, fb, 128, vrow);
            vrow = krow; u++;
            if (++kslot == 3) kslot = 0;
            if (u == 16) { flag_wait(FLAG_KV(1, j), 16 * epoch + 16); fence_async(); }
          }
        }
      }
    } else if (pw == 2) {
      if (lane == 0) {
#pragma unroll 1
        for (int i = 1; i < 18; i++) asm volatile("prefetch.tensormap [%0];" ::"l"(&prm.xm + i) : "memory");
        mbar_wait(bar + 8 * B_SK1, 0);
        STAMPW(22);
        fence_gpu(); flag_add(FLAG_KV(0, j));
        STAMPW(20);
        mbar_wait(bar + 8 * B_SK2, 0);
        fence_gpu(); flag_add(FLAG_KV(1, j));
#pragma unroll 1
        for (int t = 0; t < 9; t++) { mbar_wait(bar + 8 * B_SH, t & 1); __nanosleep(1000); fence_gpu(); flag_add(FLAG_H(cta)); }
        mbar_wait(bar + 8 * B_SO1, 0);
        fence_gpu(); flag_add(FLAG_O(cta));
      }
    } else {
      mbar_wait(bar + 8 * (B_X + PF_Q), 0);
#pragma unroll 1
      for (int i = lane; i < 122; i += 32) pf_line(prm.pwqkv + (size_t)min(i * 128 + cta, 15551) * 64);
      mbar_wait(bar + 8 * (B_QE + PF_G1), 0);
#pragma unroll 1
      for (int t = -3; t < 9; t++) {
        if (t >= 0) { mbar_wait(bar + 8 * B_SH, t & 1); __nanosleep(1500); }
        if (t < 6) {
#pragma unroll 1
          for (int i = lane; i < 72; i += 32) pf_line((i >= 36 ? prm.pwu : prm.pwg) + (size_t)(36 * m + (i >= 36 ? i - 36 : i)) * FF + 576 * j + 64 * (t + 3));
        }
        if ((t == 2 || t == 6 || t == 8)) {
          const uint32_t* kv = g_KV + (size_t)(4 * j + ((t == 2 ? 1 : t == 6 ? 2 : 3) ^ (hh * 3))) * SEQ * 20 + m * 2560;
#pragma unroll 1
          for (int i = lane; i < 80; i += 32) pf_line(kv + i * 32);
        }
        if (t >= 5) {
#pragma unroll 1
          for (int i = lane; i < 81; i += 32) {
            const int l = (2 * m + hh) * 81 + i, r = l / 9;
            pf_line(prm.pwd + (size_t)(1152 * (j >> 1) + 576 * (r / 144) + 144 * (t - 5) + r % 144) * DM + 64 * (l % 9));
          }
        }
      }
      if (cta * 41 + lane < 5184) pf_line(prm.pwo + (size_t)(cta * 41 + lane) * 64);
      if (lane < 9 && cta * 41 + 32 + lane < 5184) pf_line(prm.pwo + (size_t)(cta * 41 + 32 + lane) * 64);
      if (lane == 0) {
      mbar_wait(bar + 8 * B_SP, 0);
      const int q = j >> 1;
#pragma unroll 1
      for (int i = 0; i < 14; i++) {
        bulk_s2g(g_P + cta * 3584 + i * 256, sb + SM_SEND + i * 4096, 4096);
        asm volatile("cp.async.bulk.commit_group;\ncp.async.bulk.wait_group.read 2;" ::: "memory");
      }
      asm volatile("cp.async.bulk.wait_group 0;" ::: "memory");
      fence_gpu();
      flag_add(FLAG_P(cta));
      STAMPW(15);
      mbar_expect(bar + 8 * B_RX, 73728);
#pragma unroll 1
      for (int a = 0; a < 3; a++) {
        const int src = m * 8 + 2 * ((q + 3 - a) & 3) + hh;
        flag_wait(FLAG_P(src), epoch + 1);
        fence_async();
        bulk_g2s(sb + SM_RECV + a * 24576, g_P + src * 3584 + a * 1024, 16384, bar + 8 * B_RX);
        bulk_g2s(sb + SM_RECV + a * 24576 + 16384, g_P + src * 3584 + 3072, 8192, bar + 8 * B_RX);
      }
      STAMPW(25);
      *FLAG_EPOCH(cta) = epoch + 1;
      }
    }
  } else {
    const int tid = threadIdx.x;
    const int t = lane & 3;
    const uint32_t l0 = lane == 0;
    const uint32_t adesc = (((sb + SM_XN + wg * 8192) & 0x3FFFF) >> 4) | LO_A;
    const uint32_t bdesc = (((sb + SM_RING) & 0x3FFFF) >> 4) | LO_B;
    const uint32_t kdesc0 = (((sb + SM_KV) & 0x3FFFF) >> 4) | LO_K;
    const int hx = (j & 1) * 3;
    float accA[64], accB[64];
    Att a;
    uint32_t gs = 0, s8 = 0, fph = 0;
#define G1_ISSUE(ACC, AD, BD) _Pragma("unroll") for (int k = 0; k < 4; k++) wg_ss_n128<HI_SW128, HI_SW128>(ACC, (AD) + k * 2, (BD) + k * 128);
#define G1_ISSUE_Z(ACC, BD)                                                                                    \
  wg_ss_z_n128<HI_SW128, HI_SW128>(ACC, adesc, BD);                                                            \
  _Pragma("unroll") for (int k = 1; k < 4; k++) wg_ss_n128<HI_SW128, HI_SW128>(ACC, adesc + k * 2, (BD) + k * 128);
#define F_BAR (bar + 8 * B_F + 8 * s8)
#define F_PH fph
#define RELEASE() mbar_arrive_if(bar + 8 * B_E + 8 * s8, l0);
#define NEXT_SLOT() { gs++; fph ^= s8 == 7; s8 = s8 == 7 ? 0 : s8 + 1; }
#define NEXT_B() bd = bd == bdesc + 3072 ? bdesc : bd + 1024;
#define G1_ONLY() { mbar_wait(F_BAR, F_PH); wg_fence(); G1_ISSUE(accA, adesc + gs * 1024, bdesc + (gs & 3) * 1024) wg_commit(); wg_wait<1>(); RELEASE() NEXT_SLOT() }
    {
      const int lr = wr * 16 + (lane & 15);
      uint32_t ra[4];
#pragma unroll
      for (int k = 0; k < 4; k++) ra[k] = sb + SM_XN + lr * 128 + (((2 * k + (lane >> 4)) ^ (lr & 7)) << 4);
      asm volatile("setmaxnreg.inc.sync.aligned.u32 240;");
      float aq[96], ar[12];
#pragma unroll
      for (int i = 0; i < 96; i++) aq[i] = __int_as_float(lane >> 5);
#pragma unroll
      for (int i = 0; i < 12; i++) ar[i] = __int_as_float(lane >> 5);
      pin<96>(aq); pin<12>(ar);
      float cs[2][4] = {}, q0 = 0.f, q1 = 0.f, q2 = 0.f, q3 = 0.f;
#pragma unroll 1
      for (int c = 0; c < 9; c++) {
        mbar_wait(bar + 8 * (B_X + c), 0);
        uint32_t v[4][4];
#pragma unroll
        for (int k = 0; k < 4; k++) ldsm4(v[k], ra[k] + c * 16384);
#pragma unroll
        for (int k = 0; k < 4; k++) {
          mma_ones(cs[k & 1], v[k]);
#pragma unroll
          for (int e = 0; e < 4; e += 2) {
            const float x0 = bf_lo(v[k][e]), x1 = bf_hi(v[k][e]), y0 = bf_lo(v[k][e + 1]), y1 = bf_hi(v[k][e + 1]);
            q0 = fmaf(x0, x0, q0); q1 = fmaf(x1, x1, q1); q2 = fmaf(y0, y0, q2); q3 = fmaf(y1, y1, q3);
          }
        }
      }
      STAMP(11);
      const float mean0 = (cs[0][0] + cs[1][0]) * (1.f / 576.f), mean1 = (cs[0][2] + cs[1][2]) * (1.f / 576.f);
      q0 += q1; q2 += q3;
      q0 += __shfl_xor_sync(0xffffffffu, q0, 1); q2 += __shfl_xor_sync(0xffffffffu, q2, 1);
      q0 += __shfl_xor_sync(0xffffffffu, q0, 2); q2 += __shfl_xor_sync(0xffffffffu, q2, 2);
      float var0 = fmaf(q0, 1.f / 576.f, -mean0 * mean0), var1 = fmaf(q2, 1.f / 576.f, -mean1 * mean1);
      if (__any_sync(0xffffffffu, !(mean0 * mean0 <= 8.f * var0) || !(mean1 * mean1 <= 8.f * var1))) {
        q0 = q2 = 0.f;
#pragma unroll 1
        for (int i = 0; i < 36; i++) {
          uint32_t v[4];
          ldsm4(v, ((ra[0] + (i >> 2) * 16384) ^ ((i & 3) << 5)));
#pragma unroll
          for (int e = 0; e < 4; e += 2) {
            const float x0 = bf_lo(v[e]) - mean0, x1 = bf_hi(v[e]) - mean0, y0 = bf_lo(v[e + 1]) - mean1, y1 = bf_hi(v[e + 1]) - mean1;
            q0 = fmaf(x0, x0, fmaf(x1, x1, q0)); q2 = fmaf(y0, y0, fmaf(y1, y1, q2));
          }
        }
        q0 += __shfl_xor_sync(0xffffffffu, q0, 1); q2 += __shfl_xor_sync(0xffffffffu, q2, 1);
        q0 += __shfl_xor_sync(0xffffffffu, q0, 2); q2 += __shfl_xor_sync(0xffffffffu, q2, 2);
        var0 = q0 * (1.f / 576.f); var1 = q2 * (1.f / 576.f);
      }
      const float inv0 = rcp_fast(bf_round(sqrt_fast(bf_round(bf_round(var0) + 1e-5f)))), inv1 = rcp_fast(bf_round(sqrt_fast(bf_round(bf_round(var1) + 1e-5f))));
      const uint32_t mb0 = pack(mean0, mean0), mb1 = pack(mean1, mean1);
      const uint32_t h0 = pack(inv0, inv0), h1 = pack(inv1, inv1);
      const uint32_t e0 = pack(inv0 - bf_lo(h0), inv0 - bf_lo(h0)), e1 = pack(inv1 - bf_lo(h1), inv1 - bf_lo(h1));
      uint32_t v[4][4], xn[4][4];
#pragma unroll
      for (int k = 0; k < 4; k++) ldsm4(v[k], ra[k]);
      STAMP(1);
      const uint32_t rdesc = (((sb + SM_RING + 24576) & 0x3FFFF) >> 4) | LO_R;
      uint32_t s = 0, ph = 0;
#pragma unroll 1
      for (int kb = 0; kb < 9; kb++) {
#pragma unroll
        for (int k = 0; k < 4; k++) {
          xn[k][0] = bscale2(bsub2(v[k][0], mb0), h0, e0); xn[k][1] = bscale2(bsub2(v[k][1], mb1), h1, e1);
          xn[k][2] = bscale2(bsub2(v[k][2], mb0), h0, e0); xn[k][3] = bscale2(bsub2(v[k][3], mb1), h1, e1);
        }
        pin<16>(&xn[0][0]);
        mbar_wait(bar + 8 * B_QF + 8 * s, ph);
        wg_fence();
#pragma unroll
        for (int k = 0; k < 4; k++) {
          wg_rs_n192<HI_SW128>(aq, xn[k][0], xn[k][1], xn[k][2], xn[k][3], bdesc + s * (QST >> 4) + k * 128);
          wg_rs_n24<HI_R>(ar, xn[k][0], xn[k][1], xn[k][2], xn[k][3], rdesc + s * (QST >> 4) + k * 16);
        }
        wg_commit();
#pragma unroll
        for (int k = 0; k < 4; k++) stsm4(ra[k] + kb * 16384, xn[k][0], xn[k][1], xn[k][2], xn[k][3]);
#pragma unroll
        for (int k = 0; k < 4; k++) ldsm4(v[k], ra[k] + (kb < 8 ? kb + 1 : 8) * 16384);
        if (kb == 8) {
          asm volatile("fence.proxy.async.shared::cta;" ::: "memory");
          __syncwarp();
          mbar_arrive_if(bar + 8 * B_NR + 8 * wg, l0);
        }
        wg_wait<0>();
        mbar_arrive_if(bar + 8 * B_QE + 8 * s, l0);
        if (++s == 3) { s = 0; ph ^= 1; }
      }
      pin<96>(aq); pin<12>(ar);
      STAMP(2);
      uint32_t* kvp = g_KV + (size_t)(4 * j) * SEQ * 20 + (16 * m + 2 * wr) * 160 + lane;
      uint32_t pk[2][9][2];
#pragma unroll
      for (int p = 0; p < 2; p++)
#pragma unroll
        for (int i = 0; i < 9; i++) {
          const float* src = i < 8 ? &aq[(8 * (p + 1) + i) * 4] : &ar[4 * (p + 1)];
          pk[p][i][0] = pack(src[0], src[1]); pk[p][i][1] = pack(src[2], src[3]);
        }
      const uint32_t sk = sb + SM_KV + wg * KVST + (wr & 3) * 768 + lane * 4;
      mbar_wait(bar + 8 * (B_QE + 2), 0);
      if (hx) {
#pragma unroll
        for (int p = 0; p < 2; p++) { rotate9(pk[p]); }
        store_kv_head<3>(pk, kvp, lane, sk, sk + KVST + 3072);
      } else store_kv_head<0>(pk, kvp, lane, sk, sk + KVST + 3072);
      asm volatile("fence.proxy.async.shared::cta;" ::: "memory");
      __syncwarp();
      mbar_arrive_if(bar + 8 * B_SK1, l0);
      mbar_arrive_if(bar + 8 * B_LK, l0);
      STAMP(3);
      mbar_wait(bar + 8 * B_NR + 8 * wg, 0);
      mbar_wait(bar + 8 * B_F, 0);
      wg_fence();
      G1_ISSUE_Z(accA, bdesc)
      wg_commit();
      RELEASE()
      NEXT_SLOT()
      mbar_wait(F_BAR, F_PH);
      wg_fence();
      G1_ISSUE(accA, adesc + 1024, bdesc + 1024)
      wg_commit();
      uint32_t pq[9][2];
#pragma unroll
      for (int i = 0; i < 9; i++) {
        const float* src = i < 8 ? &aq[i * 4] : &ar[0];
        pq[i][0] = bscale2(pack(src[0], src[1]), QS_HI, QS_LO); pq[i][1] = bscale2(pack(src[2], src[3]), QS_HI, QS_LO);
      }
      if (hx) rotate9(pq);
      pin<18>(&pq[0][0]);
      wg_wait<1>();
      RELEASE()
      NEXT_SLOT()
      G1_ONLY()
      mbar_wait(F_BAR, F_PH);
      wg_fence();
      G1_ISSUE(accA, adesc + 3 * 1024, bdesc + 3 * 1024)
      wg_commit();
      if (hx) store_kv_head<0>(pk, kvp, lane); else store_kv_head<3>(pk, kvp, lane);
      store_kv_head<1>(pk, kvp, lane);
      store_kv_head<2>(pk, kvp, lane);
      __syncwarp();
      mbar_arrive_if(bar + 8 * B_SK2, l0);
      wg_wait<1>();
      RELEASE()
      NEXT_SLOT()
      mbar_wait(F_BAR, F_PH);
      wg_fence();
      G1_ISSUE(accA, adesc + 4 * 1024, bdesc)
      wg_commit();
      uint4* qp = reinterpret_cast<uint4*>(g_Q) + cta * 4 * 512 + tid;
#pragma unroll
      for (int hp = 0; hp < 4; hp++) {
        const bool up = t < hp;
        const uint4 u = make_uint4(up ? pq[2 * hp + 1][0] : pq[2 * hp][0], up ? pq[2 * hp + 1][1] : pq[2 * hp][1],
                                   up ? pq[2 * hp + 2][0] : pq[2 * hp + 1][0], up ? pq[2 * hp + 2][1] : pq[2 * hp + 1][1]);
        const uint4 v = make_uint4(t == hp ? pq[2 * hp + 2][0] : 0u, t == hp ? pq[2 * hp + 2][1] : 0u, 0u, 0u);
        qp[hp * 512] = u; qp[hp * 512 + 256] = v;
        if (hp == 0 || (hp == 3 && hx)) { a.q[0] = u.x; a.q[1] = u.y; a.q[2] = u.z; a.q[3] = u.w; a.q[4] = v.x; a.q[5] = v.y; }
      }
      a.q[6] = __shfl_sync(0xffffffffu, lane, 0); a.q[7] = __shfl_sync(0xffffffffu, lane >> 1, 1);
#pragma unroll
      for (int i = 0; i < 16; i++) a.p[i] = 0;
#pragma unroll
      for (int i = 0; i < 12; i++) a.o[i] = 0.f;
      pin<16>(a.p); pin<12>(a.o); pin<8>(a.q);
      wg_wait<1>();
      RELEASE()
      NEXT_SLOT()
    }
    static_assert(NG0 == 5 || NG0 == 7, "item boundaries must fall into even F tiles / even GEMM2 slots");
#pragma unroll 1
    while (gs < NG0) G1_ONLY()
    STAMP(4);
    mbar_wait(bar + 8 * B_LK, 0);
    mbar_wait(F_BAR, F_PH);
    STAMP(23);
    uint32_t kd = kdesc0;
    uint32_t it = 0;
    uint32_t ox0 = 0, ox1 = 0;
    uint32_t qn[6] = {0, 0, 0, 0, 0, 0};
    uint32_t* hdst = g_H + ((m * 576 + 72 * j + (t >> 1)) * 128 + 16 * wr + (lane >> 2)) * 4 + 2 * (t & 1);
    uint32_t ad = adesc + NG0 * 1024, bd = bdesc + (gs & 3) * 1024;

#define ITEM_FIRST()                                                                                           \
  {                                                                                                            \
    pin<12>(a.o);                                                                                              \
    if (it != 0) {                                                                                             \
      uint32_t w[4];                                                                                           \
      o_normalise(a.o, w, ox0, ox1, ((it >> 5) - 1) ^ hx, lane, sb + SM_BAD, wr);                              \
      uint32_t* d = g_O + cta * 9 * 512 + (((it >> 5) - 1) ^ hx) * 1024 + wr * 64 + lane;                      \
      d[0] = w[0]; d[32] = w[1]; d[512] = w[2]; d[544] = w[3];                                                 \
    }                                                                                                          \
    if (it == 96) mbar_arrive_if(bar + 8 * B_SO1, l0 & (bad_heads(sb + SM_BAD, wr) == 0));                     \
    first_tile(a, (it >> 5) ^ hx, lane);                                                                       \
  }
#define KV_ADVANCE() { kd = kd == kdesc0 + 768 ? kdesc0 : kd + 384; }
#define SOFTMAX_NEXT() { softmax_a(a); softmax_b(a); mbar_wait(F_BAR, F_PH); softmax_c(a); }
#define EPI_STEP(ACCN, ACCO)                                                                                   \
  {                                                                                                            \
    wg_fence();                                                                                                \
    G1_ISSUE_Z(ACCN, bd)                                                                                       \
    wg_commit();                                                                                               \
    wg_wait<1>();                                                                                              \
    pin<64>(ACCO);                                                                                             \
    RELEASE()                                                                                                  \
    NEXT_SLOT()                                                                                                \
    ad = adesc + 1024; NEXT_B()                                                                                \
    const uint32_t ok = mbar_test(F_BAR, F_PH);                                                                \
    h_epilogue(ACCO, hdst);                                                                                    \
    hdst += 4096;                                                                                              \
    __syncwarp();                                                                                              \
    mbar_arrive_if(bar + 8 * B_SH, l0);                                                                        \
    if (__builtin_expect(!ok, 0)) mbar_wait(F_BAR, F_PH);                                                                                            \
  }
#define ATT_LOOP1(ACC, ITEMS)                                                                                  \
  do {                                                                                                         \
    wg_fence();                                                                                                \
    issue_att(a, kd);                                                                                          \
    wg_commit();                                                                                               \
    G1_ISSUE(ACC, ad, bd)                                                                                      \
    wg_commit();                                                                                               \
    wg_wait<1>();                                                                                              \
    pin<32>(a.s);                                                                                              \
    RELEASE()                                                                                                  \
    TRACE()                                                                                                    \
    if (ITEMS) { if (__builtin_expect(((it + 1) & 31) < 2, 0)) { if (it & 1) { _Pragma("unroll") for (int i = 0; i < 6; i++) asm volatile("mov.b32 %0, %1;" : "=r"(a.q[i]) : "r"(qn[i])); } else { if (it == 64) fetch_q(qn, cta, 3 ^ hx, tid); ITEM_FIRST() } } } \
    NEXT_SLOT() it++;                                                                                                \
    KV_ADVANCE()                                                                                               \
    ad += 1024; NEXT_B()                                                                                       \
    SOFTMAX_NEXT()                                                                                             \
    pin<8>(a.q);                                                                                               \
  } while (ad != adesc + 9 * 1024);
#pragma unroll 1
    for (int pr = 0;; pr++) {
      ATT_LOOP1(accA, true)
      if (pr == 4) break;
      if (pr == 2) STAMP(29);
      EPI_STEP(accB, accA)
      if (pr == 2) STAMP(30);
      ATT_LOOP1(accB, false)
      if (pr == 2) STAMP(31);
      if (pr & 1) fetch_q(qn, cta, ((pr >> 1) + 1) ^ hx, tid);
      EPI_STEP(accA, accB)
      if (pr == 2) STAMP(21);
      if (pr == 3) STAMP(14);
    }
    STAMP(5);
    wg_wait<0>();
    pin<64>(accA);
    h_epilogue(accA, hdst);
    __syncwarp();
    mbar_arrive_if(bar + 8 * B_SH, l0);
    mbar_wait(bar + 8 * B_E, 0);
    asm volatile("st.shared.v4.b32 [%0], {%1,%2,%3,%4};\nst.shared.v2.b32 [%5], {%6,%7};" ::"r"(sb + SM_QS + tid * 16), "r"(qn[0]), "r"(qn[1]), "r"(qn[2]), "r"(qn[3]),
                 "r"(sb + SM_QS + 4096 + tid * 8), "r"(qn[4]), "r"(qn[5]) : "memory");
    STAMP(6);
    STAMP(12);

    float acc2[144];
    const uint32_t a2desc = (((sb + wg * 1024) & 0x3FFFF) >> 4) | LO_O;
    const uint32_t b2desc = (((sb + 12288) & 0x3FFFF) >> 4) | LO_B48;
    ad = a2desc; bd = b2desc;
#define G2_LO(K) wg_ss_n128<HI_O, HI_SW128>(acc2, ad + (K) * 256, bd + (K) * 128);
#define G2_HI(K) wg_ss_n160<HI_O, HI_SW128>(acc2 + 64, ad + (K) * 256, bd + (K) * 128 + 768);
#define ATT_PAIR(ZERO)                                                                                         \
  {                                                                                                            \
    wg_fence();                                                                                                \
    issue_att(a, kd);                                                                                          \
    wg_commit();                                                                                               \
    if (ZERO) { wg_ss_z_n128<HI_O, HI_SW128>(acc2, ad, bd); wg_ss_z_n160<HI_O, HI_SW128>(acc2 + 64, ad, bd + 768); } \
    else { G2_LO(0) G2_HI(0) }                                                                                 \
    G2_LO(1)                                                                                                   \
    wg_commit();                                                                                               \
    wg_wait<1>();                                                                                              \
    pin<32>(a.s);                                                                                              \
    RELEASE()                                                                                                  \
    TRACE()                                                                                                    \
    if (!(ZERO)) { if (__builtin_expect(gs == N_G2 + 96 - IT_G2, 0)) ITEM_FIRST() }                                    \
    NEXT_SLOT() it++;                                                                                                \
    KV_ADVANCE()                                                                                               \
    SOFTMAX_NEXT()                                                                                             \
    pin<8>(a.q);                                                                                               \
    wg_fence();                                                                                                \
    issue_att(a, kd);                                                                                          \
    wg_commit();                                                                                               \
    G2_HI(1) G2_LO(2) G2_HI(2)                                                                                 \
    wg_commit();                                                                                               \
    wg_wait<1>();                                                                                              \
    pin<32>(a.s);                                                                                              \
    RELEASE()                                                                                                  \
    TRACE()                                                                                                    \
    if (!(ZERO) && __builtin_expect(gs == N_G2 + 95 - IT_G2, 0)) {                                                     \
      const int ft = fresh_tid();                                                                              \
      asm volatile("ld.shared.v4.b32 {%0,%1,%2,%3}, [%6];\nld.shared.v2.b32 {%4,%5}, [%7];" : "=r"(a.q[0]), "=r"(a.q[1]), "=r"(a.q[2]), "=r"(a.q[3]), \
                   "=r"(a.q[4]), "=r"(a.q[5]) : "r"(sb + SM_QS + ft * 16), "r"(sb + SM_QS + 4096 + ft * 8) : "memory"); \
    }                                                                                                          \
    NEXT_SLOT() it++;                                                                                                \
    KV_ADVANCE()                                                                                               \
    ad = ad == a2desc + 3 * 2688 ? a2desc : ad + 2688; bd = ad + (b2desc - a2desc);                                \
    SOFTMAX_NEXT()                                                                                             \
    pin<8>(a.q);                                                                                               \
  }
    ATT_PAIR(true)
#pragma unroll 1
    for (int half = 0; half < 2; half++) {
      const uint32_t stop = half ? N_AO : N_G2 + 46;
      do ATT_PAIR(false) while (gs != stop);
      if (!half) {
        const uint32_t bad = bad_heads(sb + SM_BAD, wr);
        if (bad) { repair_rows(cta, wr, bad, 3 ^ hx, false); mbar_arrive_if(bar + 8 * B_SO1, l0); }
      }
    }
    STAMP(13);
    wg_wait<0>();
    pin<144>(acc2);
    mbar_wait(bar + 8 * (B_E + 1), 0);
    stage_partials(acc2, sb + SM_SEND, fresh_tid());
    asm volatile("fence.proxy.async.shared::cta;" ::: "memory");
    __syncwarp();
    mbar_arrive_if(bar + 8 * B_SP, l0);
    static_assert(N_END - N_AO == 8, "SM_KV2 layout");
    kd = (((sb + SM_KV2) & 0x3FFFF) >> 4) | LO_K;
    do {
      wg_fence();
      issue_att(a, kd);
      wg_commit();
      wg_wait<0>();
      pin<32>(a.s);
      RELEASE()
      TRACE()
      NEXT_SLOT() it++;
      kd += 384;
      SOFTMAX_NEXT()
    } while (gs != N_END);
    STAMP(7);
    wg_fence();
    issue_pv(a, kd);
    wg_commit();
    int tid2, bid2;
    asm volatile("mov.u32 %0, %%tid.x;" : "=r"(tid2));
    asm volatile("mov.u32 %0, %%ctaid.x;" : "=r"(bid2));
    const int m2 = bid2 & 15, j2 = bid2 >> 4;
    uint32_t tag;
    asm volatile("ld.shared.u32 %0, [%1];" : "=r"(tag) : "r"(sb + SM_TAG) : "memory");
    wg_wait<0>();
    pin<12>(a.o);
    {
      uint32_t w[4];
      o_normalise(a.o, w, ox0, ox1, 3 ^ hx, lane, sb + SM_BAD, wr);
      ox0 = __shfl_xor_sync(0xffffffffu, ox0, 2); ox1 = __shfl_xor_sync(0xffffffffu, ox1, 2);
      const uint32_t bad = bad_heads(sb + SM_BAD, wr);
      if (bad) {
        uint32_t* d = g_O + cta * 9 * 512 + wr * 64 + lane;
        uint32_t* h = d + (3 ^ hx) * 1024;
        h[0] = w[0]; h[32] = w[1]; h[512] = w[2]; h[544] = w[3]; d[4096] = ox0; d[4128] = ox1;
        __syncwarp();
        repair_rows(cta, wr, bad, 3 ^ hx, true);
        w[0] = __ldcg(h); w[1] = __ldcg(h + 32); w[2] = __ldcg(h + 512); w[3] = __ldcg(h + 544); ox0 = __ldcg(d + 4096); ox1 = __ldcg(d + 4128);
      }
      asm volatile("st.relaxed.gpu.global.v4.b32 [%0], {%1,%2,%3,%4};" ::"l"(g_L + (m2 * 8 + j2) * 384 + tid2), "r"((w[0] & ~1u) | tag), "r"((w[1] & ~1u) | tag),
                   "r"((w[2] & ~1u) | tag), "r"((w[3] & ~1u) | tag) : "memory");
      asm volatile("st.relaxed.gpu.global.v2.b32 [%0], {%1,%2};" ::"l"(reinterpret_cast<uint2*>(g_L + (m2 * 8 + j2) * 384 + 256) + tid2), "r"((ox0 & ~1u) | tag),
                   "r"((ox1 & ~1u) | tag) : "memory");
    }
    STAMP(8);
    uint32_t la[48];
    const uint4* p4 = g_L + m2 * 8 * 384 + tid2;
    const uint2* p2 = reinterpret_cast<const uint2*>(g_L + m2 * 8 * 384 + 256) + tid2;
#define LOAD_LA2() { ld2<0>(la + 32, p2); ld2<6144>(la + 34, p2); ld2<12288>(la + 36, p2); ld2<18432>(la + 38, p2); \
                     ld2<24576>(la + 40, p2); ld2<30720>(la + 42, p2); ld2<36864>(la + 44, p2); ld2<43008>(la + 46, p2); }
#define LOAD_LA4() { ld4<0>(la, p4); ld4<6144>(la + 4, p4); ld4<12288>(la + 8, p4); ld4<18432>(la + 12, p4); \
                     ld4<24576>(la + 16, p4); ld4<30720>(la + 20, p4); ld4<36864>(la + 24, p4); ld4<43008>(la + 28, p4); }
    float fin[48];
    uint32_t id[4][4];
    {
      uint32_t id2[4][4];
#pragma unroll
      for (int k = 0; k < 4; k++) {
        asm volatile("ld.volatile.shared.v4.b32 {%0,%1,%2,%3}, [%4];" : "=r"(id[k][0]), "=r"(id[k][1]), "=r"(id[k][2]), "=r"(id[k][3])
                     : "r"(sb + SM_ID + ((wr & 3) == k ? lane : 1) * 16) : "memory");
#pragma unroll
        for (int e = 0; e < 4; e++) id2[k][e] = id[k][e] + (id[k][e] & 0x00800080u);
      }
      pin<16>(&id[0][0]); pin<16>(&id2[0][0]);
      const uint32_t xdesc = (((sb + SM_RES + wg * 8192) & 0x3FFFF) >> 4) | LO_B;
      STAMP(26);
      mbar_wait(bar + 8 * B_OL, 0);
      STAMP(27);
      wg_fence();
      wg_rsb_z_n64<HI_SW128>(fin, id2[0][0], id2[0][1], id2[0][2], id2[0][3], xdesc);
      wg_rs_z_n32<HI_SW128>(fin + 32, id2[0][0], id2[0][1], id2[0][2], id2[0][3], xdesc + 1024);
#pragma unroll
      for (int k = 1; k < 4; k++) {
        wg_rsb_n64<HI_SW128>(fin, id2[k][0], id2[k][1], id2[k][2], id2[k][3], xdesc + k * 128);
        wg_rs_n32<HI_SW128>(fin + 32, id2[k][0], id2[k][1], id2[k][2], id2[k][3], xdesc + 1024 + k * 128);
      }
      wg_commit();
    }
    STAMP(28);
    const uint32_t pdesc = (((sb + SM_RECV + wg * 8192) & 0x3FFFF) >> 4) | LO_B, hdesc = (((sb + SM_RECV + 16384 + wg * 4096) & 0x3FFFF) >> 4) | LO_B;
#define RX_MMAS()                                                                                              \
  wg_fence();                                                                                                  \
  _Pragma("unroll") for (int a3 = 0; a3 < 3; a3++)                                                             \
    _Pragma("unroll") for (int k = 0; k < 4; k++) {                                                            \
      wg_rsb_n64<HI_SW128>(fin, id[k][0], id[k][1], id[k][2], id[k][3], pdesc + a3 * 1536 + k * 128);          \
      wg_rs_n32<HI_SW64>(fin + 32, id[k][0], id[k][1], id[k][2], id[k][3], hdesc + a3 * 1536 + k * 64);        \
    }                                                                                                          \
  wg_commit();
    mbar_wait(bar + 8 * B_RX, 0);
    STAMP(24);
    RX_MMAS()
    wg_wait<0>();
    pin<48>(fin);
#pragma unroll
    for (int i = 0; i < 48; i++) fin[i] += acc2[96 + i];
    pin<48>(fin);
    for (uint32_t tries = 0; tries < 0x400000u; tries++) {
      const uint32_t* pw = reinterpret_cast<const uint32_t*>(g_L + (m2 * 8 + (lane & 7)) * 384 + 256) + (tid2 | 31) * 2 + 1;
      uint32_t bad;
      do {
        asm volatile("ld.relaxed.gpu.global.b32 %0, [%1];" : "=r"(bad) : "l"(pw) : "memory");
      } while (!__all_sync(0xffffffffu, !((bad ^ tag) & 1)) && ++tries < 0x400000u);
      LOAD_LA4()
      LOAD_LA2()
      bad = 0;
#pragma unroll
      for (int i = 0; i < 48; i++) bad |= la[i] ^ tag;
      if (__all_sync(0xffffffffu, !(bad & 1))) break;
    }
#pragma unroll
    for (int i = 0; i < 48; i++) la[i] ^= tag;
    pin<48>(la);
    STAMP(19);
    const uint32_t ldesc = (((sb + SM_LB) & 0x3FFFF) >> 4) | LO_B;
    wg_fence();
#pragma unroll
    for (int k = 0; k < 12; k++) {
      wg_rsb_n64<HI_SW128>(fin, la[4 * k], la[4 * k + 1], la[4 * k + 2], la[4 * k + 3], ldesc + k * 128);
      wg_rs_n32<HI_SW128>(fin + 32, la[4 * k], la[4 * k + 1], la[4 * k + 2], la[4 * k + 3], ldesc + 1536 + k * 128);
    }
    wg_commit();
    wg_wait<0>();
    pin<48>(fin);
    STAMP(9);
    final_epilogue(fin, prm, m2, j2 & 1, j2 >> 1, tid2);
    STAMP(10);
  }
}

typedef CUresult (*EncodeFn)(CUtensorMap*, CUtensorMapDataType, cuuint32_t, void*, const cuuint64_t*, const cuuint64_t*, const cuuint32_t*, const cuuint32_t*,
                             CUtensorMapInterleave, CUtensorMapSwizzle, CUtensorMapL2promotion, CUtensorMapFloatOOBfill);

void enc2d(EncodeFn enc, CUtensorMap* tm, const void* base, uint64_t w, uint64_t h, uint64_t pitch_elems, uint32_t bw, uint32_t bh, CUtensorMapSwizzle sw) {
  cuuint64_t dims[2] = {w, h}, str[1] = {pitch_elems * 2};
  cuuint32_t box[2] = {bw, bh}, es[2] = {1, 1};
  enc(tm, CU_TENSOR_MAP_DATA_TYPE_BFLOAT16, 2, const_cast<void*>(base), dims, str, box, es, CU_TENSOR_MAP_INTERLEAVE_NONE, sw,
      CU_TENSOR_MAP_L2_PROMOTION_L2_128B, CU_TENSOR_MAP_FLOAT_OOB_FILL_NONE);
}

}

extern "C" void kernel_launch(void* const* d_in, const int* in_sizes, int n_in, void* d_out, int out_size) {
  (void)in_sizes; (void)n_in; (void)out_size;
  const __nv_bfloat16* x = (const __nv_bfloat16*)d_in[0];
  const __nv_bfloat16* wqkv = (const __nv_bfloat16*)d_in[1];
  const __nv_bfloat16* wo = (const __nv_bfloat16*)d_in[2];
  const __nv_bfloat16* wg = (const __nv_bfloat16*)d_in[4];
  const __nv_bfloat16* wu = (const __nv_bfloat16*)d_in[5];
  const __nv_bfloat16* wd = (const __nv_bfloat16*)d_in[6];
  void* fn = nullptr;
  cudaDriverEntryPointQueryResult qr;
  cudaGetDriverEntryPoint("cuTensorMapEncodeTiled", &fn, cudaEnableDefault, &qr);
  EncodeFn enc = (EncodeFn)fn;
  void* kvp = nullptr;
  cudaGetSymbolAddress(&kvp, g_KV);
  Params p;
  enc2d(enc, &p.xm, x, DM, SEQ, DM, 64, 128, CU_TENSOR_MAP_SWIZZLE_128B);
  enc2d(enc, &p.kv, kvp, 320, 32 * 256, 320, 192, 8, CU_TENSOR_MAP_SWIZZLE_NONE);
  enc2d(enc, &p.wqkv64, wqkv, 3 * DM, DM, 3 * DM, 64, 64, CU_TENSOR_MAP_SWIZZLE_128B);
  enc2d(enc, &p.wqkv8, wqkv, 3 * DM, DM, 3 * DM, 8, 64, CU_TENSOR_MAP_SWIZZLE_NONE);
  enc2d(enc, &p.wg, wg, FF, DM, FF, 64, 64, CU_TENSOR_MAP_SWIZZLE_128B);
  enc2d(enc, &p.wu, wu, FF, DM, FF, 64, 64, CU_TENSOR_MAP_SWIZZLE_128B);
  for (int v = 0; v < 3; v++) {
    const cuuint64_t wdt = v ? 32 : DM;
    const int c0 = v ? 256 + 32 * (v - 1) : 0;
    for (int e = 0; e < 3; e++) {
      cuuint64_t d3[3] = {wdt, e == 2 ? 2u : 16u, 32}, s3[2] = {DM * 2, 18 * DM * 2};
      cuuint32_t b3[3] = {64, e == 2 ? 2u : 16u, e == 0 ? 3u : e == 1 ? 2u : 8u}, e3[3] = {1, 1, 1};
      enc(e == 0 ? &p.wo3[v] : e == 1 ? &p.wo2[v] : &p.wo16[v], CU_TENSOR_MAP_DATA_TYPE_BFLOAT16, 3, (void*)(wo + c0 + (e == 2 ? 16 * DM : 0)), d3, s3, b3, e3,
          CU_TENSOR_MAP_INTERLEAVE_NONE, CU_TENSOR_MAP_SWIZZLE_128B, CU_TENSOR_MAP_L2_PROMOTION_L2_128B, CU_TENSOR_MAP_FLOAT_OOB_FILL_NONE);
    }
    cuuint64_t dims[5] = {wdt, 2, 2, 4, FF / 16}, str[4] = {DM * 2, 8 * DM * 2, 2 * DM * 2, 16 * DM * 2};
    cuuint32_t box[5] = {64, 2, 2, 4, 3}, es[5] = {1, 1, 1, 1, 1};
    enc(&p.wd[v], CU_TENSOR_MAP_DATA_TYPE_BFLOAT16, 5, (void*)(wd + c0), dims, str, box, es, CU_TENSOR_MAP_INTERLEAVE_NONE,
        CU_TENSOR_MAP_SWIZZLE_128B, CU_TENSOR_MAP_L2_PROMOTION_L2_128B, CU_TENSOR_MAP_FLOAT_OOB_FILL_NONE);
  }
  p.x = x; p.pwqkv = wqkv; p.pwo = wo; p.pwg = wg; p.pwu = wu; p.pwd = wd;
  p.out = (__nv_bfloat16*)d_out;
  cudaFuncSetAttribute(fused_kernel, cudaFuncAttributeMaxDynamicSharedMemorySize, SM_TOTAL);
  fused_kernel<<<NCTA, 384, SM_TOTAL, cudaStreamPerThread>>>(p);
}
```

```cpp
#include <cuda_runtime.h>
#include <cuda.h>
#include <cuda_bf16.h>
#include <stdint.h>

namespace {

constexpr int SEQ = 2048, DM = 576, FF = 4608;
constexpr int NCTA = 128;

constexpr uint32_t SM_XN = 0;
constexpr uint32_t SM_RING = 147456;
constexpr uint32_t SM_KV = 212992;
constexpr uint32_t QST = 27648, BST = 16384, KVST = 6144;
constexpr uint32_t G2ST = 43008;
constexpr uint32_t SM_LB = 0, SM_RES = 49152, SM_SEND = 86016, SM_RECV = SM_SEND;
constexpr uint32_t SM_QS = 204800;
constexpr uint32_t SM_KV2 = SM_KV - 6 * KVST;
constexpr uint32_t SM_ID = 231424;
constexpr uint32_t SM_BAR = 231936;
constexpr uint32_t SM_TAG = 232436;
constexpr uint32_t SM_BAD = 232432;
constexpr uint32_t SM_TOTAL = 232448;
enum { B_F = 0, B_E = 8, B_QF = 16, B_QE = 19, B_SK1 = 22, B_SK2 = 23, B_SH = 24, B_SO1 = 25, B_LK = 26, B_SP = 27, B_OL = 28, B_RX = 29, B_NR = 30, B_X = 32, B_N = 41 };
constexpr int N_G2 = 81, N_AO = 133;
#define N_END (136 + NG0)
#define IT_G2 (73 - NG0)
constexpr int NG0 = 5;
constexpr int SM_B = 12;

constexpr uint32_t HI_SW128 = 0x40000040u;
constexpr uint32_t LO_A = 1u << 16;
constexpr uint32_t LO_B = 512u << 16;
constexpr uint32_t HI_R = 64u, LO_R = 8u << 16;
constexpr uint32_t HI_K = 24u, LO_K = 8u << 16;
constexpr uint32_t HI_V = 8u, LO_V = 24u << 16;
constexpr uint32_t LO_B48 = 384u << 16;
constexpr uint32_t HI_O = 8u, LO_O = 128u << 16;
constexpr uint32_t HI_SW64 = 0x80000020u;

constexpr uint32_t QS_HI = 0x3eae3eaeu, QS_LO = 0x39553955u;
constexpr float MOFF = 90.f;

struct __align__(64) Params {
  CUtensorMap xm, wqkv64, wqkv8, wg, wu, kv, wd[3], wo3[3], wo2[3], wo16[3];
  const __nv_bfloat16 *x, *pwqkv, *pwo, *pwg, *pwu, *pwd;
  __nv_bfloat16* out;
};

__device__ __align__(1024) uint32_t g_H[16 * 576 * 512];
__device__ __align__(1024) uint32_t g_O[NCTA * 9 * 512];
__device__ __align__(1024) uint32_t g_KV[32 * SEQ * 20];
__device__ __align__(1024) uint32_t g_Q[NCTA * 4 * 1152];
__device__ __align__(1024) uint4 g_P[NCTA * 3584];
__device__ __align__(1024) uint4 g_L[NCTA * 384];
__device__ float g_S[NCTA * 8 * SEQ];
__device__ uint32_t g_flags[16 * 32 + NCTA * 32 * 4];
#define FLAG_KV(l, j) (&g_flags[((l) * 8 + (j)) * 32])
#define FLAG_H(c) (&g_flags[16 * 32 + (c) * 32])
#define FLAG_O(c) (&g_flags[16 * 32 + NCTA * 32 + (c) * 32])
#define FLAG_P(c) (&g_flags[16 * 32 + NCTA * 64 + (c) * 32])
#define FLAG_EPOCH(c) (&g_flags[16 * 32 + NCTA * 96 + (c) * 32])
#define STAMP(i)
#define STAMPW(i)
#define TRACE()

template<uint32_t BHI> __device__ __forceinline__ void wg_rs_n192(float* d, uint32_t a0, uint32_t a1, uint32_t a2, uint32_t a3, uint32_t b) {
  asm volatile("{\n.reg .pred p;\n.reg .b64 db;\nsetp.ne.b32 p, 1, 0;\nmov.b64 db, {%100, %101};\n"
    "wgmma.mma_async.sync.aligned.m64n192k16.f32.bf16.bf16 {%0, %1, %2, %3, %4, %5, %6, %7, %8, %9, %10, %11, %12, %13, %14, %15, %16, %17, %18, %19, %20, %21, %22, %23, %24, %25, %26, %27, %28, %29, %30, %31, %32, %33, %34, %35, %36, %37, %38, %39, %40, %41, %42, %43, %44, %45, %46, %47, %48, %49, %50, %51, %52, %53, %54, %55, %56, %57, %58, %59, %60, %61, %62, %63, %64, %65, %66, %67, %68, %69, %70, %71, %72, %73, %74, %75, %76, %77, %78, %79, %80, %81, %82, %83, %84, %85, %86, %87, %88, %89, %90, %91, %92, %93, %94, %95}, {%96, %97, %98, %99}, db, p, 1, 1, 1;\n}\n"
    : "+f"(d[0]), "+f"(d[1]), "+f"(d[2]), "+f"(d[3]), "+f"(d[4]), "+f"(d[5]), "+f"(d[6]), "+f"(d[7]), "+f"(d[8]), "+f"(d[9]), "+f"(d[10]), "+f"(d[11]), "+f"(d[12]), "+f"(d[13]), "+f"(d[14]), "+f"(d[15]), "+f"(d[16]), "+f"(d[17]), "+f"(d[18]), "+f"(d[19]), "+f"(d[20]), "+f"(d[21]), "+f"(d[22]), "+f"(d[23]), "+f"(d[24]), "+f"(d[25]), "+f"(d[26]), "+f"(d[27]), "+f"(d[28]), "+f"(d[29]), "+f"(d[30]), "+f"(d[31]), "+f"(d[32]), "+f"(d[33]), "+f"(d[34]), "+f"(d[35]), "+f"(d[36]), "+f"(d[37]), "+f"(d[38]), "+f"(d[39]), "+f"(d[40]), "+f"(d[41]), "+f"(d[42]), "+f"(d[43]), "+f"(d[44]), "+f"(d[45]), "+f"(d[46]), "+f"(d[47]), "+f"(d[48]), "+f"(d[49]), "+f"(d[50]), "+f"(d[51]), "+f"(d[52]), "+f"(d[53]), "+f"(d[54]), "+f"(d[55]), "+f"(d[56]), "+f"(d[57]), "+f"(d[58]), "+f"(d[59]), "+f"(d[60]), "+f"(d[61]), "+f"(d[62]), "+f"(d[63]), "+f"(d[64]), "+f"(d[65]), "+f"(d[66]), "+f"(d[67]), "+f"(d[68]), "+f"(d[69]), "+f"(d[70]), "+f"(d[71]), "+f"(d[72]), "+f"(d[73]), "+f"(d[74]), "+f"(d[75]), "+f"(d[76]), "+f"(d[77]), "+f"(d[78]), "+f"(d[79]), "+f"(d[80]), "+f"(d[81]), "+f"(d[82]), "+f"(d[83]), "+f"(d[84]), "+f"(d[85]), "+f"(d[86]), "+f"(d[87]), "+f"(d[88]), "+f"(d[89]), "+f"(d[90]), "+f"(d[91]), "+f"(d[92]), "+f"(d[93]), "+f"(d[94]), "+f"(d[95])
    : "r"(a0), "r"(a1), "r"(a2), "r"(a3), "r"(b), "n"(BHI));
}
template<uint32_t BHI> __device__ __forceinline__ void wg_rs_z_n192(float* d, uint32_t a0, uint32_t a1, uint32_t a2, uint32_t a3, uint32_t b) {
  asm volatile("{\n.reg .pred p;\n.reg .b64 db;\nsetp.ne.b32 p, 0, 0;\nmov.b64 db, {%100, %101};\n"
    "wgmma.mma_async.sync.aligned.m64n192k16.f32.bf16.bf16 {%0, %1, %2, %3, %4, %5, %6, %7, %8, %9, %10, %11, %12, %13, %14, %15, %16, %17, %18, %19, %20, %21, %22, %23, %24, %25, %26, %27, %28, %29, %30, %31, %32, %33, %34, %35, %36, %37, %38, %39, %40, %41, %42, %43, %44, %45, %46, %47, %48, %49, %50, %51, %52, %53, %54, %55, %56, %57, %58, %59, %60, %61, %62, %63, %64, %65, %66, %67, %68, %69, %70, %71, %72, %73, %74, %75, %76, %77, %78, %79, %80, %81, %82, %83, %84, %85, %86, %87, %88, %89, %90, %91, %92, %93, %94, %95}, {%96, %97, %98, %99}, db, p, 1, 1, 1;\n}\n"
    : "=f"(d[0]), "=f"(d[1]), "=f"(d[2]), "=f"(d[3]), "=f"(d[4]), "=f"(d[5]), "=f"(d[6]), "=f"(d[7]), "=f"(d[8]), "=f"(d[9]), "=f"(d[10]), "=f"(d[11]), "=f"(d[12]), "=f"(d[13]), "=f"(d[14]), "=f"(d[15]), "=f"(d[16]), "=f"(d[17]), "=f"(d[18]), "=f"(d[19]), "=f"(d[20]), "=f"(d[21]), "=f"(d[22]), "=f"(d[23]), "=f"(d[24]), "=f"(d[25]), "=f"(d[26]), "=f"(d[27]), "=f"(d[28]), "=f"(d[29]), "=f"(d[30]), "=f"(d[31]), "=f"(d[32]), "=f"(d[33]), "=f"(d[34]), "=f"(d[35]), "=f"(d[36]), "=f"(d[37]), "=f"(d[38]), "=f"(d[39]), "=f"(d[40]), "=f"(d[41]), "=f"(d[42]), "=f"(d[43]), "=f"(d[44]), "=f"(d[45]), "=f"(d[46]), "=f"(d[47]), "=f"(d[48]), "=f"(d[49]), "=f"(d[50]), "=f"(d[51]), "=f"(d[52]), "=f"(d[53]), "=f"(d[54]), "=f"(d[55]), "=f"(d[56]), "=f"(d[57]), "=f"(d[58]), "=f"(d[59]), "=f"(d[60]), "=f"(d[61]), "=f"(d[62]), "=f"(d[63]), "=f"(d[64]), "=f"(d[65]), "=f"(d[66]), "=f"(d[67]), "=f"(d[68]), "=f"(d[69]), "=f"(d[70]), "=f"(d[71]), "=f"(d[72]), "=f"(d[73]), "=f"(d[74]), "=f"(d[75]), "=f"(d[76]), "=f"(d[77]), "=f"(d[78]), "=f"(d[79]), "=f"(d[80]), "=f"(d[81]), "=f"(d[82]), "=f"(d[83]), "=f"(d[84]), "=f"(d[85]), "=f"(d[86]), "=f"(d[87]), "=f"(d[88]), "=f"(d[89]), "=f"(d[90]), "=f"(d[91]), "=f"(d[92]), "=f"(d[93]), "=f"(d[94]), "=f"(d[95])
    : "r"(a0), "r"(a1), "r"(a2), "r"(a3), "r"(b), "n"(BHI));
}
template<uint32_t AHI, uint32_t BHI> __device__ __forceinline__ void wg_ss_n128(float* d, uint32_t a, uint32_t b) {
  asm volatile("{\n.reg .pred p;\n.reg .b64 da, db;\nsetp.ne.b32 p, 1, 0;\nmov.b64 da, {%64, %66};\nmov.b64 db, {%65, %67};\n"
    "wgmma.mma_async.sync.aligned.m64n128k16.f32.bf16.bf16 {%0, %1, %2, %3, %4, %5, %6, %7, %8, %9, %10, %11, %12, %13, %14, %15, %16, %17, %18, %19, %20, %21, %22, %23, %24, %25, %26, %27, %28, %29, %30, %31, %32, %33, %34, %35, %36, %37, %38, %39, %40, %41, %42, %43, %44, %45, %46, %47, %48, %49, %50, %51, %52, %53, %54, %55, %56, %57, %58, %59, %60, %61, %62, %63}, da, db, p, 1, 1, 0, 1;\n}\n"
    : "+f"(d[0]), "+f"(d[1]), "+f"(d[2]), "+f"(d[3]), "+f"(d[4]), "+f"(d[5]), "+f"(d[6]), "+f"(d[7]), "+f"(d[8]), "+f"(d[9]), "+f"(d[10]), "+f"(d[11]), "+f"(d[12]), "+f"(d[13]), "+f"(d[14]), "+f"(d[15]), "+f"(d[16]), "+f"(d[17]), "+f"(d[18]), "+f"(d[19]), "+f"(d[20]), "+f"(d[21]), "+f"(d[22]), "+f"(d[23]), "+f"(d[24]), "+f"(d[25]), "+f"(d[26]), "+f"(d[27]), "+f"(d[28]), "+f"(d[29]), "+f"(d[30]), "+f"(d[31]), "+f"(d[32]), "+f"(d[33]), "+f"(d[34]), "+f"(d[35]), "+f"(d[36]), "+f"(d[37]), "+f"(d[38]), "+f"(d[39]), "+f"(d[40]), "+f"(d[41]), "+f"(d[42]), "+f"(d[43]), "+f"(d[44]), "+f"(d[45]), "+f"(d[46]), "+f"(d[47]), "+f"(d[48]), "+f"(d[49]), "+f"(d[50]), "+f"(d[51]), "+f"(d[52]), "+f"(d[53]), "+f"(d[54]), "+f"(d[55]), "+f"(d[56]), "+f"(d[57]), "+f"(d[58]), "+f"(d[59]), "+f"(d[60]), "+f"(d[61]), "+f"(d[62]), "+f"(d[63])
    : "r"(a), "r"(b), "n"(AHI), "n"(BHI));
}
template<uint32_t AHI, uint32_t BHI> __device__ __forceinline__ void wg_ss_z_n128(float* d, uint32_t a, uint32_t b) {
  asm volatile("{\n.reg .pred p;\n.reg .b64 da, db;\nsetp.ne.b32 p, 0, 0;\nmov.b64 da, {%64, %66};\nmov.b64 db, {%65, %67};\n"
    "wgmma.mma_async.sync.aligned.m64n128k16.f32.bf16.bf16 {%0, %1, %2, %3, %4, %5, %6, %7, %8, %9, %10, %11, %12, %13, %14, %15, %16, %17, %18, %19, %20, %21, %22, %23, %24, %25, %26, %27, %28, %29, %30, %31, %32, %33, %34, %35, %36, %37, %38, %39, %40, %41, %42, %43, %44, %45, %46, %47, %48, %49, %50, %51, %52, %53, %54, %55, %56, %57, %58, %59, %60, %61, %62, %63}, da, db, p, 1, 1, 0, 1;\n}\n"
    : "=f"(d[0]), "=f"(d[1]), "=f"(d[2]), "=f"(d[3]), "=f"(d[4]), "=f"(d[5]), "=f"(d[6]), "=f"(d[7]), "=f"(d[8]), "=f"(d[9]), "=f"(d[10]), "=f"(d[11]), "=f"(d[12]), "=f"(d[13]), "=f"(d[14]), "=f"(d[15]), "=f"(d[16]), "=f"(d[17]), "=f"(d[18]), "=f"(d[19]), "=f"(d[20]), "=f"(d[21]), "=f"(d[22]), "=f"(d[23]), "=f"(d[24]), "=f"(d[25]), "=f"(d[26]), "=f"(d[27]), "=f"(d[28]), "=f"(d[29]), "=f"(d[30]), "=f"(d[31]), "=f"(d[32]), "=f"(d[33]), "=f"(d[34]), "=f"(d[35]), "=f"(d[36]), "=f"(d[37]), "=f"(d[38]), "=f"(d[39]), "=f"(d[40]), "=f"(d[41]), "=f"(d[42]), "=f"(d[43]), "=f"(d[44]), "=f"(d[45]), "=f"(d[46]), "=f"(d[47]), "=f"(d[48]), "=f"(d[49]), "=f"(d[50]), "=f"(d[51]), "=f"(d[52]), "=f"(d[53]), "=f"(d[54]), "=f"(d[55]), "=f"(d[56]), "=f"(d[57]), "=f"(d[58]), "=f"(d[59]), "=f"(d[60]), "=f"(d[61]), "=f"(d[62]), "=f"(d[63])
    : "r"(a), "r"(b), "n"(AHI), "n"(BHI));
}
template<uint32_t AHI, uint32_t BHI> __device__ __forceinline__ void wg_ss_n160(float* d, uint32_t a, uint32_t b) {
  asm volatile("{\n.reg .pred p;\n.reg .b64 da, db;\nsetp.ne.b32 p, 1, 0;\nmov.b64 da, {%80, %82};\nmov.b64 db, {%81, %83};\n"
    "wgmma.mma_async.sync.aligned.m64n160k16.f32.bf16.bf16 {%0, %1, %2, %3, %4, %5, %6, %7, %8, %9, %10, %11, %12, %13, %14, %15, %16, %17, %18, %19, %20, %21, %22, %23, %24, %25, %26, %27, %28, %29, %30, %31, %32, %33, %34, %35, %36, %37, %38, %39, %40, %41, %42, %43, %44, %45, %46, %47, %48, %49, %50, %51, %52, %53, %54, %55, %56, %57, %58, %59, %60, %61, %62, %63, %64, %65, %66, %67, %68, %69, %70, %71, %72, %73, %74, %75, %76, %77, %78, %79}, da, db, p, 1, 1, 0, 1;\n}\n"
    : "+f"(d[0]), "+f"(d[1]), "+f"(d[2]), "+f"(d[3]), "+f"(d[4]), "+f"(d[5]), "+f"(d[6]), "+f"(d[7]), "+f"(d[8]), "+f"(d[9]), "+f"(d[10]), "+f"(d[11]), "+f"(d[12]), "+f"(d[13]), "+f"(d[14]), "+f"(d[15]), "+f"(d[16]), "+f"(d[17]), "+f"(d[18]), "+f"(d[19]), "+f"(d[20]), "+f"(d[21]), "+f"(d[22]), "+f"(d[23]), "+f"(d[24]), "+f"(d[25]), "+f"(d[26]), "+f"(d[27]), "+f"(d[28]), "+f"(d[29]), "+f"(d[30]), "+f"(d[31]), "+f"(d[32]), "+f"(d[33]), "+f"(d[34]), "+f"(d[35]), "+f"(d[36]), "+f"(d[37]), "+f"(d[38]), "+f"(d[39]), "+f"(d[40]), "+f"(d[41]), "+f"(d[42]), "+f"(d[43]), "+f"(d[44]), "+f"(d[45]), "+f"(d[46]), "+f"(d[47]), "+f"(d[48]), "+f"(d[49]), "+f"(d[50]), "+f"(d[51]), "+f"(d[52]), "+f"(d[53]), "+f"(d[54]), "+f"(d[55]), "+f"(d[56]), "+f"(d[57]), "+f"(d[58]), "+f"(d[59]), "+f"(d[60]), "+f"(d[61]), "+f"(d[62]), "+f"(d[63]), "+f"(d[64]), "+f"(d[65]), "+f"(d[66]), "+f"(d[67]), "+f"(d[68]), "+f"(d[69]), "+f"(d[70]), "+f"(d[71]), "+f"(d[72]), "+f"(d[73]), "+f"(d[74]), "+f"(d[75]), "+f"(d[76]), "+f"(d[77]), "+f"(d[78]), "+f"(d[79])
    : "r"(a), "r"(b), "n"(AHI), "n"(BHI));
}
template<uint32_t AHI, uint32_t BHI> __device__ __forceinline__ void wg_ss_z_n160(float* d, uint32_t a, uint32_t b) {
  asm volatile("{\n.reg .pred p;\n.reg .b64 da, db;\nsetp.ne.b32 p, 0, 0;\nmov.b64 da, {%80, %82};\nmov.b64 db, {%81, %83};\n"
    "wgmma.mma_async.sync.aligned.m64n160k16.f32.bf16.bf16 {%0, %1, %2, %3, %4, %5, %6, %7, %8, %9, %10, %11, %12, %13, %14, %15, %16, %17, %18, %19, %20, %21, %22, %23, %24, %25, %26, %27, %28, %29, %30, %31, %32, %33, %34, %35, %36, %37, %38, %39, %40, %41, %42, %43, %44, %45, %46, %47, %48, %49, %50, %51, %52, %53, %54, %55, %56, %57, %58, %59, %60, %61, %62, %63, %64, %65, %66, %67, %68, %69, %70, %71, %72, %73, %74, %75, %76, %77, %78, %79}, da, db, p, 1, 1, 0, 1;\n}\n"
    : "=f"(d[0]), "=f"(d[1]), "=f"(d[2]), "=f"(d[3]), "=f"(d[4]), "=f"(d[5]), "=f"(d[6]), "=f"(d[7]), "=f"(d[8]), "=f"(d[9]), "=f"(d[10]), "=f"(d[11]), "=f"(d[12]), "=f"(d[13]), "=f"(d[14]), "=f"(d[15]), "=f"(d[16]), "=f"(d[17]), "=f"(d[18]), "=f"(d[19]), "=f"(d[20]), "=f"(d[21]), "=f"(d[22]), "=f"(d[23]), "=f"(d[24]), "=f"(d[25]), "=f"(d[26]), "=f"(d[27]), "=f"(d[28]), "=f"(d[29]), "=f"(d[30]), "=f"(d[31]), "=f"(d[32]), "=f"(d[33]), "=f"(d[34]), "=f"(d[35]), "=f"(d[36]), "=f"(d[37]), "=f"(d[38]), "=f"(d[39]), "=f"(d[40]), "=f"(d[41]), "=f"(d[42]), "=f"(d[43]), "=f"(d[44]), "=f"(d[45]), "=f"(d[46]), "=f"(d[47]), "=f"(d[48]), "=f"(d[49]), "=f"(d[50]), "=f"(d[51]), "=f"(d[52]), "=f"(d[53]), "=f"(d[54]), "=f"(d[55]), "=f"(d[56]), "=f"(d[57]), "=f"(d[58]), "=f"(d[59]), "=f"(d[60]), "=f"(d[61]), "=f"(d[62]), "=f"(d[63]), "=f"(d[64]), "=f"(d[65]), "=f"(d[66]), "=f"(d[67]), "=f"(d[68]), "=f"(d[69]), "=f"(d[70]), "=f"(d[71]), "=f"(d[72]), "=f"(d[73]), "=f"(d[74]), "=f"(d[75]), "=f"(d[76]), "=f"(d[77]), "=f"(d[78]), "=f"(d[79])
    : "r"(a), "r"(b), "n"(AHI), "n"(BHI));
}
template<uint32_t BHI> __device__ __forceinline__ void wg_rs_n32(float* d, uint32_t a0, uint32_t a1, uint32_t a2, uint32_t a3, uint32_t b) {
  asm volatile("{\n.reg .pred p;\n.reg .b64 db;\nsetp.ne.b32 p, 1, 0;\nmov.b64 db, {%20, %21};\n"
    "wgmma.mma_async.sync.aligned.m64n32k16.f32.bf16.bf16 {%0, %1, %2, %3, %4, %5, %6, %7, %8, %9, %10, %11, %12, %13, %14, %15}, {%16, %17, %18, %19}, db, p, 1, 1, 1;\n}\n"
    : "+f"(d[0]), "+f"(d[1]), "+f"(d[2]), "+f"(d[3]), "+f"(d[4]), "+f"(d[5]), "+f"(d[6]), "+f"(d[7]), "+f"(d[8]), "+f"(d[9]), "+f"(d[10]), "+f"(d[11]), "+f"(d[12]), "+f"(d[13]), "+f"(d[14]), "+f"(d[15])
    : "r"(a0), "r"(a1), "r"(a2), "r"(a3), "r"(b), "n"(BHI));
}
template<uint32_t BHI> __device__ __forceinline__ void wg_rs_z_n32(float* d, uint32_t a0, uint32_t a1, uint32_t a2, uint32_t a3, uint32_t b) {
  asm volatile("{\n.reg .pred p;\n.reg .b64 db;\nsetp.ne.b32 p, 0, 0;\nmov.b64 db, {%20, %21};\n"
    "wgmma.mma_async.sync.aligned.m64n32k16.f32.bf16.bf16 {%0, %1, %2, %3, %4, %5, %6, %7, %8, %9, %10, %11, %12, %13, %14, %15}, {%16, %17, %18, %19}, db, p, 1, 1, 1;\n}\n"
    : "=f"(d[0]), "=f"(d[1]), "=f"(d[2]), "=f"(d[3]), "=f"(d[4]), "=f"(d[5]), "=f"(d[6]), "=f"(d[7]), "=f"(d[8]), "=f"(d[9]), "=f"(d[10]), "=f"(d[11]), "=f"(d[12]), "=f"(d[13]), "=f"(d[14]), "=f"(d[15])
    : "r"(a0), "r"(a1), "r"(a2), "r"(a3), "r"(b), "n"(BHI));
}
template<uint32_t BHI> __device__ __forceinline__ void wg_rs_n64(float* d, uint32_t a0, uint32_t a1, uint32_t a2, uint32_t a3, uint32_t b) {
  asm volatile("{\n.reg .pred p;\n.reg .b64 db;\nsetp.ne.b32 p, 1, 0;\nmov.b64 db, {%36, %37};\n"
    "wgmma.mma_async.sync.aligned.m64n64k16.f32.bf16.bf16 {%0, %1, %2, %3, %4, %5, %6, %7, %8, %9, %10, %11, %12, %13, %14, %15, %16, %17, %18, %19, %20, %21, %22, %23, %24, %25, %26, %27, %28, %29, %30, %31}, {%32, %33, %34, %35}, db, p, 1, 1, 0;\n}\n"
    : "+f"(d[0]), "+f"(d[1]), "+f"(d[2]), "+f"(d[3]), "+f"(d[4]), "+f"(d[5]), "+f"(d[6]), "+f"(d[7]), "+f"(d[8]), "+f"(d[9]), "+f"(d[10]), "+f"(d[11]), "+f"(d[12]), "+f"(d[13]), "+f"(d[14]), "+f"(d[15]), "+f"(d[16]), "+f"(d[17]), "+f"(d[18]), "+f"(d[19]), "+f"(d[20]), "+f"(d[21]), "+f"(d[22]), "+f"(d[23]), "+f"(d[24]), "+f"(d[25]), "+f"(d[26]), "+f"(d[27]), "+f"(d[28]), "+f"(d[29]), "+f"(d[30]), "+f"(d[31])
    : "r"(a0), "r"(a1), "r"(a2), "r"(a3), "r"(b), "n"(BHI));
}
template<uint32_t BHI> __device__ __forceinline__ void wg_rs_z_n64(float* d, uint32_t a0, uint32_t a1, uint32_t a2, uint32_t a3, uint32_t b) {
  asm volatile("{\n.reg .pred p;\n.reg .b64 db;\nsetp.ne.b32 p, 0, 0;\nmov.b64 db, {%36, %37};\n"
    "wgmma.mma_async.sync.aligned.m64n64k16.f32.bf16.bf16 {%0, %1, %2, %3, %4, %5, %6, %7, %8, %9, %10, %11, %12, %13, %14, %15, %16, %17, %18, %19, %20, %21, %22, %23, %24, %25, %26, %27, %28, %29, %30, %31}, {%32, %33, %34, %35}, db, p, 1, 1, 0;\n}\n"
    : "=f"(d[0]), "=f"(d[1]), "=f"(d[2]), "=f"(d[3]), "=f"(d[4]), "=f"(d[5]), "=f"(d[6]), "=f"(d[7]), "=f"(d[8]), "=f"(d[9]), "=f"(d[10]), "=f"(d[11]), "=f"(d[12]), "=f"(d[13]), "=f"(d[14]), "=f"(d[15]), "=f"(d[16]), "=f"(d[17]), "=f"(d[18]), "=f"(d[19]), "=f"(d[20]), "=f"(d[21]), "=f"(d[22]), "=f"(d[23]), "=f"(d[24]), "=f"(d[25]), "=f"(d[26]), "=f"(d[27]), "=f"(d[28]), "=f"(d[29]), "=f"(d[30]), "=f"(d[31])
    : "r"(a0), "r"(a1), "r"(a2), "r"(a3), "r"(b), "n"(BHI));
}
template<uint32_t BHI> __device__ __forceinline__ void wg_rs_n24(float* d, uint32_t a0, uint32_t a1, uint32_t a2, uint32_t a3, uint32_t b) {
  asm volatile("{\n.reg .pred p;\n.reg .b64 db;\nsetp.ne.b32 p, 1, 0;\nmov.b64 db, {%16, %17};\n"
    "wgmma.mma_async.sync.aligned.m64n24k16.f32.bf16.bf16 {%0, %1, %2, %3, %4, %5, %6, %7, %8, %9, %10, %11}, {%12, %13, %14, %15}, db, p, 1, 1, 1;\n}\n"
    : "+f"(d[0]), "+f"(d[1]), "+f"(d[2]), "+f"(d[3]), "+f"(d[4]), "+f"(d[5]), "+f"(d[6]), "+f"(d[7]), "+f"(d[8]), "+f"(d[9]), "+f"(d[10]), "+f"(d[11])
    : "r"(a0), "r"(a1), "r"(a2), "r"(a3), "r"(b), "n"(BHI));
}
template<uint32_t BHI> __device__ __forceinline__ void wg_rs_z_n24(float* d, uint32_t a0, uint32_t a1, uint32_t a2, uint32_t a3, uint32_t b) {
  asm volatile("{\n.reg .pred p;\n.reg .b64 db;\nsetp.ne.b32 p, 0, 0;\nmov.b64 db, {%16, %17};\n"
    "wgmma.mma_async.sync.aligned.m64n24k16.f32.bf16.bf16 {%0, %1, %2, %3, %4, %5, %6, %7, %8, %9, %10, %11}, {%12, %13, %14, %15}, db, p, 1, 1, 1;\n}\n"
    : "=f"(d[0]), "=f"(d[1]), "=f"(d[2]), "=f"(d[3]), "=f"(d[4]), "=f"(d[5]), "=f"(d[6]), "=f"(d[7]), "=f"(d[8]), "=f"(d[9]), "=f"(d[10]), "=f"(d[11])
    : "r"(a0), "r"(a1), "r"(a2), "r"(a3), "r"(b), "n"(BHI));
}
template<uint32_t BHI> __device__ __forceinline__ void wg_rsb_n64(float* d, uint32_t a0, uint32_t a1, uint32_t a2, uint32_t a3, uint32_t b) {
  asm volatile("{\n.reg .pred p;\n.reg .b64 db;\nsetp.ne.b32 p, 1, 0;\nmov.b64 db, {%36, %37};\n"
    "wgmma.mma_async.sync.aligned.m64n64k16.f32.bf16.bf16 {%0, %1, %2, %3, %4, %5, %6, %7, %8, %9, %10, %11, %12, %13, %14, %15, %16, %17, %18, %19, %20, %21, %22, %23, %24, %25, %26, %27, %28, %29, %30, %31}, {%32, %33, %34, %35}, db, p, 1, 1, 1;\n}\n"
    : "+f"(d[0]), "+f"(d[1]), "+f"(d[2]), "+f"(d[3]), "+f"(d[4]), "+f"(d[5]), "+f"(d[6]), "+f"(d[7]), "+f"(d[8]), "+f"(d[9]), "+f"(d[10]), "+f"(d[11]), "+f"(d[12]), "+f"(d[13]), "+f"(d[14]), "+f"(d[15]), "+f"(d[16]), "+f"(d[17]), "+f"(d[18]), "+f"(d[19]), "+f"(d[20]), "+f"(d[21]), "+f"(d[22]), "+f"(d[23]), "+f"(d[24]), "+f"(d[25]), "+f"(d[26]), "+f"(d[27]), "+f"(d[28]), "+f"(d[29]), "+f"(d[30]), "+f"(d[31])
    : "r"(a0), "r"(a1), "r"(a2), "r"(a3), "r"(b), "n"(BHI));
}
template<uint32_t BHI> __device__ __forceinline__ void wg_rsb_z_n64(float* d, uint32_t a0, uint32_t a1, uint32_t a2, uint32_t a3, uint32_t b) {
  asm volatile("{\n.reg .pred p;\n.reg .b64 db;\nsetp.ne.b32 p, 0, 0;\nmov.b64 db, {%36, %37};\n"
    "wgmma.mma_async.sync.aligned.m64n64k16.f32.bf16.bf16 {%0, %1, %2, %3, %4, %5, %6, %7, %8, %9, %10, %11, %12, %13, %14, %15, %16, %17, %18, %19, %20, %21, %22, %23, %24, %25, %26, %27, %28, %29, %30, %31}, {%32, %33, %34, %35}, db, p, 1, 1, 1;\n}\n"
    : "=f"(d[0]), "=f"(d[1]), "=f"(d[2]), "=f"(d[3]), "=f"(d[4]), "=f"(d[5]), "=f"(d[6]), "=f"(d[7]), "=f"(d[8]), "=f"(d[9]), "=f"(d[10]), "=f"(d[11]), "=f"(d[12]), "=f"(d[13]), "=f"(d[14]), "=f"(d[15]), "=f"(d[16]), "=f"(d[17]), "=f"(d[18]), "=f"(d[19]), "=f"(d[20]), "=f"(d[21]), "=f"(d[22]), "=f"(d[23]), "=f"(d[24]), "=f"(d[25]), "=f"(d[26]), "=f"(d[27]), "=f"(d[28]), "=f"(d[29]), "=f"(d[30]), "=f"(d[31])
    : "r"(a0), "r"(a1), "r"(a2), "r"(a3), "r"(b), "n"(BHI));
}

__device__ __forceinline__ void wg_fence() { asm volatile("wgmma.fence.sync.aligned;" ::: "memory"); }
__device__ __forceinline__ void wg_commit() { asm volatile("wgmma.commit_group.sync.aligned;" ::: "memory"); }
template <int N> __device__ __forceinline__ void wg_wait() { asm volatile("wgmma.wait_group.sync.aligned %0;" ::"n"(N) : "memory"); }
template <int R> __device__ __forceinline__ void pin(float* d) {
#pragma unroll
  for (int i = 0; i < R; i++) asm volatile("" : "+f"(d[i])::"memory");
}
template <int R> __device__ __forceinline__ void pin(uint32_t* d) {
#pragma unroll
  for (int i = 0; i < R; i++) asm volatile("" : "+r"(d[i])::"memory");
}
__device__ __forceinline__ float ex2(float x) { float y; asm("ex2.approx.ftz.f32 %0, %1;" : "=f"(y) : "f"(x)); return y; }
__device__ __forceinline__ float tanh_fast(float x) { float y; asm("tanh.approx.f32 %0, %1;" : "=f"(y) : "f"(x)); return y; }
__device__ __forceinline__ uint32_t pack(float lo, float hi) { uint32_t r; asm("cvt.rn.bf16x2.f32 %0, %1, %2;" : "=r"(r) : "f"(hi), "f"(lo)); return r; }
__device__ __forceinline__ float bf_lo(uint32_t v) { return __uint_as_float(v << 16); }
__device__ __forceinline__ float bf_hi(uint32_t v) { return __uint_as_float(v & 0xffff0000u); }
__device__ __forceinline__ float bf_round(float x) { return bf_lo(pack(x, 0.f)); }

__device__ __forceinline__ void mbar_init(uint32_t bar, uint32_t cnt) { asm volatile("mbarrier.init.shared::cta.b64 [%0], %1;" ::"r"(bar), "r"(cnt) : "memory"); }
__device__ __forceinline__ void mbar_expect(uint32_t bar, uint32_t bytes) { asm volatile("mbarrier.arrive.expect_tx.shared::cta.b64 _, [%0], %1;" ::"r"(bar), "r"(bytes) : "memory"); }
__device__ __forceinline__ void mbar_wait(uint32_t bar, uint32_t parity) {
  asm volatile(
      "{\n.reg .pred p;\n.reg .u32 c;\n"
      "mbarrier.try_wait.parity.shared::cta.b64 p, [%0], %1;\n"
      "@p bra.uni DONE;\n"
      "mov.u32 c, 0;\n"
      "LOOP:\n"
      "mbarrier.try_wait.parity.shared::cta.b64 p, [%0], %1;\n"
      "@p bra.uni DONE;\n"
      "add.u32 c, c, 1;\n"
      "setp.lt.u32 p, c, 0x400000;\n"
      "@p bra.uni LOOP;\n"
      "trap;\n"
      "DONE:\n}\n" ::"r"(bar), "r"(parity) : "memory");
}
__device__ __forceinline__ uint32_t mbar_test(uint32_t bar, uint32_t parity) {
  uint32_t ok;
  asm volatile("{\n.reg .pred p;\nmbarrier.test_wait.parity.shared::cta.b64 p, [%1], %2;\nselp.u32 %0, 1, 0, p;\n}\n" : "=r"(ok) : "r"(bar), "r"(parity) : "memory");
  return ok;
}
__device__ __forceinline__ void mbar_arrive_if(uint32_t bar, uint32_t cond) {
  asm volatile("{\n.reg .pred p;\nsetp.ne.u32 p, %1, 0;\n@p mbarrier.arrive.shared::cta.b64 _, [%0];\n}\n" ::"r"(bar), "r"(cond) : "memory");
}
__device__ __forceinline__ uint32_t bsub2(uint32_t a, uint32_t b) { uint32_t d; asm("sub.rn.bf16x2 %0, %1, %2;" : "=r"(d) : "r"(a), "r"(b)); return d; }
__device__ __forceinline__ uint32_t bscale2(uint32_t d, uint32_t hi, uint32_t lo) {
  uint32_t t, r;
  asm("mul.rn.bf16x2 %0, %1, %2;" : "=r"(t) : "r"(d), "r"(lo));
  asm("fma.rn.bf16x2 %0, %1, %2, %3;" : "=r"(r) : "r"(d), "r"(hi), "r"(t));
  return r;
}
__device__ __forceinline__ void flag_wait(const uint32_t* f, uint32_t target) {
  asm volatile(
      "{\n.reg .pred p;\n.reg .u32 c, v;\n"
      "mov.u32 c, 0;\n"
      "LOOP:\n"
      "ld.acquire.gpu.global.u32 v, [%0];\n"
      "sub.u32 v, v, %1;\n"
      "setp.ge.s32 p, v, 0;\n"
      "@p bra DONE;\n"
      "add.u32 c, c, 1;\n"
      "setp.lt.u32 p, c, 0x400000;\n"
      "@p bra LOOP;\n"
      "trap;\n"
      "DONE:\n}\n" ::"l"(f), "r"(target) : "memory");
}
__device__ __forceinline__ uint32_t flag_wait_v(const uint32_t* f, uint32_t target) {
  uint32_t v;
  asm volatile(
      "{\n.reg .pred p;\n.reg .u32 c, d;\n"
      "mov.u32 c, 0;\n"
      "LOOP:\n"
      "ld.acquire.gpu.global.u32 %0, [%1];\n"
      "sub.u32 d, %0, %2;\n"
      "setp.ge.s32 p, d, 0;\n"
      "@p bra DONE;\n"
      "add.u32 c, c, 1;\n"
      "setp.lt.u32 p, c, 0x400000;\n"
      "@p bra LOOP;\n"
      "trap;\n"
      "DONE:\n}\n" : "=&r"(v) : "l"(f), "r"(target) : "memory");
  return v;
}
__device__ __forceinline__ float sqrt_fast(float x) { float y; asm("sqrt.approx.f32 %0, %1;" : "=f"(y) : "f"(x)); return y; }
__device__ __forceinline__ float rcp_fast(float x) { float y; asm("rcp.approx.ftz.f32 %0, %1;" : "=f"(y) : "f"(x)); return y; }
__device__ __forceinline__ void ldsm4(uint32_t* v, uint32_t addr) {
  asm volatile("ldmatrix.sync.aligned.m8n8.x4.shared.b16 {%0,%1,%2,%3}, [%4];" : "=r"(v[0]), "=r"(v[1]), "=r"(v[2]), "=r"(v[3]) : "r"(addr) : "memory");
}
__device__ __forceinline__ void stsm4(uint32_t addr, uint32_t a, uint32_t b, uint32_t c, uint32_t d) {
  asm volatile("stmatrix.sync.aligned.m8n8.x4.shared.b16 [%0], {%1,%2,%3,%4};" ::"r"(addr), "r"(a), "r"(b), "r"(c), "r"(d) : "memory");
}
__device__ __forceinline__ void flag_add(uint32_t* f) { asm volatile("red.relaxed.gpu.global.add.u32 [%0], 1;" ::"l"(f) : "memory"); }
__device__ __forceinline__ void fence_gpu() { asm volatile("fence.acq_rel.gpu;" ::: "memory"); }
__device__ __forceinline__ void fence_async() { asm volatile("fence.proxy.async.global;" ::: "memory"); }
__device__ __forceinline__ void tma2d(uint32_t dst, const CUtensorMap* tm, uint32_t bar, int c0, int c1) {
  asm volatile("cp.async.bulk.tensor.2d.shared::cluster.global.mbarrier::complete_tx::bytes [%0], [%1, {%3, %4}], [%2];" ::"r"(dst), "l"(tm), "r"(bar), "r"(c0), "r"(c1) : "memory");
}
__device__ __forceinline__ void tma2d_h(uint32_t dst, const CUtensorMap* tm, uint32_t bar, int c0, int c1, uint64_t pol) {
  asm volatile("cp.async.bulk.tensor.2d.shared::cluster.global.mbarrier::complete_tx::bytes.L2::cache_hint [%0], [%1, {%3, %4}], [%2], %5;" ::"r"(dst), "l"(tm), "r"(bar), "r"(c0), "r"(c1), "l"(pol) : "memory");
}
__device__ __forceinline__ void bulk_s2g(void* dst, uint32_t src, uint32_t bytes) {
  asm volatile("cp.async.bulk.global.shared::cta.bulk_group [%0], [%1], %2;" ::"l"(dst), "r"(src), "r"(bytes) : "memory");
}
__device__ __forceinline__ void mma_ones(float* c, const uint32_t* a) {
  asm("mma.sync.aligned.m16n8k16.row.col.f32.bf16.bf16.f32 {%0,%1,%2,%3}, {%4,%5,%6,%7}, {%8,%8}, {%0,%1,%2,%3};"
      : "+f"(c[0]), "+f"(c[1]), "+f"(c[2]), "+f"(c[3]) : "r"(a[0]), "r"(a[1]), "r"(a[2]), "r"(a[3]), "r"(0x3f803f80u));
}
__device__ __forceinline__ void tma5d(uint32_t dst, const CUtensorMap* tm, uint32_t bar, int c0, int c4) {
  asm volatile("cp.async.bulk.tensor.5d.shared::cluster.global.mbarrier::complete_tx::bytes [%0], [%1, {%3, %5, %5, %5, %4}], [%2];" ::"r"(dst), "l"(tm), "r"(bar), "r"(c0), "r"(c4), "r"(0) : "memory");
}
__device__ __forceinline__ void tma3d(uint32_t dst, const CUtensorMap* tm, uint32_t bar, int c0, int c2) {
  asm volatile("cp.async.bulk.tensor.3d.shared::cluster.global.mbarrier::complete_tx::bytes [%0], [%1, {%3, %5, %4}], [%2];" ::"r"(dst), "l"(tm), "r"(bar), "r"(c0), "r"(c2), "r"(0) : "memory");
}
__device__ __forceinline__ void bulk_g2s(uint32_t dst, const void* src, uint32_t bytes, uint32_t bar) {
  asm volatile("cp.async.bulk.shared::cluster.global.mbarrier::complete_tx::bytes [%0], [%1], %2, [%3];" ::"r"(dst), "l"(src), "r"(bytes), "r"(bar) : "memory");
}
__device__ __forceinline__ void pf_line(const void* p) { asm volatile("prefetch.global.L2 [%0];" ::"l"(p) : "memory"); }
__device__ __forceinline__ int fresh_tid() { int v; asm volatile("mov.u32 %0, %%tid.x;" : "=r"(v)); return v; }
struct Att {
  float s[32];
  float o[12];
  uint32_t p[16];
  uint32_t q[8];
};

__device__ __forceinline__ float warp_sum(float v) {
#pragma unroll 1
  for (int d = 16; d; d >>= 1) v += __shfl_xor_sync(0xffffffffu, v, d);
  return v;
}
#define OPAQUE(x) asm volatile("" : "+r"(x))
__device__ __forceinline__ void attn_slow_row(int cta, uint32_t& w) {
  float mx = -INFINITY;
#pragma unroll 1
  for (uint32_t key = threadIdx.x & 31; key < SEQ; key += 32) {
    float s = 0.f;
#pragma unroll 1
    for (uint32_t v = 0; v < 9; v++) {
      OPAQUE(w); OPAQUE(key);
      const uint32_t hp = (w >> 4) & 3, pos = (v + hp) & 3;
      const uint32_t q = g_Q[(cta * 4 + hp) * 1152 + ((w >> 3) & 1) + (v < 8 ? (((w >> 6) & 7) * 32 + (w & 7) * 4 + pos) * 4 + 2 * (v >> 2) : 1024 + (((w >> 6) & 7) * 8 + (w & 7)) * 2)];
      const uint32_t u = g_KV[(4 * (cta & 7) + hp) * SEQ * 20 + (key >> 3) * 160 + (key & 7) * 4 + (v >> 2) * 32 + pos];
      s = fmaf(bf_lo(q), bf_lo(u), fmaf(bf_hi(q), bf_hi(u), s));
    }
    g_S[(cta * 8 + ((w >> 6) & 7)) * SEQ + key] = s;
    mx = fmaxf(mx, s);
  }
#pragma unroll 1
  for (int d = 16; d; d >>= 1) mx = fmaxf(mx, __shfl_xor_sync(0xffffffffu, mx, d));
  float l = 0.f;
#pragma unroll 1
  for (uint32_t key = threadIdx.x & 31; key < SEQ; key += 32) l += ex2(g_S[(cta * 8 + ((w >> 6) & 7)) * SEQ + key] - mx);
  l = 2.f * rcp_fast(warp_sum(l));
#pragma unroll 1
  for (uint32_t v = w >> 9; v < 9; v++) {
    float a = 0.f, b = 0.f;
#pragma unroll 1
    for (uint32_t key = threadIdx.x & 31; key < SEQ; key += 32) {
      OPAQUE(w); OPAQUE(v);
      const uint32_t hp = (w >> 4) & 3;
      const uint32_t u = g_KV[(4 * (cta & 7) + hp) * SEQ * 20 + (key >> 3) * 160 + (key & 7) * 4 + (v < 8 ? (3 + (v >> 2)) * 32 + (v & 3) : 64 + ((hp + 2) & 3))];
      const float p = ex2(g_S[(cta * 8 + ((w >> 6) & 7)) * SEQ + key] - mx);
      a = fmaf(p, bf_lo(u), a); b = fmaf(p, bf_hi(u), b);
    }
    a = warp_sum(a); b = warp_sum(b);
    OPAQUE(w);
    const uint32_t hp = (w >> 4) & 3;
    if ((threadIdx.x & 31) == 0) g_O[cta * 9 * 512 + (((w >> 6) & 7) * 16 + (w & 15)) * 4 + (v < 8 ? (2 * hp + (v >> 2)) * 512 + (v & 3) : 8 * 512 + hp)] = pack(a * l, b * l);
  }
}

__device__ __forceinline__ uint32_t bad_heads(uint32_t bad_addr, int wr) {
  uint32_t bad;
  __syncwarp();
  asm volatile("ld.volatile.shared.u32 %0, [%1];" : "=r"(bad) : "r"(bad_addr) : "memory");
  return __shfl_sync(0xffffffffu, (bad >> (4 * wr)) & 15, 0);
}
__device__ __forceinline__ void repair_rows(int cta, int wr, uint32_t bad, int last_head, bool final) {
#pragma unroll 1
  for (uint32_t w = wr * 64; w < wr * 64 + 64; w++) {
    if (!((bad >> ((w >> 4) & 3)) & 1)) continue;
    if (final && ((w >> 4) & 3) != last_head) w |= 8u << 9;
    attn_slow_row(cta, w);
    w &= 511;
  }
  __syncwarp();
}
__device__ __forceinline__ void o_normalise(const float* o, uint32_t* w, uint32_t& x0, uint32_t& x1, int hp, int lane, uint32_t bad_addr, int wr) {
  const int src = (lane & ~3) | ((hp + 1) & 3);
  float l0 = __shfl_sync(0xffffffffu, o[0], src), l1 = __shfl_sync(0xffffffffu, o[2], src);
  float sa = 0.f;
#pragma unroll
  for (int i = 0; i < 12; i++) sa += fabsf(o[i]);
  bool ok = (l0 <= 1.329228e36f) && (l1 <= 1.329228e36f) && (l0 > 0.f) && (l1 > 0.f) && (sa <= 3.0e38f);
  float i0 = 2.f * rcp_fast(l0), i1 = 2.f * rcp_fast(l1);
  w[0] = pack(o[4] * i0, o[5] * i0);
  w[1] = pack(o[6] * i1, o[7] * i1);
  w[2] = pack(o[8] * i0, o[9] * i0);
  w[3] = pack(o[10] * i1, o[11] * i1);
  if ((lane & 3) == ((hp + 2) & 3)) { x0 = pack(o[0] * i0, o[1] * i0); x1 = pack(o[2] * i1, o[3] * i1); }
  if (!ok) asm volatile("red.shared.or.b32 [%0], %1;" ::"r"(bad_addr), "r"(1u << (4 * wr + hp)) : "memory");
}

__device__ __forceinline__ void issue_pv(Att& a, uint32_t kdesc) {
  const uint32_t vdesc = kdesc + 192 + (LO_V - LO_K);
#pragma unroll
  for (int k = 0; k < 4; k++) wg_rs_n24<HI_V>(a.o, a.p[4 * k], a.p[4 * k + 1], a.p[4 * k + 2], a.p[4 * k + 3], vdesc + k * 48);
}
__device__ __forceinline__ void issue_att(Att& a, uint32_t kdesc) {
  issue_pv(a, kdesc);
  wg_rs_z_n64<HI_K>(a.s, a.q[0], a.q[1], a.q[2], a.q[3], kdesc);
  wg_rs_n64<HI_K>(a.s, a.q[4], a.q[5], a.q[6], a.q[7], kdesc + 16);
}
__device__ __forceinline__ void softmax_a(Att& a) {
#pragma unroll
  for (int i = 0; i < SM_B; i++) a.p[i] = pack(ex2(a.s[2 * i]), ex2(a.s[2 * i + 1]));
  a.s[2 * SM_B] = ex2(a.s[2 * SM_B]); a.s[2 * SM_B + 1] = ex2(a.s[2 * SM_B + 1]);
  pin<SM_B>(a.p); pin<2>(a.s + 2 * SM_B);
}
__device__ __forceinline__ void softmax_b(Att& a) {
  a.p[SM_B] = pack(a.s[2 * SM_B], a.s[2 * SM_B + 1]);
#pragma unroll
  for (int i = SM_B + 1; i < 16; i++) a.p[i] = pack(ex2(a.s[2 * i]), ex2(a.s[2 * i + 1]));
  pin<16 - SM_B>(a.p + SM_B);
}
__device__ __forceinline__ void first_tile(Att& a, int hp, int lane) {
  float m0 = fmaxf(a.s[0], a.s[1]), m1 = fmaxf(a.s[2], a.s[3]);
#pragma unroll
  for (int i = 4; i < 32; i += 4) { m0 = fmaxf(m0, fmaxf(a.s[i], a.s[i + 1])); m1 = fmaxf(m1, fmaxf(a.s[i + 2], a.s[i + 3])); }
  m0 = fmaxf(m0, __shfl_xor_sync(0xffffffffu, m0, 1)); m1 = fmaxf(m1, __shfl_xor_sync(0xffffffffu, m1, 1));
  m0 = fmaxf(m0, __shfl_xor_sync(0xffffffffu, m0, 2)); m1 = fmaxf(m1, __shfl_xor_sync(0xffffffffu, m1, 2));
  float n0 = -(m0 + MOFF), n1 = -(m1 + MOFF);
  float h0 = bf_round(n0), h1 = bf_round(n1);
  uint32_t e0 = pack(h0, n0 - h0), e1 = pack(h1, n1 - h1);
  n0 = h0 + bf_hi(e0); n1 = h1 + bf_hi(e1);
  if ((lane & 3) == ((hp + 1) & 3)) { a.q[4] = e0; a.q[5] = e1; }
#pragma unroll
  for (int i = 0; i < 32; i += 4) { a.s[i] += n0; a.s[i + 1] += n0; a.s[i + 2] += n1; a.s[i + 3] += n1; }
#pragma unroll
  for (int i = 0; i < 12; i++) a.o[i] = 0.f;
  pin<12>(a.o); pin<8>(a.q);
}
__device__ __forceinline__ void fetch_q(uint32_t* q, int cta, int hp, int tid) {
  const uint32_t* src = g_Q + (cta * 4 + hp) * 1152;
  const uint4 u = __ldcg(reinterpret_cast<const uint4*>(src) + tid);
  uint2 v = make_uint2(0u, 0u);
  if ((tid & 3) == hp) v = __ldcg(reinterpret_cast<const uint2*>(src + 1024) + (tid >> 2));
  q[0] = u.x; q[1] = u.y; q[2] = u.z; q[3] = u.w; q[4] = v.x; q[5] = v.y;
}
__device__ __forceinline__ void store_q(const uint32_t* q, int cta, int hp, int tid) {
  uint32_t* dst = g_Q + (cta * 4 + hp) * 1152;
  reinterpret_cast<uint4*>(dst)[tid] = make_uint4(q[0], q[1], q[2], q[3]);
  if ((tid & 3) == hp) reinterpret_cast<uint2*>(dst + 1024)[tid >> 2] = make_uint2(q[4], q[5]);
}
__device__ __forceinline__ void h_epilogue(const float* acc, uint32_t* dst) {
#pragma unroll
  for (int b = 0; b < 4; b++) {
    uint32_t w[2][2];
#pragma unroll
    for (int i = 0; i < 2; i++) {
      float h[4];
#pragma unroll
      for (int e = 0; e < 4; e++) {
        const float g = acc[(2 * b + i) * 4 + e], u = acc[32 + (2 * b + i) * 4 + e];
        h[e] = fmaf(tanh_fast(0.5f * g), u, u);
      }
      w[0][i] = pack(h[0], h[1]); w[1][i] = pack(h[2], h[3]);
    }
    *reinterpret_cast<uint2*>(dst + 1024 * b) = make_uint2(w[0][0], w[0][1]);
    *reinterpret_cast<uint2*>(dst + 1024 * b + 32) = make_uint2(w[1][0], w[1][1]);
  }
}
__device__ __forceinline__ void rotate9(uint32_t (&v)[9][2]) {
#pragma unroll
  for (int rh = 0; rh < 2; rh++) {
    const uint32_t r = v[8][rh];
#pragma unroll
    for (int i = 8; i > 0; i--) v[i][rh] = v[i - 1][rh];
    v[0][rh] = r;
  }
}
template <int HP> __device__ __forceinline__ void store_kv_head(uint32_t (&pk)[2][9][2], uint32_t* kvp, int lane, uint32_t sk = 0, uint32_t sv = 0) {
  const int t = lane & 3, dv = ((t - HP) & 3) - t;
  const bool up = t < HP;
#pragma unroll
  for (int rh = 0; rh < 2; rh++) {
    uint32_t* d = kvp + HP * SEQ * 20 + rh * 160;
    const uint32_t c0 = up ? pk[0][2 * HP + 1][rh] : pk[0][2 * HP][rh], c1 = up ? pk[0][2 * HP + 2][rh] : pk[0][2 * HP + 1][rh];
    const uint32_t c3 = up ? pk[1][2 * HP + 1][rh] : pk[1][2 * HP][rh], c4 = up ? pk[1][2 * HP + 2][rh] : pk[1][2 * HP + 1][rh];
    const uint32_t v9 = __shfl_sync(0xffffffffu, pk[1][2 * HP + 2][rh], (lane & ~3) | HP);
    const uint32_t c2 = t == HP ? pk[0][2 * HP + 2][rh] : t == ((HP + 1) & 3) ? 0x3f803f80u : t == ((HP + 2) & 3) ? v9 : 0u;
    d[0] = c0; d[32] = c1; d[64] = c2; d[96 + dv] = c3; d[128 + dv] = c4;
    if (sk) {
      asm volatile("st.shared.b32 [%0], %1;\nst.shared.b32 [%0 + 128], %2;\nst.shared.b32 [%0 + 256], %3;" ::"r"(sk + rh * 384), "r"(c0), "r"(c1), "r"(c2) : "memory");
      asm volatile("st.shared.b32 [%0], %1;\nst.shared.b32 [%2 + 128], %3;\nst.shared.b32 [%2 + 256], %4;" ::"r"(sv + rh * 384), "r"(c2), "r"(sv + rh * 384 + dv * 4), "r"(c3), "r"(c4) : "memory");
    }
  }
}

template <int OFF> __device__ __forceinline__ void ld4(uint32_t* v, const void* p) {
  asm volatile("ld.relaxed.gpu.global.v4.b32 {%0,%1,%2,%3}, [%4 + %5];" : "=r"(v[0]), "=r"(v[1]), "=r"(v[2]), "=r"(v[3]) : "l"(p), "n"(OFF) : "memory");
}
template <int OFF> __device__ __forceinline__ void ld2(uint32_t* v, const void* p) {
  asm volatile("ld.relaxed.gpu.global.v2.b32 {%0,%1}, [%2 + %3];" : "=r"(v[0]), "=r"(v[1]) : "l"(p), "n"(OFF) : "memory");
}
__device__ __forceinline__ void stage_partials(const float* acc, uint32_t dst, int tid) {
  const int lane = tid & 31, row = (tid >> 5) * 16 + (lane & 15);
  const uint32_t r128 = dst + row * 128, r64 = dst + 49152 + row * 64;
#pragma unroll
  for (int i = 0; i < 12; i++) {
    const float* v = acc + 8 * i;
    stsm4(r128 + (i >> 2) * 16384 + (((2 * (i & 3) + (lane >> 4)) ^ (row & 7)) << 4), pack(v[0], v[1]), pack(v[2], v[3]), pack(v[4], v[5]), pack(v[6], v[7]));
  }
#pragma unroll
  for (int i = 0; i < 2; i++) {
    const float* v = acc + 128 + 8 * i;
    stsm4(r64 + (((2 * i + (lane >> 4)) ^ ((row >> 1) & 3)) << 4), pack(v[0], v[1]), pack(v[2], v[3]), pack(v[4], v[5]), pack(v[6], v[7]));
  }
}
__device__ __forceinline__ void final_epilogue(const float* acc, const Params& prm, int m, int hh, int q, int tid) {
  uint32_t r[18];
#pragma unroll
  for (int i = 0; i < 16; i++) r[i] = pack(acc[2 * i] * 0.5f, acc[2 * i + 1] * 0.5f);
#pragma unroll
  for (int i = 0; i < 2; i++) {
    const int o = 32 + 4 * i;
    const float a0 = (q & 2) ? acc[o + 2] : acc[o], a1 = (q & 2) ? acc[o + 10] : acc[o + 8];
    const float b0 = (q & 2) ? acc[o + 3] : acc[o + 1], b1 = (q & 2) ? acc[o + 11] : acc[o + 9];
    r[16 + i] = pack(((q & 1) ? a1 : a0) * 0.5f, ((q & 1) ? b1 : b0) * 0.5f);
  }
  const size_t off = (size_t)(128 * m + (tid >> 5) * 16 + ((tid & 31) >> 2)) * DM + 2 * (tid & 3);
  const bool odd = tid & 1;
  uint32_t* o1 = reinterpret_cast<uint32_t*>(prm.out + off + 320 * hh + 64 * q) + (odd ? 3 : 0);
  uint32_t* o2 = reinterpret_cast<uint32_t*>(prm.out + off + 256 + 32 * hh + 16 * (q & 1) + (q >> 1) * 8 * DM) + (odd ? 3 : 0);
#pragma unroll
  for (int i = 0; i < 9; i++) {
    const uint32_t A = i < 8 ? r[4 * (i >> 1) + (i & 1)] : r[16], B = i < 8 ? r[4 * (i >> 1) + 2 + (i & 1)] : r[17];
    const uint32_t y = __shfl_xor_sync(0xffffffffu, odd ? A : B, 1);
    *reinterpret_cast<uint2*>(i < 8 ? o1 + 8 * (i >> 1) + (i & 1) * 8 * (DM / 2) : o2) = odd ? make_uint2(y, B) : make_uint2(A, y);
  }
}

__global__ void __launch_bounds__(384, 1) fused_kernel(const __grid_constant__ Params prm) {
  extern __shared__ __align__(1024) uint8_t smem[];
  constexpr uint32_t sb = 1024;
  const uint32_t bar = sb + SM_BAR;
  const int m = blockIdx.x & 15, j = blockIdx.x >> 4;
  const int cta = m * 8 + j;
  const int wr = __shfl_sync(0xffffffffu, (int)(threadIdx.x >> 5), 0);
  const int wg = wr >> 2;
  const int lane = threadIdx.x & 31;
  STAMP(0);
  if (wg == 2 && lane == 0) {
    if (wr == 8) {
      asm volatile("prefetch.tensormap [%0];" ::"l"(&prm.xm) : "memory");
#pragma unroll
      for (int c = 0; c < 9; c++) mbar_init(bar + 8 * (B_X + c), 1);
#pragma unroll
      for (int c = 0; c < 9; c++) mbar_expect(bar + 8 * (B_X + c), 16384);
      asm volatile("fence.proxy.async.shared::cta;" ::: "memory");
#pragma unroll
      for (int c = 0; c < 3; c++) tma2d(sb + SM_XN + c * 16384, &prm.xm, bar + 8 * (B_X + c), 64 * c, 128 * m);
    } else {
      if (wr == 9) {
#pragma unroll
        for (int i = 0; i < 8; i++) mbar_init(bar + 8 * (B_F + i), 2);
#pragma unroll
        for (int i = 0; i < 3; i++) mbar_init(bar + 8 * (B_QF + i), 1);
      } else if (wr == 10) {
#pragma unroll
        for (int i = 0; i < 8; i++) mbar_init(bar + 8 * (B_E + i), 8);
#pragma unroll
        for (int i = 0; i < 3; i++) mbar_init(bar + 8 * (B_QE + i), 8);
      } else {
#pragma unroll
        for (int i = B_SK1; i <= B_SP; i++) mbar_init(bar + 8 * i, 8);
        mbar_init(bar + 8 * B_OL, 1); mbar_init(bar + 8 * B_RX, 1);
        mbar_init(bar + 8 * B_NR, 4); mbar_init(bar + 8 * (B_NR + 1), 4);
        asm volatile("st.shared.u32 [%0], 0;" ::"r"(sb + SM_BAD) : "memory");
        if ((uint32_t)__cvta_generic_to_shared(smem) != sb || (sb & 1023)) asm volatile("trap;");
      }
      asm volatile("fence.proxy.async.shared::cta;" ::: "memory");
    }
  }
  if (wr == 0) {
    const uint32_t one = (lane >> 3) == (lane & 3) ? ((lane & 4) ? 0x3f800000u : 0x00003f80u) : 0u;
    asm volatile("st.shared.v4.b32 [%0], {%1,%2,%2,%1};" ::"r"(sb + SM_ID + lane * 16), "r"(one), "r"(0) : "memory");
  }
  __syncthreads();

  if (wg == 2) {
    asm volatile("setmaxnreg.dec.sync.aligned.u32 24;");
    const int pw = wr & 3;
    const uint32_t epoch = *(volatile uint32_t*)FLAG_EPOCH(cta);
    const int hh = j & 1;
#define ACOL(A) (320 * hh + 64 * (((j >> 1) + 1 + (A)) & 3))
    if (pw == 0) {
      if (lane == 0) {
#pragma unroll
        for (int c = 3; c < 9; c++) tma2d(sb + SM_XN + c * 16384, &prm.xm, bar + 8 * (B_X + c), 64 * c, 128 * m);
        uint64_t pol;
        asm volatile("createpolicy.fractional.L2::evict_first.b64 %0, 1.0;" : "=l"(pol));
#pragma unroll 1
        for (int kb = 0; kb < 9; kb++) {
          const int s = kb % 3;
          if (kb >= 3) mbar_wait(bar + 8 * (B_QE + s), (kb / 3 - 1) & 1);
          const uint32_t fb = bar + 8 * (B_QF + s), dst = sb + SM_RING + s * QST;
          mbar_expect(fb, QST);
#pragma unroll
          for (int p = 0; p < 3; p++) {
            tma2d_h(dst + p * 8192, &prm.wqkv64, fb, 576 * p + 72 * j + 8 * hh, 64 * kb, pol);
            tma2d(dst + 24576 + p * 1024, &prm.wqkv8, fb, 576 * p + 72 * j + 64 - 64 * hh, 64 * kb);
          }
        }
        asm volatile("st.shared.u32 [%0], %1;" ::"r"(sb + SM_TAG), "r"((epoch + 1) & 1) : "memory");
        int col = 576 * j, kr = 0;
#pragma unroll 1
        for (int n = 0; n < N_G2; n++) {
          const uint32_t fb = bar + 8 * (B_F + (n & 7)), dst = sb + SM_RING + (n & 3) * BST;
          mbar_expect(fb, BST);
          if (n >= 4) mbar_wait(bar + 8 * (B_E + ((n - 3) & 7)), ((n - 3) >> 3) & 1);
          else if (n != 2) mbar_wait(bar + 8 * (B_QE + (n == 3 ? 2 : n)), 0);
          tma2d_h(dst, &prm.wg, fb, col, kr, pol);
          tma2d_h(dst + 8192, &prm.wu, fb, col, kr, pol);
          if ((kr += 64) == 576) { kr = 0; col += 64; }
        }
        uint32_t seen = 0;
#pragma unroll 1
        for (int b = 0; b < 26; b++) {
          const int n = N_G2 + 2 * b;
          const uint32_t fb = bar + 8 * (B_F + (n & 7)), dst = sb + (b & 3) * G2ST;
          const int own = b < 10 || b == 20 || b == 21, jj = own ? j : (j ^ 1), lb = b < 10 ? b : b < 20 ? b - 10 : 10 + (b & 1), need = (3 * lb + 6) >> 2;
          if (b < 24) {
            if (b == 10 || b == 20 || b == 22) seen = 0;
            if (seen < need) { seen = flag_wait_v(FLAG_H(m * 8 + jj), 9 * epoch + need) - 9 * epoch; fence_async(); }
          } else {
            flag_wait(FLAG_O((cta & ~1) + b - 24), epoch + 1);
            fence_async();
          }
          mbar_wait(bar + 8 * (B_E + ((n - 5) & 7)), ((n - 5) >> 3) & 1);
          if (b == 0) STAMPW(16);
          mbar_expect(fb, G2ST);
          if (b < 24) {
            bulk_g2s(dst, g_H + (m * 576 + 72 * jj + 6 * lb) * 512, 12288, fb);
#pragma unroll
            for (int a = 0; a < 4; a++) tma5d(dst + 12288 + a * 6144, &prm.wd[0], fb, ACOL(a), 36 * jj + 3 * lb);
            tma5d(dst + 36864, &prm.wd[1 + hh], fb, 0, 36 * jj + 3 * lb);
          } else {
            const int r = b - 24;
            bulk_g2s(dst, g_O + ((cta & ~1) + r) * 9 * 512 + r * 1024, 12288, fb);
#pragma unroll
            for (int a = 0; a < 4; a++) tma3d(dst + 12288 + a * 6144, &prm.wo3[0], fb, ACOL(a), 4 * (j & 6) + 5 * r);
            tma3d(dst + 36864, &prm.wo3[1 + hh], fb, 0, 4 * (j & 6) + 5 * r);
          }
          if (b == 0) STAMPW(17);
        }
        mbar_wait(bar + 8 * B_SP, 0);
        mbar_expect(bar + 8 * B_OL, 49152 + 32768);
        tma2d(sb + SM_RES, &prm.xm, bar + 8 * B_OL, ACOL(3), 128 * m);
        __nanosleep(200);
        tma2d(sb + SM_RES + 16384, &prm.xm, bar + 8 * B_OL, 256 + 32 * hh, 128 * m);
#pragma unroll 1
        for (int i = 0; i < 4; i++) {
          __nanosleep(200);
          tma3d(sb + SM_LB + i * 4096, &prm.wo2[0], bar + 8 * B_OL, ACOL(3), 8 * i + 3);
          tma3d(sb + SM_LB + 24576 + i * 4096, &prm.wo2[1 + hh], bar + 8 * B_OL, 0, 8 * i + 3);
          tma3d(sb + SM_LB + 16384 + i * 2048, &prm.wo16[0], bar + 8 * B_OL, ACOL(3), 8 * i);
          tma3d(sb + SM_LB + 40960 + i * 2048, &prm.wo16[1 + hh], bar + 8 * B_OL, 0, 8 * i);
        }
      }
    } else if (pw == 1) {
      if (lane == 0) {
        const int hx = hh * 3;
        int u = 0, kslot = 0, vrow = 0, kb = 0;
#pragma unroll 1
        for (int n = 0; n <= N_END; n++) {
          const uint32_t fb = bar + 8 * (B_F + (n & 7)), dst = n < N_AO ? sb + SM_KV + kslot * KVST : sb + SM_KV2 + (n - N_AO) * KVST;
          const bool att = n >= N_G2 || (n >= NG0 && kb != 0);
          if (++kb == 9) kb = 0;
          if (n >= N_AO) mbar_wait(bar + 8 * (B_E + ((n - 7) & 7)), ((n - 7) >> 3) & 1);
          mbar_expect(fb, !att || u < 2 ? 0 : (u == 2 || u == 128) ? KVST / 2 : KVST);
          if (n >= N_AO || (n > N_G2 && !(n & 1))) mbar_expect(fb, 0);
          if (u == 2 && att) { flag_wait(FLAG_KV(0, j), 16 * epoch + 16); fence_async(); STAMPW(18); }
          if (n >= 4 && n < N_AO) mbar_wait(bar + 8 * (B_E + ((n - 3) & 7)), ((n - 3) >> 3) & 1);
          if (att) {
            const int krow = (4 * j + ((u >> 5) ^ hx)) * 256 + ((u + 2 * m) & 31) * 8;
            if (u >= 2 && u < 128) tma2d(dst, &prm.kv, fb, 0, krow);
            if (u >= 3) tma2d(dst + 3072, &prm.kv, fb, 128, vrow);
            vrow = krow; u++;
            if (++kslot == 3) kslot = 0;
            if (u == 16) { flag_wait(FLAG_KV(1, j), 16 * epoch + 16); fence_async(); }
          }
        }
      }
    } else if (pw == 2) {
      if (lane == 0) {
#pragma unroll 1
        for (int i = 1; i < 18; i++) asm volatile("prefetch.tensormap [%0];" ::"l"(&prm.xm + i) : "memory");
        mbar_wait(bar + 8 * B_SK1, 0);
        STAMPW(22);
        fence_gpu(); flag_add(FLAG_KV(0, j));
        STAMPW(20);
        mbar_wait(bar + 8 * B_SK2, 0);
        fence_gpu(); flag_add(FLAG_KV(1, j));
#pragma unroll 1
        for (int t = 0; t < 9; t++) { mbar_wait(bar + 8 * B_SH, t & 1); __nanosleep(1000); fence_gpu(); flag_add(FLAG_H(cta)); }
        mbar_wait(bar + 8 * B_SO1, 0);
        fence_gpu(); flag_add(FLAG_O(cta));
      }
    } else {
      mbar_wait(bar + 8 * (B_X + 6), 0);
#pragma unroll 1
      for (int i = lane; i < 122; i += 32) pf_line(prm.pwqkv + (size_t)min(i * 128 + cta, 15551) * 64);
      mbar_wait(bar + 8 * (B_QE + 1), 0);
#pragma unroll 1
      for (int t = -3; t < 9; t++) {
        if (t >= 0) { mbar_wait(bar + 8 * B_SH, t & 1); __nanosleep(1500); }
        if (t < 6) {
#pragma unroll 1
          for (int i = lane; i < 72; i += 32) pf_line((i >= 36 ? prm.pwu : prm.pwg) + (size_t)(36 * m + (i >= 36 ? i - 36 : i)) * FF + 576 * j + 64 * (t + 3));
        }
        if ((t == 2 || t == 6 || t == 8)) {
          const uint32_t* kv = g_KV + (size_t)(4 * j + ((t == 2 ? 1 : t == 6 ? 2 : 3) ^ (hh * 3))) * SEQ * 20 + m * 2560;
#pragma unroll 1
          for (int i = lane; i < 80; i += 32) pf_line(kv + i * 32);
        }
        if (t >= 7) {
          const uint32_t* h = g_H + (m * 576 + 72 * j + 30 * (t - 7)) * 512;
#pragma unroll 1
          for (int i = lane; i < 480; i += 32) pf_line(h + i * 32);
        }
        if (t >= 5) {
#pragma unroll 1
          for (int i = lane; i < 81; i += 32) {
            const int l = (2 * m + hh) * 81 + i, r = l / 9;
            pf_line(prm.pwd + (size_t)(1152 * (j >> 1) + 576 * (r / 144) + 144 * (t - 5) + r % 144) * DM + 64 * (l % 9));
          }
        }
      }
      if (cta * 41 + lane < 5184) pf_line(prm.pwo + (size_t)(cta * 41 + lane) * 64);
      if (lane < 9 && cta * 41 + 32 + lane < 5184) pf_line(prm.pwo + (size_t)(cta * 41 + 32 + lane) * 64);
      if (lane == 0) {
      mbar_wait(bar + 8 * B_SP, 0);
      const int q = j >> 1;
#pragma unroll 1
      for (int i = 0; i < 14; i++) {
        bulk_s2g(g_P + cta * 3584 + i * 256, sb + SM_SEND + i * 4096, 4096);
        asm volatile("cp.async.bulk.commit_group;\ncp.async.bulk.wait_group.read 4;" ::: "memory");
      }
      asm volatile("cp.async.bulk.wait_group 0;" ::: "memory");
      fence_gpu();
      flag_add(FLAG_P(cta));
      STAMPW(15);
      mbar_expect(bar + 8 * B_RX, 73728);
#pragma unroll 1
      for (int a = 0; a < 3; a++) {
        const int src = m * 8 + 2 * ((q + 3 - a) & 3) + hh;
        flag_wait(FLAG_P(src), epoch + 1);
        fence_async();
        bulk_g2s(sb + SM_RECV + a * 24576, g_P + src * 3584 + a * 1024, 16384, bar + 8 * B_RX);
        bulk_g2s(sb + SM_RECV + a * 24576 + 16384, g_P + src * 3584 + 3072, 8192, bar + 8 * B_RX);
      }
      STAMPW(25);
      *FLAG_EPOCH(cta) = epoch + 1;
      }
    }
  } else {
    const int tid = threadIdx.x;
    const int t = lane & 3;
    const uint32_t l0 = lane == 0;
    const uint32_t adesc = (((sb + SM_XN + wg * 8192) & 0x3FFFF) >> 4) | LO_A;
    const uint32_t bdesc = (((sb + SM_RING) & 0x3FFFF) >> 4) | LO_B;
    const uint32_t kdesc0 = (((sb + SM_KV) & 0x3FFFF) >> 4) | LO_K;
    const int hx = (j & 1) * 3;
    float accA[64], accB[64];
    uint32_t qn[6];
    Att a;
    uint32_t gs = 0, s8 = 0, fph = 0;
#define G1_ISSUE(ACC, AD, BD) _Pragma("unroll") for (int k = 0; k < 4; k++) wg_ss_n128<HI_SW128, HI_SW128>(ACC, (AD) + k * 2, (BD) + k * 128);
#define G1_ISSUE_Z(ACC, BD)                                                                                    \
  wg_ss_z_n128<HI_SW128, HI_SW128>(ACC, adesc, BD);                                                            \
  _Pragma("unroll") for (int k = 1; k < 4; k++) wg_ss_n128<HI_SW128, HI_SW128>(ACC, adesc + k * 2, (BD) + k * 128);
#define F_BAR (bar + 8 * B_F + 8 * s8)
#define F_PH fph
#define RELEASE() mbar_arrive_if(bar + 8 * B_E + 8 * s8, l0);
#define NEXT_SLOT() { gs++; fph ^= s8 == 7; s8 = s8 == 7 ? 0 : s8 + 1; }
#define NEXT_B() bd = bd == bdesc + 3072 ? bdesc : bd + 1024;
#define G1_ONLY() { mbar_wait(F_BAR, F_PH); wg_fence(); G1_ISSUE(accA, adesc + gs * 1024, bdesc + (gs & 3) * 1024) wg_commit(); wg_wait<1>(); RELEASE() NEXT_SLOT() }
    {
      const int lr = wr * 16 + (lane & 15);
      uint32_t ra[4];
#pragma unroll
      for (int k = 0; k < 4; k++) ra[k] = sb + SM_XN + lr * 128 + (((2 * k + (lane >> 4)) ^ (lr & 7)) << 4);
      asm volatile("setmaxnreg.inc.sync.aligned.u32 240;");
      float aq[96], ar[12];
#pragma unroll
      for (int i = 0; i < 96; i++) aq[i] = __int_as_float(lane >> 5);
#pragma unroll
      for (int i = 0; i < 12; i++) ar[i] = __int_as_float(lane >> 5);
      pin<96>(aq); pin<12>(ar);
      float cs[2][4] = {}, q0 = 0.f, q1 = 0.f, q2 = 0.f, q3 = 0.f;
#pragma unroll 1
      for (int c = 0; c < 9; c++) {
        mbar_wait(bar + 8 * (B_X + c), 0);
        uint32_t v[4][4];
#pragma unroll
        for (int k = 0; k < 4; k++) ldsm4(v[k], ra[k] + c * 16384);
#pragma unroll
        for (int k = 0; k < 4; k++) {
          mma_ones(cs[k & 1], v[k]);
#pragma unroll
          for (int e = 0; e < 4; e += 2) {
            const float x0 = bf_lo(v[k][e]), x1 = bf_hi(v[k][e]), y0 = bf_lo(v[k][e + 1]), y1 = bf_hi(v[k][e + 1]);
            q0 = fmaf(x0, x0, q0); q1 = fmaf(x1, x1, q1); q2 = fmaf(y0, y0, q2); q3 = fmaf(y1, y1, q3);
          }
        }
      }
      STAMP(11);
      const float mean0 = (cs[0][0] + cs[1][0]) * (1.f / 576.f), mean1 = (cs[0][2] + cs[1][2]) * (1.f / 576.f);
      q0 += q1; q2 += q3;
      q0 += __shfl_xor_sync(0xffffffffu, q0, 1); q2 += __shfl_xor_sync(0xffffffffu, q2, 1);
      q0 += __shfl_xor_sync(0xffffffffu, q0, 2); q2 += __shfl_xor_sync(0xffffffffu, q2, 2);
      float var0 = fmaf(q0, 1.f / 576.f, -mean0 * mean0), var1 = fmaf(q2, 1.f / 576.f, -mean1 * mean1);
      if (__any_sync(0xffffffffu, !(mean0 * mean0 <= 8.f * var0) || !(mean1 * mean1 <= 8.f * var1))) {
        q0 = q2 = 0.f;
#pragma unroll 1
        for (int i = 0; i < 36; i++) {
          uint32_t v[4];
          ldsm4(v, ((ra[0] + (i >> 2) * 16384) ^ ((i & 3) << 5)));
#pragma unroll
          for (int e = 0; e < 4; e += 2) {
            const float x0 = bf_lo(v[e]) - mean0, x1 = bf_hi(v[e]) - mean0, y0 = bf_lo(v[e + 1]) - mean1, y1 = bf_hi(v[e + 1]) - mean1;
            q0 = fmaf(x0, x0, fmaf(x1, x1, q0)); q2 = fmaf(y0, y0, fmaf(y1, y1, q2));
          }
        }
        q0 += __shfl_xor_sync(0xffffffffu, q0, 1); q2 += __shfl_xor_sync(0xffffffffu, q2, 1);
        q0 += __shfl_xor_sync(0xffffffffu, q0, 2); q2 += __shfl_xor_sync(0xffffffffu, q2, 2);
        var0 = q0 * (1.f / 576.f); var1 = q2 * (1.f / 576.f);
      }
      const float inv0 = rcp_fast(bf_round(sqrt_fast(bf_round(bf_round(var0) + 1e-5f)))), inv1 = rcp_fast(bf_round(sqrt_fast(bf_round(bf_round(var1) + 1e-5f))));
      const uint32_t mb0 = pack(mean0, mean0), mb1 = pack(mean1, mean1);
      const uint32_t h0 = pack(inv0, inv0), h1 = pack(inv1, inv1);
      const uint32_t e0 = pack(inv0 - bf_lo(h0), inv0 - bf_lo(h0)), e1 = pack(inv1 - bf_lo(h1), inv1 - bf_lo(h1));
      uint32_t v[4][4], xn[4][4];
#pragma unroll
      for (int k = 0; k < 4; k++) ldsm4(v[k], ra[k]);
      STAMP(1);
      const uint32_t rdesc = (((sb + SM_RING + 24576) & 0x3FFFF) >> 4) | LO_R;
      uint32_t s = 0, ph = 0;
#pragma unroll 1
      for (int kb = 0; kb < 9; kb++) {
#pragma unroll
        for (int k = 0; k < 4; k++) {
          xn[k][0] = bscale2(bsub2(v[k][0], mb0), h0, e0); xn[k][1] = bscale2(bsub2(v[k][1], mb1), h1, e1);
          xn[k][2] = bscale2(bsub2(v[k][2], mb0), h0, e0); xn[k][3] = bscale2(bsub2(v[k][3], mb1), h1, e1);
        }
        pin<16>(&xn[0][0]);
        mbar_wait(bar + 8 * B_QF + 8 * s, ph);
        wg_fence();
#pragma unroll
        for (int k = 0; k < 4; k++) {
          wg_rs_n192<HI_SW128>(aq, xn[k][0], xn[k][1], xn[k][2], xn[k][3], bdesc + s * (QST >> 4) + k * 128);
          wg_rs_n24<HI_R>(ar, xn[k][0], xn[k][1], xn[k][2], xn[k][3], rdesc + s * (QST >> 4) + k * 16);
        }
        wg_commit();
#pragma unroll
        for (int k = 0; k < 4; k++) stsm4(ra[k] + kb * 16384, xn[k][0], xn[k][1], xn[k][2], xn[k][3]);
#pragma unroll
        for (int k = 0; k < 4; k++) ldsm4(v[k], ra[k] + (kb < 8 ? kb + 1 : 8) * 16384);
        if (kb == 8) {
          asm volatile("fence.proxy.async.shared::cta;" ::: "memory");
          __syncwarp();
          mbar_arrive_if(bar + 8 * B_NR + 8 * wg, l0);
        }
        wg_wait<0>();
        mbar_arrive_if(bar + 8 * B_QE + 8 * s, l0);
        if (++s == 3) { s = 0; ph ^= 1; }
      }
      pin<96>(aq); pin<12>(ar);
      STAMP(2);
      uint32_t* kvp = g_KV + (size_t)(4 * j) * SEQ * 20 + (16 * m + 2 * wr) * 160 + lane;
      uint32_t pk[2][9][2];
#pragma unroll
      for (int p = 0; p < 2; p++)
#pragma unroll
        for (int i = 0; i < 9; i++) {
          const float* src = i < 8 ? &aq[(8 * (p + 1) + i) * 4] : &ar[4 * (p + 1)];
          pk[p][i][0] = pack(src[0], src[1]); pk[p][i][1] = pack(src[2], src[3]);
        }
      const uint32_t sk = sb + SM_KV + wg * KVST + (wr & 3) * 768 + lane * 4;
      mbar_wait(bar + 8 * (B_QE + 2), 0);
      if (hx) {
#pragma unroll
        for (int p = 0; p < 2; p++) { rotate9(pk[p]); }
        store_kv_head<3>(pk, kvp, lane, sk, sk + KVST + 3072);
      } else store_kv_head<0>(pk, kvp, lane, sk, sk + KVST + 3072);
      asm volatile("fence.proxy.async.shared::cta;" ::: "memory");
      __syncwarp();
      mbar_arrive_if(bar + 8 * B_SK1, l0);
      mbar_arrive_if(bar + 8 * B_LK, l0);
      STAMP(3);
      mbar_wait(bar + 8 * B_NR + 8 * wg, 0);
      mbar_wait(bar + 8 * B_F, 0);
      wg_fence();
      G1_ISSUE_Z(accA, bdesc)
      wg_commit();
      RELEASE()
      NEXT_SLOT()
      mbar_wait(F_BAR, F_PH);
      wg_fence();
      G1_ISSUE(accA, adesc + 1024, bdesc + 1024)
      wg_commit();
      uint32_t pq[9][2];
#pragma unroll
      for (int i = 0; i < 9; i++) {
        const float* src = i < 8 ? &aq[i * 4] : &ar[0];
        pq[i][0] = bscale2(pack(src[0], src[1]), QS_HI, QS_LO); pq[i][1] = bscale2(pack(src[2], src[3]), QS_HI, QS_LO);
      }
      if (hx) rotate9(pq);
      pin<18>(&pq[0][0]);
      wg_wait<1>();
      RELEASE()
      NEXT_SLOT()
      G1_ONLY()
      mbar_wait(F_BAR, F_PH);
      wg_fence();
      G1_ISSUE(accA, adesc + 3 * 1024, bdesc + 3 * 1024)
      wg_commit();
      if (hx) store_kv_head<0>(pk, kvp, lane); else store_kv_head<3>(pk, kvp, lane);
      store_kv_head<1>(pk, kvp, lane);
      store_kv_head<2>(pk, kvp, lane);
      __syncwarp();
      mbar_arrive_if(bar + 8 * B_SK2, l0);
      wg_wait<1>();
      RELEASE()
      NEXT_SLOT()
      mbar_wait(F_BAR, F_PH);
      wg_fence();
      G1_ISSUE(accA, adesc + 4 * 1024, bdesc)
      wg_commit();
      uint32_t qf[4][6];
#pragma unroll
      for (int hp = 0; hp < 4; hp++) {
        const bool up = t < hp;
        qf[hp][0] = up ? pq[2 * hp + 1][0] : pq[2 * hp][0]; qf[hp][1] = up ? pq[2 * hp + 1][1] : pq[2 * hp][1];
        qf[hp][2] = up ? pq[2 * hp + 2][0] : pq[2 * hp + 1][0]; qf[hp][3] = up ? pq[2 * hp + 2][1] : pq[2 * hp + 1][1];
        qf[hp][4] = t == hp ? pq[2 * hp + 2][0] : 0u; qf[hp][5] = t == hp ? pq[2 * hp + 2][1] : 0u;
      }
      if (hx) {
        store_q(qf[0], cta, 0, tid); store_q(qf[1], cta, 1, tid);
#pragma unroll
        for (int i = 0; i < 6; i++) { a.q[i] = qf[3][i]; qn[i] = qf[2][i]; }
      } else {
        store_q(qf[2], cta, 2, tid); store_q(qf[3], cta, 3, tid);
#pragma unroll
        for (int i = 0; i < 6; i++) { a.q[i] = qf[0][i]; qn[i] = qf[1][i]; }
      }
      a.q[6] = __shfl_sync(0xffffffffu, lane, 0); a.q[7] = __shfl_sync(0xffffffffu, lane >> 1, 1);
#pragma unroll
      for (int i = 0; i < 16; i++) a.p[i] = 0;
#pragma unroll
      for (int i = 0; i < 12; i++) a.o[i] = 0.f;
      pin<16>(a.p); pin<12>(a.o); pin<8>(a.q);
      wg_wait<1>();
      RELEASE()
      NEXT_SLOT()
    }
    static_assert(NG0 == 5, "item boundaries must fall into even F tiles / even GEMM2 slots");
    STAMP(4);
    mbar_wait(bar + 8 * B_LK, 0);
    mbar_wait(F_BAR, F_PH);
    STAMP(23);
    uint32_t kd = kdesc0;
    uint32_t it = 0;
    uint32_t ox0 = 0, ox1 = 0;
    uint32_t* hdst = g_H + ((m * 576 + 72 * j + (t >> 1)) * 128 + 16 * wr + (lane >> 2)) * 4 + 2 * (t & 1);
    uint32_t ad = adesc + NG0 * 1024, bd = bdesc + (gs & 3) * 1024;

#define ITEM_FIRST()                                                                                           \
  {                                                                                                            \
    pin<12>(a.o);                                                                                              \
    if (it != 0) {                                                                                             \
      uint32_t w[4];                                                                                           \
      o_normalise(a.o, w, ox0, ox1, ((it >> 5) - 1) ^ hx, lane, sb + SM_BAD, wr);                              \
      uint32_t* d = g_O + cta * 9 * 512 + (((it >> 5) - 1) ^ hx) * 1024 + wr * 64 + lane;                      \
      d[0] = w[0]; d[32] = w[1]; d[512] = w[2]; d[544] = w[3];                                                 \
    }                                                                                                          \
    if (it == 96) mbar_arrive_if(bar + 8 * B_SO1, l0 & (bad_heads(sb + SM_BAD, wr) == 0));                     \
    first_tile(a, (it >> 5) ^ hx, lane);                                                                       \
  }
#define KV_ADVANCE() { kd = kd == kdesc0 + 768 ? kdesc0 : kd + 384; }
#define SOFTMAX_NEXT() { softmax_a(a); mbar_wait(F_BAR, F_PH); softmax_b(a); }
#define EPI_STEP(ACCN, ACCO)                                                                                   \
  {                                                                                                            \
    wg_fence();                                                                                                \
    G1_ISSUE_Z(ACCN, bd)                                                                                       \
    wg_commit();                                                                                               \
    wg_wait<1>();                                                                                              \
    pin<64>(ACCO);                                                                                             \
    RELEASE()                                                                                                  \
    NEXT_SLOT()                                                                                                \
    ad = adesc + 1024; NEXT_B()                                                                                \
    const uint32_t ok = mbar_test(F_BAR, F_PH);                                                                \
    h_epilogue(ACCO, hdst);                                                                                    \
    hdst += 4096;                                                                                              \
    __syncwarp();                                                                                              \
    mbar_arrive_if(bar + 8 * B_SH, l0);                                                                        \
    if (__builtin_expect(!ok, 0)) mbar_wait(F_BAR, F_PH);                                                                                            \
  }
#define ATT_LOOP1(ACC, ITEMS)                                                                                  \
  do {                                                                                                         \
    wg_fence();                                                                                                \
    issue_att(a, kd);                                                                                          \
    wg_commit();                                                                                               \
    G1_ISSUE(ACC, ad, bd)                                                                                      \
    wg_commit();                                                                                               \
    wg_wait<1>();                                                                                              \
    pin<32>(a.s);                                                                                              \
    RELEASE()                                                                                                  \
    TRACE()                                                                                                    \
    if (ITEMS) { if (__builtin_expect(((it + 1) & 31) < 2, 0)) { if (it & 1) { store_q(a.q, cta, (it >> 5) ^ hx, tid); _Pragma("unroll") for (int i = 0; i < 6; i++) asm volatile("mov.b32 %0, %1;" : "=r"(a.q[i]) : "r"(qn[i])); } else { if (it == 64) fetch_q(qn, cta, 3 ^ hx, tid); ITEM_FIRST() } } } \
    NEXT_SLOT() it++;                                                                                                \
    KV_ADVANCE()                                                                                               \
    ad += 1024; NEXT_B()                                                                                       \
    SOFTMAX_NEXT()                                                                                             \
    pin<8>(a.q);                                                                                               \
  } while (ad != adesc + 9 * 1024);
#pragma unroll 1
    for (int pr = 0;; pr++) {
      ATT_LOOP1(accA, true)
      if (pr == 4) break;
      if (pr == 2) STAMP(29);
      EPI_STEP(accB, accA)
      if (pr == 2) STAMP(30);
      ATT_LOOP1(accB, false)
      if (pr == 2) STAMP(31);
      if (pr == 3) fetch_q(qn, cta, 2 ^ hx, tid);
      EPI_STEP(accA, accB)
      if (pr == 2) STAMP(21);
      if (pr == 3) STAMP(14);
    }
    STAMP(5);
    wg_wait<0>();
    pin<64>(accA);
    h_epilogue(accA, hdst);
    __syncwarp();
    mbar_arrive_if(bar + 8 * B_SH, l0);
    mbar_wait(bar + 8 * B_E, 0);
    asm volatile("st.shared.v4.b32 [%0], {%1,%2,%3,%4};\nst.shared.v2.b32 [%5], {%6,%7};" ::"r"(sb + SM_QS + tid * 16), "r"(qn[0]), "r"(qn[1]), "r"(qn[2]), "r"(qn[3]),
                 "r"(sb + SM_QS + 4096 + tid * 8), "r"(qn[4]), "r"(qn[5]) : "memory");
    asm volatile("fence.proxy.async.shared::cta;" ::: "memory");
    STAMP(6);
    STAMP(12);

    float acc2[144];
    const uint32_t a2desc = (((sb + wg * 1024) & 0x3FFFF) >> 4) | LO_O;
    const uint32_t b2desc = (((sb + 12288) & 0x3FFFF) >> 4) | LO_B48;
    ad = a2desc; bd = b2desc;
#define G2_LO(K) wg_ss_n128<HI_O, HI_SW128>(acc2, ad + (K) * 256, bd + (K) * 128);
#define G2_HI(K) wg_ss_n160<HI_O, HI_SW128>(acc2 + 64, ad + (K) * 256, bd + (K) * 128 + 768);
#define ATT_PAIR(ZERO)                                                                                         \
  {                                                                                                            \
    wg_fence();                                                                                                \
    issue_att(a, kd);                                                                                          \
    wg_commit();                                                                                               \
    if (ZERO) { wg_ss_z_n128<HI_O, HI_SW128>(acc2, ad, bd); wg_ss_z_n160<HI_O, HI_SW128>(acc2 + 64, ad, bd + 768); } \
    else { G2_LO(0) G2_HI(0) }                                                                                 \
    G2_LO(1)                                                                                                   \
    wg_commit();                                                                                               \
    wg_wait<1>();                                                                                              \
    pin<32>(a.s);                                                                                              \
    RELEASE()                                                                                                  \
    TRACE()                                                                                                    \
    if (!(ZERO)) { if (__builtin_expect(gs == N_G2 + 96 - IT_G2, 0)) ITEM_FIRST() }                                    \
    NEXT_SLOT() it++;                                                                                                \
    KV_ADVANCE()                                                                                               \
    SOFTMAX_NEXT()                                                                                             \
    pin<8>(a.q);                                                                                               \
    wg_fence();                                                                                                \
    issue_att(a, kd);                                                                                          \
    wg_commit();                                                                                               \
    G2_HI(1) G2_LO(2) G2_HI(2)                                                                                 \
    wg_commit();                                                                                               \
    wg_wait<1>();                                                                                              \
    pin<32>(a.s);                                                                                              \
    RELEASE()                                                                                                  \
    TRACE()                                                                                                    \
    if (!(ZERO) && __builtin_expect(gs == N_G2 + 95 - IT_G2, 0)) {                                                     \
      const int ft = fresh_tid();                                                                              \
      asm volatile("ld.shared.v4.b32 {%0,%1,%2,%3}, [%6];\nld.shared.v2.b32 {%4,%5}, [%7];" : "=r"(a.q[0]), "=r"(a.q[1]), "=r"(a.q[2]), "=r"(a.q[3]), \
                   "=r"(a.q[4]), "=r"(a.q[5]) : "r"(sb + SM_QS + ft * 16), "r"(sb + SM_QS + 4096 + ft * 8) : "memory"); \
    }                                                                                                          \
    NEXT_SLOT() it++;                                                                                                \
    KV_ADVANCE()                                                                                               \
    ad = ad == a2desc + 3 * 2688 ? a2desc : ad + 2688; bd = ad + (b2desc - a2desc);                                \
    SOFTMAX_NEXT()                                                                                             \
    pin<8>(a.q);                                                                                               \
  }
    ATT_PAIR(true)
#pragma unroll 1
    for (int half = 0; half < 2; half++) {
      const uint32_t stop = half ? N_AO : N_G2 + 46;
      do ATT_PAIR(false) while (gs != stop);
      if (!half) {
        const uint32_t bad = bad_heads(sb + SM_BAD, wr);
        if (bad) { repair_rows(cta, wr, bad, 3 ^ hx, false); mbar_arrive_if(bar + 8 * B_SO1, l0); }
      }
    }
    STAMP(13);
    wg_wait<0>();
    pin<144>(acc2);
    mbar_wait(bar + 8 * (B_E + 1), 0);
    stage_partials(acc2, sb + SM_SEND, fresh_tid());
    asm volatile("fence.proxy.async.shared::cta;" ::: "memory");
    __syncwarp();
    mbar_arrive_if(bar + 8 * B_SP, l0);
    static_assert(N_END - N_AO == 8, "SM_KV2 layout");
    kd = (((sb + SM_KV2) & 0x3FFFF) >> 4) | LO_K;
    do {
      wg_fence();
      issue_att(a, kd);
      wg_commit();
      wg_wait<0>();
      pin<32>(a.s);
      RELEASE()
      TRACE()
      NEXT_SLOT() it++;
      kd += 384;
      SOFTMAX_NEXT()
    } while (gs != N_END);
    STAMP(7);
    wg_fence();
    issue_pv(a, kd);
    wg_commit();
    int tid2, bid2;
    asm volatile("mov.u32 %0, %%tid.x;" : "=r"(tid2));
    asm volatile("mov.u32 %0, %%ctaid.x;" : "=r"(bid2));
    const int m2 = bid2 & 15, j2 = bid2 >> 4;
    uint32_t tag;
    asm volatile("ld.shared.u32 %0, [%1];" : "=r"(tag) : "r"(sb + SM_TAG) : "memory");
    wg_wait<0>();
    pin<12>(a.o);
    {
      uint32_t w[4];
      o_normalise(a.o, w, ox0, ox1, 3 ^ hx, lane, sb + SM_BAD, wr);
      ox0 = __shfl_xor_sync(0xffffffffu, ox0, 2); ox1 = __shfl_xor_sync(0xffffffffu, ox1, 2);
      const uint32_t bad = bad_heads(sb + SM_BAD, wr);
      if (bad) {
        uint32_t* d = g_O + cta * 9 * 512 + wr * 64 + lane;
        uint32_t* h = d + (3 ^ hx) * 1024;
        h[0] = w[0]; h[32] = w[1]; h[512] = w[2]; h[544] = w[3]; d[4096] = ox0; d[4128] = ox1;
        __syncwarp();
        repair_rows(cta, wr, bad, 3 ^ hx, true);
        w[0] = __ldcg(h); w[1] = __ldcg(h + 32); w[2] = __ldcg(h + 512); w[3] = __ldcg(h + 544); ox0 = __ldcg(d + 4096); ox1 = __ldcg(d + 4128);
      }
      asm volatile("st.relaxed.gpu.global.v4.b32 [%0], {%1,%2,%3,%4};" ::"l"(g_L + (m2 * 8 + j2) * 384 + tid2), "r"((w[0] & ~1u) | tag), "r"((w[1] & ~1u) | tag),
                   "r"((w[2] & ~1u) | tag), "r"((w[3] & ~1u) | tag) : "memory");
      asm volatile("st.relaxed.gpu.global.v2.b32 [%0], {%1,%2};" ::"l"(reinterpret_cast<uint2*>(g_L + (m2 * 8 + j2) * 384 + 256) + tid2), "r"((ox0 & ~1u) | tag),
                   "r"((ox1 & ~1u) | tag) : "memory");
    }
    STAMP(8);
    uint32_t la[48];
    const uint4* p4 = g_L + m2 * 8 * 384 + tid2;
    const uint2* p2 = reinterpret_cast<const uint2*>(g_L + m2 * 8 * 384 + 256) + tid2;
#define LOAD_LA2() { ld2<0>(la + 32, p2); ld2<6144>(la + 34, p2); ld2<12288>(la + 36, p2); ld2<18432>(la + 38, p2); \
                     ld2<24576>(la + 40, p2); ld2<30720>(la + 42, p2); ld2<36864>(la + 44, p2); ld2<43008>(la + 46, p2); }
#define LOAD_LA4() { ld4<0>(la, p4); ld4<6144>(la + 4, p4); ld4<12288>(la + 8, p4); ld4<18432>(la + 12, p4); \
                     ld4<24576>(la + 16, p4); ld4<30720>(la + 20, p4); ld4<36864>(la + 24, p4); ld4<43008>(la + 28, p4); }
    float fin[48];
    uint32_t id[4][4];
    {
      uint32_t id2[4][4];
#pragma unroll
      for (int k = 0; k < 4; k++) {
        asm volatile("ld.volatile.shared.v4.b32 {%0,%1,%2,%3}, [%4];" : "=r"(id[k][0]), "=r"(id[k][1]), "=r"(id[k][2]), "=r"(id[k][3])
                     : "r"(sb + SM_ID + ((wr & 3) == k ? lane : 1) * 16) : "memory");
#pragma unroll
        for (int e = 0; e < 4; e++) id2[k][e] = id[k][e] + (id[k][e] & 0x00800080u);
      }
      pin<16>(&id[0][0]); pin<16>(&id2[0][0]);
      const uint32_t xdesc = (((sb + SM_RES + wg * 8192) & 0x3FFFF) >> 4) | LO_B;
      STAMP(26);
      mbar_wait(bar + 8 * B_OL, 0);
      STAMP(27);
      wg_fence();
      wg_rsb_z_n64<HI_SW128>(fin, id2[0][0], id2[0][1], id2[0][2], id2[0][3], xdesc);
      wg_rs_z_n32<HI_SW128>(fin + 32, id2[0][0], id2[0][1], id2[0][2], id2[0][3], xdesc + 1024);
#pragma unroll
      for (int k = 1; k < 4; k++) {
        wg_rsb_n64<HI_SW128>(fin, id2[k][0], id2[k][1], id2[k][2], id2[k][3], xdesc + k * 128);
        wg_rs_n32<HI_SW128>(fin + 32, id2[k][0], id2[k][1], id2[k][2], id2[k][3], xdesc + 1024 + k * 128);
      }
      wg_commit();
    }
    STAMP(28);
    const uint32_t pdesc = (((sb + SM_RECV + wg * 8192) & 0x3FFFF) >> 4) | LO_B, hdesc = (((sb + SM_RECV + 16384 + wg * 4096) & 0x3FFFF) >> 4) | LO_B;
#define RX_MMAS()                                                                                              \
  wg_fence();                                                                                                  \
  _Pragma("unroll") for (int a3 = 0; a3 < 3; a3++)                                                             \
    _Pragma("unroll") for (int k = 0; k < 4; k++) {                                                            \
      wg_rsb_n64<HI_SW128>(fin, id[k][0], id[k][1], id[k][2], id[k][3], pdesc + a3 * 1536 + k * 128);          \
      wg_rs_n32<HI_SW64>(fin + 32, id[k][0], id[k][1], id[k][2], id[k][3], hdesc + a3 * 1536 + k * 64);        \
    }                                                                                                          \
  wg_commit();
    mbar_wait(bar + 8 * B_RX, 0);
    STAMP(24);
    RX_MMAS()
    wg_wait<0>();
    pin<48>(fin);
#pragma unroll
    for (int i = 0; i < 48; i++) fin[i] += acc2[96 + i];
    pin<48>(fin);
    for (uint32_t tries = 0; tries < 0x400000u; tries++) {
      const uint32_t* pw = reinterpret_cast<const uint32_t*>(g_L + (m2 * 8 + (lane & 7)) * 384 + 256) + (tid2 | 31) * 2 + 1;
      uint32_t bad;
      do {
        asm volatile("ld.relaxed.gpu.global.b32 %0, [%1];" : "=r"(bad) : "l"(pw) : "memory");
      } while (!__all_sync(0xffffffffu, !((bad ^ tag) & 1)) && ++tries < 0x400000u);
      LOAD_LA4()
      LOAD_LA2()
      bad = 0;
#pragma unroll
      for (int i = 0; i < 48; i++) bad |= la[i] ^ tag;
      if (__all_sync(0xffffffffu, !(bad & 1))) break;
    }
#pragma unroll
    for (int i = 0; i < 48; i++) la[i] ^= tag;
    pin<48>(la);
    STAMP(19);
    const uint32_t ldesc = (((sb + SM_LB) & 0x3FFFF) >> 4) | LO_B;
    wg_fence();
#pragma unroll
    for (int k = 0; k < 12; k++) {
      wg_rsb_n64<HI_SW128>(fin, la[4 * k], la[4 * k + 1], la[4 * k + 2], la[4 * k + 3], ldesc + k * 128);
      wg_rs_n32<HI_SW128>(fin + 32, la[4 * k], la[4 * k + 1], la[4 * k + 2], la[4 * k + 3], ldesc + 1536 + k * 128);
    }
    wg_commit();
    wg_wait<0>();
    pin<48>(fin);
    STAMP(9);
    final_epilogue(fin, prm, m2, j2 & 1, j2 >> 1, tid2);
    STAMP(10);
  }
}

typedef CUresult (*EncodeFn)(CUtensorMap*, CUtensorMapDataType, cuuint32_t, void*, const cuuint64_t*, const cuuint64_t*, const cuuint32_t*, const cuuint32_t*,
                             CUtensorMapInterleave, CUtensorMapSwizzle, CUtensorMapL2promotion, CUtensorMapFloatOOBfill);

void enc2d(EncodeFn enc, CUtensorMap* tm, const void* base, uint64_t w, uint64_t h, uint64_t pitch_elems, uint32_t bw, uint32_t bh, CUtensorMapSwizzle sw) {
  cuuint64_t dims[2] = {w, h}, str[1] = {pitch_elems * 2};
  cuuint32_t box[2] = {bw, bh}, es[2] = {1, 1};
  enc(tm, CU_TENSOR_MAP_DATA_TYPE_BFLOAT16, 2, const_cast<void*>(base), dims, str, box, es, CU_TENSOR_MAP_INTERLEAVE_NONE, sw,
      CU_TENSOR_MAP_L2_PROMOTION_L2_128B, CU_TENSOR_MAP_FLOAT_OOB_FILL_NONE);
}

}

extern "C" void kernel_launch(void* const* d_in, const int* in_sizes, int n_in, void* d_out, int out_size) {
  (void)in_sizes; (void)n_in; (void)out_size;
  const __nv_bfloat16* x = (const __nv_bfloat16*)d_in[0];
  const __nv_bfloat16* wqkv = (const __nv_bfloat16*)d_in[1];
  const __nv_bfloat16* wo = (const __nv_bfloat16*)d_in[2];
  const __nv_bfloat16* wg = (const __nv_bfloat16*)d_in[4];
  const __nv_bfloat16* wu = (const __nv_bfloat16*)d_in[5];
  const __nv_bfloat16* wd = (const __nv_bfloat16*)d_in[6];
  void* fn = nullptr;
  cudaDriverEntryPointQueryResult qr;
  cudaGetDriverEntryPoint("cuTensorMapEncodeTiled", &fn, cudaEnableDefault, &qr);
  EncodeFn enc = (EncodeFn)fn;
  void* kvp = nullptr;
  cudaGetSymbolAddress(&kvp, g_KV);
  Params p;
  enc2d(enc, &p.xm, x, DM, SEQ, DM, 64, 128, CU_TENSOR_MAP_SWIZZLE_128B);
  enc2d(enc, &p.kv, kvp, 320, 32 * 256, 320, 192, 8, CU_TENSOR_MAP_SWIZZLE_NONE);
  enc2d(enc, &p.wqkv64, wqkv, 3 * DM, DM, 3 * DM, 64, 64, CU_TENSOR_MAP_SWIZZLE_128B);
  enc2d(enc, &p.wqkv8, wqkv, 3 * DM, DM, 3 * DM, 8, 64, CU_TENSOR_MAP_SWIZZLE_NONE);
  enc2d(enc, &p.wg, wg, FF, DM, FF, 64, 64, CU_TENSOR_MAP_SWIZZLE_128B);
  enc2d(enc, &p.wu, wu, FF, DM, FF, 64, 64, CU_TENSOR_MAP_SWIZZLE_128B);
  for (int v = 0; v < 3; v++) {
    const cuuint64_t wdt = v ? 32 : DM;
    const int c0 = v ? 256 + 32 * (v - 1) : 0;
    for (int e = 0; e < 3; e++) {
      cuuint64_t d3[3] = {wdt, e == 2 ? 2u : 16u, 32}, s3[2] = {DM * 2, 18 * DM * 2};
      cuuint32_t b3[3] = {64, e == 2 ? 2u : 16u, e == 0 ? 3u : e == 1 ? 2u : 8u}, e3[3] = {1, 1, 1};
      enc(e == 0 ? &p.wo3[v] : e == 1 ? &p.wo2[v] : &p.wo16[v], CU_TENSOR_MAP_DATA_TYPE_BFLOAT16, 3, (void*)(wo + c0 + (e == 2 ? 16 * DM : 0)), d3, s3, b3, e3,
          CU_TENSOR_MAP_INTERLEAVE_NONE, CU_TENSOR_MAP_SWIZZLE_128B, CU_TENSOR_MAP_L2_PROMOTION_L2_128B, CU_TENSOR_MAP_FLOAT_OOB_FILL_NONE);
    }
    cuuint64_t dims[5] = {wdt, 2, 2, 4, FF / 16}, str[4] = {DM * 2, 8 * DM * 2, 2 * DM * 2, 16 * DM * 2};
    cuuint32_t box[5] = {64, 2, 2, 4, 3}, es[5] = {1, 1, 1, 1, 1};
    enc(&p.wd[v], CU_TENSOR_MAP_DATA_TYPE_BFLOAT16, 5, (void*)(wd + c0), dims, str, box, es, CU_TENSOR_MAP_INTERLEAVE_NONE,
        CU_TENSOR_MAP_SWIZZLE_128B, CU_TENSOR_MAP_L2_PROMOTION_L2_128B, CU_TENSOR_MAP_FLOAT_OOB_FILL_NONE);
  }
  p.x = x; p.pwqkv = wqkv; p.pwo = wo; p.pwg = wg; p.pwu = wu; p.pwd = wd;
  p.out = (__nv_bfloat16*)d_out;
  cudaFuncSetAttribute(fused_kernel, cudaFuncAttributeMaxDynamicSharedMemorySize, SM_TOTAL);
  fused_kernel<<<NCTA, 384, SM_TOTAL, cudaStreamPerThread>>>(p);
}
```

```cpp
#include <cuda_runtime.h>
#include <cuda.h>
#include <cuda_bf16.h>
#include <stdint.h>

namespace {

constexpr int SEQ = 2048, DM = 576, FF = 4608;
constexpr int NCTA = 128;

constexpr uint32_t SM_XN = 0;
constexpr uint32_t SM_RING = 147456;
constexpr uint32_t SM_KV = 212992;
constexpr uint32_t QST = 27648, BST = 16384, KVST = 6144;
constexpr uint32_t G2ST = 43008;
constexpr uint32_t SM_LB = 0, SM_RES = 49152, SM_SEND = 86016, SM_RECV = SM_SEND;
constexpr uint32_t SM_QS = 204800;
constexpr uint32_t SM_KV2 = SM_KV - 6 * KVST;
constexpr uint32_t SM_ID = 231424;
constexpr uint32_t SM_BAR = 231936;
constexpr uint32_t SM_TAG = 232436;
constexpr uint32_t SM_BAD = 232432;
constexpr uint32_t SM_TOTAL = 232448;
enum { B_F = 0, B_E = 8, B_QF = 16, B_QE = 19, B_SK1 = 22, B_SK2 = 23, B_SH = 24, B_SO1 = 25, B_LK = 26, B_SP = 27, B_OL = 28, B_RX = 29, B_NR = 30, B_X = 32, B_N = 41 };
constexpr int N_G2 = 81, N_AO = 133;
#define N_END (136 + NG0)
#define IT_G2 (73 - NG0)
constexpr int NG0 = 5;
constexpr int SM_B = 12;

constexpr uint32_t HI_SW128 = 0x40000040u;
constexpr uint32_t LO_A = 1u << 16;
constexpr uint32_t LO_B = 512u << 16;
constexpr uint32_t HI_R = 64u, LO_R = 8u << 16;
constexpr uint32_t HI_K = 24u, LO_K = 8u << 16;
constexpr uint32_t HI_V = 8u, LO_V = 24u << 16;
constexpr uint32_t LO_B48 = 384u << 16;
constexpr uint32_t HI_O = 8u, LO_O = 128u << 16;

constexpr uint32_t QS_HI = 0x3eae3eaeu, QS_LO = 0x39553955u;
constexpr float MOFF = 90.f;

struct __align__(64) Params {
  CUtensorMap xm, wqkv64, wqkv8, wg, wu, kv, wd[3], wo3[3], wo2[3], wo16[3];
  const __nv_bfloat16 *x, *pwqkv, *pwo, *pwg, *pwu, *pwd;
  __nv_bfloat16* out;
};

__device__ __align__(1024) uint32_t g_H[16 * 576 * 512];
__device__ __align__(1024) uint32_t g_O[NCTA * 9 * 512];
__device__ __align__(1024) uint32_t g_KV[32 * SEQ * 20];
__device__ __align__(1024) uint32_t g_Q[NCTA * 4 * 1152];
__device__ __align__(1024) uint4 g_P[NCTA * 3584];
__device__ __align__(1024) uint4 g_L[NCTA * 384];
__device__ float g_S[NCTA * 8 * SEQ];
__device__ uint32_t g_flags[16 * 32 + NCTA * 32 * 4];
#define FLAG_KV(l, j) (&g_flags[((l) * 8 + (j)) * 32])
#define FLAG_H(c) (&g_flags[16 * 32 + (c) * 32])
#define FLAG_O(c) (&g_flags[16 * 32 + NCTA * 32 + (c) * 32])
#define FLAG_P(c) (&g_flags[16 * 32 + NCTA * 64 + (c) * 32])
#define FLAG_EPOCH(c) (&g_flags[16 * 32 + NCTA * 96 + (c) * 32])
#define STAMP(i)
#define STAMPW(i)
#define TRACE()

template<uint32_t BHI> __device__ __forceinline__ void wg_rs_n192(float* d, uint32_t a0, uint32_t a1, uint32_t a2, uint32_t a3, uint32_t b) {
  asm volatile("{\n.reg .pred p;\n.reg .b64 db;\nsetp.ne.b32 p, 1, 0;\nmov.b64 db, {%100, %101};\n"
    "wgmma.mma_async.sync.aligned.m64n192k16.f32.bf16.bf16 {%0, %1, %2, %3, %4, %5, %6, %7, %8, %9, %10, %11, %12, %13, %14, %15, %16, %17, %18, %19, %20, %21, %22, %23, %24, %25, %26, %27, %28, %29, %30, %31, %32, %33, %34, %35, %36, %37, %38, %39, %40, %41, %42, %43, %44, %45, %46, %47, %48, %49, %50, %51, %52, %53, %54, %55, %56, %57, %58, %59, %60, %61, %62, %63, %64, %65, %66, %67, %68, %69, %70, %71, %72, %73, %74, %75, %76, %77, %78, %79, %80, %81, %82, %83, %84, %85, %86, %87, %88, %89, %90, %91, %92, %93, %94, %95}, {%96, %97, %98, %99}, db, p, 1, 1, 1;\n}\n"
    : "+f"(d[0]), "+f"(d[1]), "+f"(d[2]), "+f"(d[3]), "+f"(d[4]), "+f"(d[5]), "+f"(d[6]), "+f"(d[7]), "+f"(d[8]), "+f"(d[9]), "+f"(d[10]), "+f"(d[11]), "+f"(d[12]), "+f"(d[13]), "+f"(d[14]), "+f"(d[15]), "+f"(d[16]), "+f"(d[17]), "+f"(d[18]), "+f"(d[19]), "+f"(d[20]), "+f"(d[21]), "+f"(d[22]), "+f"(d[23]), "+f"(d[24]), "+f"(d[25]), "+f"(d[26]), "+f"(d[27]), "+f"(d[28]), "+f"(d[29]), "+f"(d[30]), "+f"(d[31]), "+f"(d[32]), "+f"(d[33]), "+f"(d[34]), "+f"(d[35]), "+f"(d[36]), "+f"(d[37]), "+f"(d[38]), "+f"(d[39]), "+f"(d[40]), "+f"(d[41]), "+f"(d[42]), "+f"(d[43]), "+f"(d[44]), "+f"(d[45]), "+f"(d[46]), "+f"(d[47]), "+f"(d[48]), "+f"(d[49]), "+f"(d[50]), "+f"(d[51]), "+f"(d[52]), "+f"(d[53]), "+f"(d[54]), "+f"(d[55]), "+f"(d[56]), "+f"(d[57]), "+f"(d[58]), "+f"(d[59]), "+f"(d[60]), "+f"(d[61]), "+f"(d[62]), "+f"(d[63]), "+f"(d[64]), "+f"(d[65]), "+f"(d[66]), "+f"(d[67]), "+f"(d[68]), "+f"(d[69]), "+f"(d[70]), "+f"(d[71]), "+f"(d[72]), "+f"(d[73]), "+f"(d[74]), "+f"(d[75]), "+f"(d[76]), "+f"(d[77]), "+f"(d[78]), "+f"(d[79]), "+f"(d[80]), "+f"(d[81]), "+f"(d[82]), "+f"(d[83]), "+f"(d[84]), "+f"(d[85]), "+f"(d[86]), "+f"(d[87]), "+f"(d[88]), "+f"(d[89]), "+f"(d[90]), "+f"(d[91]), "+f"(d[92]), "+f"(d[93]), "+f"(d[94]), "+f"(d[95])
    : "r"(a0), "r"(a1), "r"(a2), "r"(a3), "r"(b), "n"(BHI));
}
template<uint32_t BHI> __device__ __forceinline__ void wg_rs_z_n192(float* d, uint32_t a0, uint32_t a1, uint32_t a2, uint32_t a3, uint32_t b) {
  asm volatile("{\n.reg .pred p;\n.reg .b64 db;\nsetp.ne.b32 p, 0, 0;\nmov.b64 db, {%100, %101};\n"
    "wgmma.mma_async.sync.aligned.m64n192k16.f32.bf16.bf16 {%0, %1, %2, %3, %4, %5, %6, %7, %8, %9, %10, %11, %12, %13, %14, %15, %16, %17, %18, %19, %20, %21, %22, %23, %24, %25, %26, %27, %28, %29, %30, %31, %32, %33, %34, %35, %36, %37, %38, %39, %40, %41, %42, %43, %44, %45, %46, %47, %48, %49, %50, %51, %52, %53, %54, %55, %56, %57, %58, %59, %60, %61, %62, %63, %64, %65, %66, %67, %68, %69, %70, %71, %72, %73, %74, %75, %76, %77, %78, %79, %80, %81, %82, %83, %84, %85, %86, %87, %88, %89, %90, %91, %92, %93, %94, %95}, {%96, %97, %98, %99}, db, p, 1, 1, 1;\n}\n"
    : "=f"(d[0]), "=f"(d[1]), "=f"(d[2]), "=f"(d[3]), "=f"(d[4]), "=f"(d[5]), "=f"(d[6]), "=f"(d[7]), "=f"(d[8]), "=f"(d[9]), "=f"(d[10]), "=f"(d[11]), "=f"(d[12]), "=f"(d[13]), "=f"(d[14]), "=f"(d[15]), "=f"(d[16]), "=f"(d[17]), "=f"(d[18]), "=f"(d[19]), "=f"(d[20]), "=f"(d[21]), "=f"(d[22]), "=f"(d[23]), "=f"(d[24]), "=f"(d[25]), "=f"(d[26]), "=f"(d[27]), "=f"(d[28]), "=f"(d[29]), "=f"(d[30]), "=f"(d[31]), "=f"(d[32]), "=f"(d[33]), "=f"(d[34]), "=f"(d[35]), "=f"(d[36]), "=f"(d[37]), "=f"(d[38]), "=f"(d[39]), "=f"(d[40]), "=f"(d[41]), "=f"(d[42]), "=f"(d[43]), "=f"(d[44]), "=f"(d[45]), "=f"(d[46]), "=f"(d[47]), "=f"(d[48]), "=f"(d[49]), "=f"(d[50]), "=f"(d[51]), "=f"(d[52]), "=f"(d[53]), "=f"(d[54]), "=f"(d[55]), "=f"(d[56]), "=f"(d[57]), "=f"(d[58]), "=f"(d[59]), "=f"(d[60]), "=f"(d[61]), "=f"(d[62]), "=f"(d[63]), "=f"(d[64]), "=f"(d[65]), "=f"(d[66]), "=f"(d[67]), "=f"(d[68]), "=f"(d[69]), "=f"(d[70]), "=f"(d[71]), "=f"(d[72]), "=f"(d[73]), "=f"(d[74]), "=f"(d[75]), "=f"(d[76]), "=f"(d[77]), "=f"(d[78]), "=f"(d[79]), "=f"(d[80]), "=f"(d[81]), "=f"(d[82]), "=f"(d[83]), "=f"(d[84]), "=f"(d[85]), "=f"(d[86]), "=f"(d[87]), "=f"(d[88]), "=f"(d[89]), "=f"(d[90]), "=f"(d[91]), "=f"(d[92]), "=f"(d[93]), "=f"(d[94]), "=f"(d[95])
    : "r"(a0), "r"(a1), "r"(a2), "r"(a3), "r"(b), "n"(BHI));
}
template<uint32_t AHI, uint32_t BHI> __device__ __forceinline__ void wg_ss_n128(float* d, uint32_t a, uint32_t b) {
  asm volatile("{\n.reg .pred p;\n.reg .b64 da, db;\nsetp.ne.b32 p, 1, 0;\nmov.b64 da, {%64, %66};\nmov.b64 db, {%65, %67};\n"
    "wgmma.mma_async.sync.aligned.m64n128k16.f32.bf16.bf16 {%0, %1, %2, %3, %4, %5, %6, %7, %8, %9, %10, %11, %12, %13, %14, %15, %16, %17, %18, %19, %20, %21, %22, %23, %24, %25, %26, %27, %28, %29, %30, %31, %32, %33, %34, %35, %36, %37, %38, %39, %40, %41, %42, %43, %44, %45, %46, %47, %48, %49, %50, %51, %52, %53, %54, %55, %56, %57, %58, %59, %60, %61, %62, %63}, da, db, p, 1, 1, 0, 1;\n}\n"
    : "+f"(d[0]), "+f"(d[1]), "+f"(d[2]), "+f"(d[3]), "+f"(d[4]), "+f"(d[5]), "+f"(d[6]), "+f"(d[7]), "+f"(d[8]), "+f"(d[9]), "+f"(d[10]), "+f"(d[11]), "+f"(d[12]), "+f"(d[13]), "+f"(d[14]), "+f"(d[15]), "+f"(d[16]), "+f"(d[17]), "+f"(d[18]), "+f"(d[19]), "+f"(d[20]), "+f"(d[21]), "+f"(d[22]), "+f"(d[23]), "+f"(d[24]), "+f"(d[25]), "+f"(d[26]), "+f"(d[27]), "+f"(d[28]), "+f"(d[29]), "+f"(d[30]), "+f"(d[31]), "+f"(d[32]), "+f"(d[33]), "+f"(d[34]), "+f"(d[35]), "+f"(d[36]), "+f"(d[37]), "+f"(d[38]), "+f"(d[39]), "+f"(d[40]), "+f"(d[41]), "+f"(d[42]), "+f"(d[43]), "+f"(d[44]), "+f"(d[45]), "+f"(d[46]), "+f"(d[47]), "+f"(d[48]), "+f"(d[49]), "+f"(d[50]), "+f"(d[51]), "+f"(d[52]), "+f"(d[53]), "+f"(d[54]), "+f"(d[55]), "+f"(d[56]), "+f"(d[57]), "+f"(d[58]), "+f"(d[59]), "+f"(d[60]), "+f"(d[61]), "+f"(d[62]), "+f"(d[63])
    : "r"(a), "r"(b), "n"(AHI), "n"(BHI));
}
template<uint32_t AHI, uint32_t BHI> __device__ __forceinline__ void wg_ss_z_n128(float* d, uint32_t a, uint32_t b) {
  asm volatile("{\n.reg .pred p;\n.reg .b64 da, db;\nsetp.ne.b32 p, 0, 0;\nmov.b64 da, {%64, %66};\nmov.b64 db, {%65, %67};\n"
    "wgmma.mma_async.sync.aligned.m64n128k16.f32.bf16.bf16 {%0, %1, %2, %3, %4, %5, %6, %7, %8, %9, %10, %11, %12, %13, %14, %15, %16, %17, %18, %19, %20, %21, %22, %23, %24, %25, %26, %27, %28, %29, %30, %31, %32, %33, %34, %35, %36, %37, %38, %39, %40, %41, %42, %43, %44, %45, %46, %47, %48, %49, %50, %51, %52, %53, %54, %55, %56, %57, %58, %59, %60, %61, %62, %63}, da, db, p, 1, 1, 0, 1;\n}\n"
    : "=f"(d[0]), "=f"(d[1]), "=f"(d[2]), "=f"(d[3]), "=f"(d[4]), "=f"(d[5]), "=f"(d[6]), "=f"(d[7]), "=f"(d[8]), "=f"(d[9]), "=f"(d[10]), "=f"(d[11]), "=f"(d[12]), "=f"(d[13]), "=f"(d[14]), "=f"(d[15]), "=f"(d[16]), "=f"(d[17]), "=f"(d[18]), "=f"(d[19]), "=f"(d[20]), "=f"(d[21]), "=f"(d[22]), "=f"(d[23]), "=f"(d[24]), "=f"(d[25]), "=f"(d[26]), "=f"(d[27]), "=f"(d[28]), "=f"(d[29]), "=f"(d[30]), "=f"(d[31]), "=f"(d[32]), "=f"(d[33]), "=f"(d[34]), "=f"(d[35]), "=f"(d[36]), "=f"(d[37]), "=f"(d[38]), "=f"(d[39]), "=f"(d[40]), "=f"(d[41]), "=f"(d[42]), "=f"(d[43]), "=f"(d[44]), "=f"(d[45]), "=f"(d[46]), "=f"(d[47]), "=f"(d[48]), "=f"(d[49]), "=f"(d[50]), "=f"(d[51]), "=f"(d[52]), "=f"(d[53]), "=f"(d[54]), "=f"(d[55]), "=f"(d[56]), "=f"(d[57]), "=f"(d[58]), "=f"(d[59]), "=f"(d[60]), "=f"(d[61]), "=f"(d[62]), "=f"(d[63])
    : "r"(a), "r"(b), "n"(AHI), "n"(BHI));
}
template<uint32_t AHI, uint32_t BHI> __device__ __forceinline__ void wg_ss_n160(float* d, uint32_t a, uint32_t b) {
  asm volatile("{\n.reg .pred p;\n.reg .b64 da, db;\nsetp.ne.b32 p, 1, 0;\nmov.b64 da, {%80, %82};\nmov.b64 db, {%81, %83};\n"
    "wgmma.mma_async.sync.aligned.m64n160k16.f32.bf16.bf16 {%0, %1, %2, %3, %4, %5, %6, %7, %8, %9, %10, %11, %12, %13, %14, %15, %16, %17, %18, %19, %20, %21, %22, %23, %24, %25, %26, %27, %28, %29, %30, %31, %32, %33, %34, %35, %36, %37, %38, %39, %40, %41, %42, %43, %44, %45, %46, %47, %48, %49, %50, %51, %52, %53, %54, %55, %56, %57, %58, %59, %60, %61, %62, %63, %64, %65, %66, %67, %68, %69, %70, %71, %72, %73, %74, %75, %76, %77, %78, %79}, da, db, p, 1, 1, 0, 1;\n}\n"
    : "+f"(d[0]), "+f"(d[1]), "+f"(d[2]), "+f"(d[3]), "+f"(d[4]), "+f"(d[5]), "+f"(d[6]), "+f"(d[7]), "+f"(d[8]), "+f"(d[9]), "+f"(d[10]), "+f"(d[11]), "+f"(d[12]), "+f"(d[13]), "+f"(d[14]), "+f"(d[15]), "+f"(d[16]), "+f"(d[17]), "+f"(d[18]), "+f"(d[19]), "+f"(d[20]), "+f"(d[21]), "+f"(d[22]), "+f"(d[23]), "+f"(d[24]), "+f"(d[25]), "+f"(d[26]), "+f"(d[27]), "+f"(d[28]), "+f"(d[29]), "+f"(d[30]), "+f"(d[31]), "+f"(d[32]), "+f"(d[33]), "+f"(d[34]), "+f"(d[35]), "+f"(d[36]), "+f"(d[37]), "+f"(d[38]), "+f"(d[39]), "+f"(d[40]), "+f"(d[41]), "+f"(d[42]), "+f"(d[43]), "+f"(d[44]), "+f"(d[45]), "+f"(d[46]), "+f"(d[47]), "+f"(d[48]), "+f"(d[49]), "+f"(d[50]), "+f"(d[51]), "+f"(d[52]), "+f"(d[53]), "+f"(d[54]), "+f"(d[55]), "+f"(d[56]), "+f"(d[57]), "+f"(d[58]), "+f"(d[59]), "+f"(d[60]), "+f"(d[61]), "+f"(d[62]), "+f"(d[63]), "+f"(d[64]), "+f"(d[65]), "+f"(d[66]), "+f"(d[67]), "+f"(d[68]), "+f"(d[69]), "+f"(d[70]), "+f"(d[71]), "+f"(d[72]), "+f"(d[73]), "+f"(d[74]), "+f"(d[75]), "+f"(d[76]), "+f"(d[77]), "+f"(d[78]), "+f"(d[79])
    : "r"(a), "r"(b), "n"(AHI), "n"(BHI));
}
template<uint32_t AHI, uint32_t BHI> __device__ __forceinline__ void wg_ss_z_n160(float* d, uint32_t a, uint32_t b) {
  asm volatile("{\n.reg .pred p;\n.reg .b64 da, db;\nsetp.ne.b32 p, 0, 0;\nmov.b64 da, {%80, %82};\nmov.b64 db, {%81, %83};\n"
    "wgmma.mma_async.sync.aligned.m64n160k16.f32.bf16.bf16 {%0, %1, %2, %3, %4, %5, %6, %7, %8, %9, %10, %11, %12, %13, %14, %15, %16, %17, %18, %19, %20, %21, %22, %23, %24, %25, %26, %27, %28, %29, %30, %31, %32, %33, %34, %35, %36, %37, %38, %39, %40, %41, %42, %43, %44, %45, %46, %47, %48, %49, %50, %51, %52, %53, %54, %55, %56, %57, %58, %59, %60, %61, %62, %63, %64, %65, %66, %67, %68, %69, %70, %71, %72, %73, %74, %75, %76, %77, %78, %79}, da, db, p, 1, 1, 0, 1;\n}\n"
    : "=f"(d[0]), "=f"(d[1]), "=f"(d[2]), "=f"(d[3]), "=f"(d[4]), "=f"(d[5]), "=f"(d[6]), "=f"(d[7]), "=f"(d[8]), "=f"(d[9]), "=f"(d[10]), "=f"(d[11]), "=f"(d[12]), "=f"(d[13]), "=f"(d[14]), "=f"(d[15]), "=f"(d[16]), "=f"(d[17]), "=f"(d[18]), "=f"(d[19]), "=f"(d[20]), "=f"(d[21]), "=f"(d[22]), "=f"(d[23]), "=f"(d[24]), "=f"(d[25]), "=f"(d[26]), "=f"(d[27]), "=f"(d[28]), "=f"(d[29]), "=f"(d[30]), "=f"(d[31]), "=f"(d[32]), "=f"(d[33]), "=f"(d[34]), "=f"(d[35]), "=f"(d[36]), "=f"(d[37]), "=f"(d[38]), "=f"(d[39]), "=f"(d[40]), "=f"(d[41]), "=f"(d[42]), "=f"(d[43]), "=f"(d[44]), "=f"(d[45]), "=f"(d[46]), "=f"(d[47]), "=f"(d[48]), "=f"(d[49]), "=f"(d[50]), "=f"(d[51]), "=f"(d[52]), "=f"(d[53]), "=f"(d[54]), "=f"(d[55]), "=f"(d[56]), "=f"(d[57]), "=f"(d[58]), "=f"(d[59]), "=f"(d[60]), "=f"(d[61]), "=f"(d[62]), "=f"(d[63]), "=f"(d[64]), "=f"(d[65]), "=f"(d[66]), "=f"(d[67]), "=f"(d[68]), "=f"(d[69]), "=f"(d[70]), "=f"(d[71]), "=f"(d[72]), "=f"(d[73]), "=f"(d[74]), "=f"(d[75]), "=f"(d[76]), "=f"(d[77]), "=f"(d[78]), "=f"(d[79])
    : "r"(a), "r"(b), "n"(AHI), "n"(BHI));
}
template<uint32_t BHI> __device__ __forceinline__ void wg_rs_n32(float* d, uint32_t a0, uint32_t a1, uint32_t a2, uint32_t a3, uint32_t b) {
  asm volatile("{\n.reg .pred p;\n.reg .b64 db;\nsetp.ne.b32 p, 1, 0;\nmov.b64 db, {%20, %21};\n"
    "wgmma.mma_async.sync.aligned.m64n32k16.f32.bf16.bf16 {%0, %1, %2, %3, %4, %5, %6, %7, %8, %9, %10, %11, %12, %13, %14, %15}, {%16, %17, %18, %19}, db, p, 1, 1, 1;\n}\n"
    : "+f"(d[0]), "+f"(d[1]), "+f"(d[2]), "+f"(d[3]), "+f"(d[4]), "+f"(d[5]), "+f"(d[6]), "+f"(d[7]), "+f"(d[8]), "+f"(d[9]), "+f"(d[10]), "+f"(d[11]), "+f"(d[12]), "+f"(d[13]), "+f"(d[14]), "+f"(d[15])
    : "r"(a0), "r"(a1), "r"(a2), "r"(a3), "r"(b), "n"(BHI));
}
template<uint32_t BHI> __device__ __forceinline__ void wg_rs_z_n32(float* d, uint32_t a0, uint32_t a1, uint32_t a2, uint32_t a3, uint32_t b) {
  asm volatile("{\n.reg .pred p;\n.reg .b64 db;\nsetp.ne.b32 p, 0, 0;\nmov.b64 db, {%20, %21};\n"
    "wgmma.mma_async.sync.aligned.m64n32k16.f32.bf16.bf16 {%0, %1, %2, %3, %4, %5, %6, %7, %8, %9, %10, %11, %12, %13, %14, %15}, {%16, %17, %18, %19}, db, p, 1, 1, 1;\n}\n"
    : "=f"(d[0]), "=f"(d[1]), "=f"(d[2]), "=f"(d[3]), "=f"(d[4]), "=f"(d[5]), "=f"(d[6]), "=f"(d[7]), "=f"(d[8]), "=f"(d[9]), "=f"(d[10]), "=f"(d[11]), "=f"(d[12]), "=f"(d[13]), "=f"(d[14]), "=f"(d[15])
    : "r"(a0), "r"(a1), "r"(a2), "r"(a3), "r"(b), "n"(BHI));
}
template<uint32_t BHI> __device__ __forceinline__ void wg_rs_n64(float* d, uint32_t a0, uint32_t a1, uint32_t a2, uint32_t a3, uint32_t b) {
  asm volatile("{\n.reg .pred p;\n.reg .b64 db;\nsetp.ne.b32 p, 1, 0;\nmov.b64 db, {%36, %37};\n"
    "wgmma.mma_async.sync.aligned.m64n64k16.f32.bf16.bf16 {%0, %1, %2, %3, %4, %5, %6, %7, %8, %9, %10, %11, %12, %13, %14, %15, %16, %17, %18, %19, %20, %21, %22, %23, %24, %25, %26, %27, %28, %29, %30, %31}, {%32, %33, %34, %35}, db, p, 1, 1, 0;\n}\n"
    : "+f"(d[0]), "+f"(d[1]), "+f"(d[2]), "+f"(d[3]), "+f"(d[4]), "+f"(d[5]), "+f"(d[6]), "+f"(d[7]), "+f"(d[8]), "+f"(d[9]), "+f"(d[10]), "+f"(d[11]), "+f"(d[12]), "+f"(d[13]), "+f"(d[14]), "+f"(d[15]), "+f"(d[16]), "+f"(d[17]), "+f"(d[18]), "+f"(d[19]), "+f"(d[20]), "+f"(d[21]), "+f"(d[22]), "+f"(d[23]), "+f"(d[24]), "+f"(d[25]), "+f"(d[26]), "+f"(d[27]), "+f"(d[28]), "+f"(d[29]), "+f"(d[30]), "+f"(d[31])
    : "r"(a0), "r"(a1), "r"(a2), "r"(a3), "r"(b), "n"(BHI));
}
template<uint32_t BHI> __device__ __forceinline__ void wg_rs_z_n64(float* d, uint32_t a0, uint32_t a1, uint32_t a2, uint32_t a3, uint32_t b) {
  asm volatile("{\n.reg .pred p;\n.reg .b64 db;\nsetp.ne.b32 p, 0, 0;\nmov.b64 db, {%36, %37};\n"
    "wgmma.mma_async.sync.aligned.m64n64k16.f32.bf16.bf16 {%0, %1, %2, %3, %4, %5, %6, %7, %8, %9, %10, %11, %12, %13, %14, %15, %16, %17, %18, %19, %20, %21, %22, %23, %24, %25, %26, %27, %28, %29, %30, %31}, {%32, %33, %34, %35}, db, p, 1, 1, 0;\n}\n"
    : "=f"(d[0]), "=f"(d[1]), "=f"(d[2]), "=f"(d[3]), "=f"(d[4]), "=f"(d[5]), "=f"(d[6]), "=f"(d[7]), "=f"(d[8]), "=f"(d[9]), "=f"(d[10]), "=f"(d[11]), "=f"(d[12]), "=f"(d[13]), "=f"(d[14]), "=f"(d[15]), "=f"(d[16]), "=f"(d[17]), "=f"(d[18]), "=f"(d[19]), "=f"(d[20]), "=f"(d[21]), "=f"(d[22]), "=f"(d[23]), "=f"(d[24]), "=f"(d[25]), "=f"(d[26]), "=f"(d[27]), "=f"(d[28]), "=f"(d[29]), "=f"(d[30]), "=f"(d[31])
    : "r"(a0), "r"(a1), "r"(a2), "r"(a3), "r"(b), "n"(BHI));
}
template<uint32_t BHI> __device__ __forceinline__ void wg_rs_n24(float* d, uint32_t a0, uint32_t a1, uint32_t a2, uint32_t a3, uint32_t b) {
  asm volatile("{\n.reg .pred p;\n.reg .b64 db;\nsetp.ne.b32 p, 1, 0;\nmov.b64 db, {%16, %17};\n"
    "wgmma.mma_async.sync.aligned.m64n24k16.f32.bf16.bf16 {%0, %1, %2, %3, %4, %5, %6, %7, %8, %9, %10, %11}, {%12, %13, %14, %15}, db, p, 1, 1, 1;\n}\n"
    : "+f"(d[0]), "+f"(d[1]), "+f"(d[2]), "+f"(d[3]), "+f"(d[4]), "+f"(d[5]), "+f"(d[6]), "+f"(d[7]), "+f"(d[8]), "+f"(d[9]), "+f"(d[10]), "+f"(d[11])
    : "r"(a0), "r"(a1), "r"(a2), "r"(a3), "r"(b), "n"(BHI));
}
template<uint32_t BHI> __device__ __forceinline__ void wg_rs_z_n24(float* d, uint32_t a0, uint32_t a1, uint32_t a2, uint32_t a3, uint32_t b) {
  asm volatile("{\n.reg .pred p;\n.reg .b64 db;\nsetp.ne.b32 p, 0, 0;\nmov.b64 db, {%16, %17};\n"
    "wgmma.mma_async.sync.aligned.m64n24k16.f32.bf16.bf16 {%0, %1, %2, %3, %4, %5, %6, %7, %8, %9, %10, %11}, {%12, %13, %14, %15}, db, p, 1, 1, 1;\n}\n"
    : "=f"(d[0]), "=f"(d[1]), "=f"(d[2]), "=f"(d[3]), "=f"(d[4]), "=f"(d[5]), "=f"(d[6]), "=f"(d[7]), "=f"(d[8]), "=f"(d[9]), "=f"(d[10]), "=f"(d[11])
    : "r"(a0), "r"(a1), "r"(a2), "r"(a3), "r"(b), "n"(BHI));
}
template<uint32_t BHI> __device__ __forceinline__ void wg_rsb_n64(float* d, uint32_t a0, uint32_t a1, uint32_t a2, uint32_t a3, uint32_t b) {
  asm volatile("{\n.reg .pred p;\n.reg .b64 db;\nsetp.ne.b32 p, 1, 0;\nmov.b64 db, {%36, %37};\n"
    "wgmma.mma_async.sync.aligned.m64n64k16.f32.bf16.bf16 {%0, %1, %2, %3, %4, %5, %6, %7, %8, %9, %10, %11, %12, %13, %14, %15, %16, %17, %18, %19, %20, %21, %22, %23, %24, %25, %26, %27, %28, %29, %30, %31}, {%32, %33, %34, %35}, db, p, 1, 1, 1;\n}\n"
    : "+f"(d[0]), "+f"(d[1]), "+f"(d[2]), "+f"(d[3]), "+f"(d[4]), "+f"(d[5]), "+f"(d[6]), "+f"(d[7]), "+f"(d[8]), "+f"(d[9]), "+f"(d[10]), "+f"(d[11]), "+f"(d[12]), "+f"(d[13]), "+f"(d[14]), "+f"(d[15]), "+f"(d[16]), "+f"(d[17]), "+f"(d[18]), "+f"(d[19]), "+f"(d[20]), "+f"(d[21]), "+f"(d[22]), "+f"(d[23]), "+f"(d[24]), "+f"(d[25]), "+f"(d[26]), "+f"(d[27]), "+f"(d[28]), "+f"(d[29]), "+f"(d[30]), "+f"(d[31])
    : "r"(a0), "r"(a1), "r"(a2), "r"(a3), "r"(b), "n"(BHI));
}
template<uint32_t BHI> __device__ __forceinline__ void wg_rsb_z_n64(float* d, uint32_t a0, uint32_t a1, uint32_t a2, uint32_t a3, uint32_t b) {
  asm volatile("{\n.reg .pred p;\n.reg .b64 db;\nsetp.ne.b32 p, 0, 0;\nmov.b64 db, {%36, %37};\n"
    "wgmma.mma_async.sync.aligned.m64n64k16.f32.bf16.bf16 {%0, %1, %2, %3, %4, %5, %6, %7, %8, %9, %10, %11, %12, %13, %14, %15, %16, %17, %18, %19, %20, %21, %22, %23, %24, %25, %26, %27, %28, %29, %30, %31}, {%32, %33, %34, %35}, db, p, 1, 1, 1;\n}\n"
    : "=f"(d[0]), "=f"(d[1]), "=f"(d[2]), "=f"(d[3]), "=f"(d[4]), "=f"(d[5]), "=f"(d[6]), "=f"(d[7]), "=f"(d[8]), "=f"(d[9]), "=f"(d[10]), "=f"(d[11]), "=f"(d[12]), "=f"(d[13]), "=f"(d[14]), "=f"(d[15]), "=f"(d[16]), "=f"(d[17]), "=f"(d[18]), "=f"(d[19]), "=f"(d[20]), "=f"(d[21]), "=f"(d[22]), "=f"(d[23]), "=f"(d[24]), "=f"(d[25]), "=f"(d[26]), "=f"(d[27]), "=f"(d[28]), "=f"(d[29]), "=f"(d[30]), "=f"(d[31])
    : "r"(a0), "r"(a1), "r"(a2), "r"(a3), "r"(b), "n"(BHI));
}

__device__ __forceinline__ void wg_fence() { asm volatile("wgmma.fence.sync.aligned;" ::: "memory"); }
__device__ __forceinline__ void wg_commit() { asm volatile("wgmma.commit_group.sync.aligned;" ::: "memory"); }
template <int N> __device__ __forceinline__ void wg_wait() { asm volatile("wgmma.wait_group.sync.aligned %0;" ::"n"(N) : "memory"); }
template <int R> __device__ __forceinline__ void pin(float* d) {
#pragma unroll
  for (int i = 0; i < R; i++) asm volatile("" : "+f"(d[i])::"memory");
}
template <int R> __device__ __forceinline__ void pin(uint32_t* d) {
#pragma unroll
  for (int i = 0; i < R; i++) asm volatile("" : "+r"(d[i])::"memory");
}
__device__ __forceinline__ float ex2(float x) { float y; asm("ex2.approx.ftz.f32 %0, %1;" : "=f"(y) : "f"(x)); return y; }
__device__ __forceinline__ float tanh_fast(float x) { float y; asm("tanh.approx.f32 %0, %1;" : "=f"(y) : "f"(x)); return y; }
__device__ __forceinline__ uint32_t pack(float lo, float hi) { uint32_t r; asm("cvt.rn.bf16x2.f32 %0, %1, %2;" : "=r"(r) : "f"(hi), "f"(lo)); return r; }
__device__ __forceinline__ float bf_lo(uint32_t v) { return __uint_as_float(v << 16); }
__device__ __forceinline__ float bf_hi(uint32_t v) { return __uint_as_float(v & 0xffff0000u); }
__device__ __forceinline__ float bf_round(float x) { return bf_lo(pack(x, 0.f)); }

__device__ __forceinline__ void mbar_init(uint32_t bar, uint32_t cnt) { asm volatile("mbarrier.init.shared::cta.b64 [%0], %1;" ::"r"(bar), "r"(cnt) : "memory"); }
__device__ __forceinline__ void mbar_expect(uint32_t bar, uint32_t bytes) { asm volatile("mbarrier.arrive.expect_tx.shared::cta.b64 _, [%0], %1;" ::"r"(bar), "r"(bytes) : "memory"); }
__device__ __forceinline__ void mbar_wait(uint32_t bar, uint32_t parity) {
  asm volatile(
      "{\n.reg .pred p;\n.reg .u32 c;\n"
      "mbarrier.try_wait.parity.shared::cta.b64 p, [%0], %1;\n"
      "@p bra.uni DONE;\n"
      "mov.u32 c, 0;\n"
      "LOOP:\n"
      "mbarrier.try_wait.parity.shared::cta.b64 p, [%0], %1;\n"
      "@p bra.uni DONE;\n"
      "add.u32 c, c, 1;\n"
      "setp.lt.u32 p, c, 0x400000;\n"
      "@p bra.uni LOOP;\n"
      "trap;\n"
      "DONE:\n}\n" ::"r"(bar), "r"(parity) : "memory");
}
__device__ __forceinline__ uint32_t mbar_test(uint32_t bar, uint32_t parity) {
  uint32_t ok;
  asm volatile("{\n.reg .pred p;\nmbarrier.test_wait.parity.shared::cta.b64 p, [%1], %2;\nselp.u32 %0, 1, 0, p;\n}\n" : "=r"(ok) : "r"(bar), "r"(parity) : "memory");
  return ok;
}
__device__ __forceinline__ void mbar_arrive_if(uint32_t bar, uint32_t cond) {
  asm volatile("{\n.reg .pred p;\nsetp.ne.u32 p, %1, 0;\n@p mbarrier.arrive.shared::cta.b64 _, [%0];\n}\n" ::"r"(bar), "r"(cond) : "memory");
}
__device__ __forceinline__ uint32_t bsub2(uint32_t a, uint32_t b) { uint32_t d; asm("sub.rn.bf16x2 %0, %1, %2;" : "=r"(d) : "r"(a), "r"(b)); return d; }
__device__ __forceinline__ uint32_t bscale2(uint32_t d, uint32_t hi, uint32_t lo) {
  uint32_t t, r;
  asm("mul.rn.bf16x2 %0, %1, %2;" : "=r"(t) : "r"(d), "r"(lo));
  asm("fma.rn.bf16x2 %0, %1, %2, %3;" : "=r"(r) : "r"(d), "r"(hi), "r"(t));
  return r;
}
__device__ __forceinline__ void flag_wait(const uint32_t* f, uint32_t target) {
  asm volatile(
      "{\n.reg .pred p;\n.reg .u32 c, v;\n"
      "mov.u32 c, 0;\n"
      "LOOP:\n"
      "ld.acquire.gpu.global.u32 v, [%0];\n"
      "sub.u32 v, v, %1;\n"
      "setp.ge.s32 p, v, 0;\n"
      "@p bra DONE;\n"
      "add.u32 c, c, 1;\n"
      "setp.lt.u32 p, c, 0x400000;\n"
      "@p bra LOOP;\n"
      "trap;\n"
      "DONE:\n}\n" ::"l"(f), "r"(target) : "memory");
}
__device__ __forceinline__ uint32_t flag_wait_v(const uint32_t* f, uint32_t target) {
  uint32_t v;
  asm volatile(
      "{\n.reg .pred p;\n.reg .u32 c, d;\n"
      "mov.u32 c, 0;\n"
      "LOOP:\n"
      "ld.acquire.gpu.global.u32 %0, [%1];\n"
      "sub.u32 d, %0, %2;\n"
      "setp.ge.s32 p, d, 0;\n"
      "@p bra DONE;\n"
      "add.u32 c, c, 1;\n"
      "setp.lt.u32 p, c, 0x400000;\n"
      "@p bra LOOP;\n"
      "trap;\n"
      "DONE:\n}\n" : "=&r"(v) : "l"(f), "r"(target) : "memory");
  return v;
}
__device__ __forceinline__ float sqrt_fast(float x) { float y; asm("sqrt.approx.f32 %0, %1;" : "=f"(y) : "f"(x)); return y; }
__device__ __forceinline__ float rcp_fast(float x) { float y; asm("rcp.approx.ftz.f32 %0, %1;" : "=f"(y) : "f"(x)); return y; }
__device__ __forceinline__ void ldsm4(uint32_t* v, uint32_t addr) {
  asm volatile("ldmatrix.sync.aligned.m8n8.x4.shared.b16 {%0,%1,%2,%3}, [%4];" : "=r"(v[0]), "=r"(v[1]), "=r"(v[2]), "=r"(v[3]) : "r"(addr) : "memory");
}
__device__ __forceinline__ void stsm4(uint32_t addr, uint32_t a, uint32_t b, uint32_t c, uint32_t d) {
  asm volatile("stmatrix.sync.aligned.m8n8.x4.shared.b16 [%0], {%1,%2,%3,%4};" ::"r"(addr), "r"(a), "r"(b), "r"(c), "r"(d) : "memory");
}
__device__ __forceinline__ void flag_add(uint32_t* f) { asm volatile("red.relaxed.gpu.global.add.u32 [%0], 1;" ::"l"(f) : "memory"); }
__device__ __forceinline__ void fence_gpu() { asm volatile("fence.acq_rel.gpu;" ::: "memory"); }
__device__ __forceinline__ void fence_async() { asm volatile("fence.proxy.async.global;" ::: "memory"); }
__device__ __forceinline__ void tma2d(uint32_t dst, const CUtensorMap* tm, uint32_t bar, int c0, int c1) {
  asm volatile("cp.async.bulk.tensor.2d.shared::cluster.global.mbarrier::complete_tx::bytes [%0], [%1, {%3, %4}], [%2];" ::"r"(dst), "l"(tm), "r"(bar), "r"(c0), "r"(c1) : "memory");
}
__device__ __forceinline__ void tma2d_h(uint32_t dst, const CUtensorMap* tm, uint32_t bar, int c0, int c1, uint64_t pol) {
  asm volatile("cp.async.bulk.tensor.2d.shared::cluster.global.mbarrier::complete_tx::bytes.L2::cache_hint [%0], [%1, {%3, %4}], [%2], %5;" ::"r"(dst), "l"(tm), "r"(bar), "r"(c0), "r"(c1), "l"(pol) : "memory");
}
__device__ __forceinline__ void bulk_s2g(void* dst, uint32_t src, uint32_t bytes) {
  asm volatile("cp.async.bulk.global.shared::cta.bulk_group [%0], [%1], %2;" ::"l"(dst), "r"(src), "r"(bytes) : "memory");
}
__device__ __forceinline__ void mma_ones(float* c, const uint32_t* a) {
  asm("mma.sync.aligned.m16n8k16.row.col.f32.bf16.bf16.f32 {%0,%1,%2,%3}, {%4,%5,%6,%7}, {%8,%8}, {%0,%1,%2,%3};"
      : "+f"(c[0]), "+f"(c[1]), "+f"(c[2]), "+f"(c[3]) : "r"(a[0]), "r"(a[1]), "r"(a[2]), "r"(a[3]), "r"(0x3f803f80u));
}
__device__ __forceinline__ void tma5d(uint32_t dst, const CUtensorMap* tm, uint32_t bar, int c0, int c4) {
  asm volatile("cp.async.bulk.tensor.5d.shared::cluster.global.mbarrier::complete_tx::bytes [%0], [%1, {%3, %5, %5, %5, %4}], [%2];" ::"r"(dst), "l"(tm), "r"(bar), "r"(c0), "r"(c4), "r"(0) : "memory");
}
__device__ __forceinline__ void tma3d(uint32_t dst, const CUtensorMap* tm, uint32_t bar, int c0, int c2) {
  asm volatile("cp.async.bulk.tensor.3d.shared::cluster.global.mbarrier::complete_tx::bytes [%0], [%1, {%3, %5, %4}], [%2];" ::"r"(dst), "l"(tm), "r"(bar), "r"(c0), "r"(c2), "r"(0) : "memory");
}
__device__ __forceinline__ void bulk_g2s(uint32_t dst, const void* src, uint32_t bytes, uint32_t bar) {
  asm volatile("cp.async.bulk.shared::cluster.global.mbarrier::complete_tx::bytes [%0], [%1], %2, [%3];" ::"r"(dst), "l"(src), "r"(bytes), "r"(bar) : "memory");
}
__device__ __forceinline__ void pf_line(const void* p) { asm volatile("prefetch.global.L2 [%0];" ::"l"(p) : "memory"); }
__device__ __forceinline__ int fresh_tid() { int v; asm volatile("mov.u32 %0, %%tid.x;" : "=r"(v)); return v; }
struct Att {
  float s[32];
  float o[12];
  uint32_t p[16];
  uint32_t q[8];
};

__device__ __forceinline__ float warp_sum(float v) {
#pragma unroll 1
  for (int d = 16; d; d >>= 1) v += __shfl_xor_sync(0xffffffffu, v, d);
  return v;
}
#define OPAQUE(x) asm volatile("" : "+r"(x))
__device__ __forceinline__ void attn_slow_row(int cta, uint32_t& w) {
  float mx = -INFINITY;
#pragma unroll 1
  for (uint32_t key = threadIdx.x & 31; key < SEQ; key += 32) {
    float s = 0.f;
#pragma unroll 1
    for (uint32_t v = 0; v < 9; v++) {
      OPAQUE(w); OPAQUE(key);
      const uint32_t hp = (w >> 4) & 3, pos = (v + hp) & 3;
      const uint32_t q = g_Q[(cta * 4 + hp) * 1152 + ((w >> 3) & 1) + (v < 8 ? (((w >> 6) & 7) * 32 + (w & 7) * 4 + pos) * 4 + 2 * (v >> 2) : 1024 + (((w >> 6) & 7) * 8 + (w & 7)) * 2)];
      const uint32_t u = g_KV[(4 * (cta & 7) + hp) * SEQ * 20 + (key >> 3) * 160 + (key & 7) * 4 + (v >> 2) * 32 + pos];
      s = fmaf(bf_lo(q), bf_lo(u), fmaf(bf_hi(q), bf_hi(u), s));
    }
    g_S[(cta * 8 + ((w >> 6) & 7)) * SEQ + key] = s;
    mx = fmaxf(mx, s);
  }
#pragma unroll 1
  for (int d = 16; d; d >>= 1) mx = fmaxf(mx, __shfl_xor_sync(0xffffffffu, mx, d));
  float l = 0.f;
#pragma unroll 1
  for (uint32_t key = threadIdx.x & 31; key < SEQ; key += 32) l += ex2(g_S[(cta * 8 + ((w >> 6) & 7)) * SEQ + key] - mx);
  l = 2.f * rcp_fast(warp_sum(l));
#pragma unroll 1
  for (uint32_t v = w >> 9; v < 9; v++) {
    float a = 0.f, b = 0.f;
#pragma unroll 1
    for (uint32_t key = threadIdx.x & 31; key < SEQ; key += 32) {
      OPAQUE(w); OPAQUE(v);
      const uint32_t hp = (w >> 4) & 3;
      const uint32_t u = g_KV[(4 * (cta & 7) + hp) * SEQ * 20 + (key >> 3) * 160 + (key & 7) * 4 + (v < 8 ? (3 + (v >> 2)) * 32 + (v & 3) : 64 + ((hp + 2) & 3))];
      const float p = ex2(g_S[(cta * 8 + ((w >> 6) & 7)) * SEQ + key] - mx);
      a = fmaf(p, bf_lo(u), a); b = fmaf(p, bf_hi(u), b);
    }
    a = warp_sum(a); b = warp_sum(b);
    OPAQUE(w);
    const uint32_t hp = (w >> 4) & 3;
    if ((threadIdx.x & 31) == 0) g_O[cta * 9 * 512 + (((w >> 6) & 7) * 16 + (w & 15)) * 4 + (v < 8 ? (2 * hp + (v >> 2)) * 512 + (v & 3) : 8 * 512 + hp)] = pack(a * l, b * l);
  }
}

__device__ __forceinline__ uint32_t bad_heads(uint32_t bad_addr, int wr) {
  uint32_t bad;
  __syncwarp();
  asm volatile("ld.volatile.shared.u32 %0, [%1];" : "=r"(bad) : "r"(bad_addr) : "memory");
  return __shfl_sync(0xffffffffu, (bad >> (4 * wr)) & 15, 0);
}
__device__ __forceinline__ void repair_rows(int cta, int wr, uint32_t bad, int last_head, bool final) {
#pragma unroll 1
  for (uint32_t w = wr * 64; w < wr * 64 + 64; w++) {
    if (!((bad >> ((w >> 4) & 3)) & 1)) continue;
    if (final && ((w >> 4) & 3) != last_head) w |= 8u << 9;
    attn_slow_row(cta, w);
    w &= 511;
  }
  __syncwarp();
}
__device__ __forceinline__ void o_normalise(const float* o, uint32_t* w, uint32_t& x0, uint32_t& x1, int hp, int lane, uint32_t bad_addr, int wr) {
  const int src = (lane & ~3) | ((hp + 1) & 3);
  float l0 = __shfl_sync(0xffffffffu, o[0], src), l1 = __shfl_sync(0xffffffffu, o[2], src);
  float sa = 0.f;
#pragma unroll
  for (int i = 0; i < 12; i++) sa += fabsf(o[i]);
  bool ok = (l0 <= 1.329228e36f) && (l1 <= 1.329228e36f) && (l0 > 0.f) && (l1 > 0.f) && (sa <= 3.0e38f);
  float i0 = 2.f * rcp_fast(l0), i1 = 2.f * rcp_fast(l1);
  w[0] = pack(o[4] * i0, o[5] * i0);
  w[1] = pack(o[6] * i1, o[7] * i1);
  w[2] = pack(o[8] * i0, o[9] * i0);
  w[3] = pack(o[10] * i1, o[11] * i1);
  if ((lane & 3) == ((hp + 2) & 3)) { x0 = pack(o[0] * i0, o[1] * i0); x1 = pack(o[2] * i1, o[3] * i1); }
  if (!ok) asm volatile("red.shared.or.b32 [%0], %1;" ::"r"(bad_addr), "r"(1u << (4 * wr + hp)) : "memory");
}

__device__ __forceinline__ void issue_pv(Att& a, uint32_t kdesc) {
  const uint32_t vdesc = kdesc + 192 + (LO_V - LO_K);
#pragma unroll
  for (int k = 0; k < 4; k++) wg_rs_n24<HI_V>(a.o, a.p[4 * k], a.p[4 * k + 1], a.p[4 * k + 2], a.p[4 * k + 3], vdesc + k * 48);
}
__device__ __forceinline__ void issue_att(Att& a, uint32_t kdesc) {
  issue_pv(a, kdesc);
  wg_rs_z_n64<HI_K>(a.s, a.q[0], a.q[1], a.q[2], a.q[3], kdesc);
  wg_rs_n64<HI_K>(a.s, a.q[4], a.q[5], a.q[6], a.q[7], kdesc + 16);
}
__device__ __forceinline__ void softmax_a(Att& a) {
#pragma unroll
  for (int i = 0; i < SM_B; i++) a.p[i] = pack(ex2(a.s[2 * i]), ex2(a.s[2 * i + 1]));
  a.s[2 * SM_B] = ex2(a.s[2 * SM_B]); a.s[2 * SM_B + 1] = ex2(a.s[2 * SM_B + 1]);
  pin<SM_B>(a.p); pin<2>(a.s + 2 * SM_B);
}
__device__ __forceinline__ void softmax_b(Att& a) {
  a.p[SM_B] = pack(a.s[2 * SM_B], a.s[2 * SM_B + 1]);
#pragma unroll
  for (int i = SM_B + 1; i < 16; i++) a.p[i] = pack(ex2(a.s[2 * i]), ex2(a.s[2 * i + 1]));
  pin<16 - SM_B>(a.p + SM_B);
}
__device__ __forceinline__ void first_tile(Att& a, int hp, int lane) {
  float m0 = fmaxf(a.s[0], a.s[1]), m1 = fmaxf(a.s[2], a.s[3]);
#pragma unroll
  for (int i = 4; i < 32; i += 4) { m0 = fmaxf(m0, fmaxf(a.s[i], a.s[i + 1])); m1 = fmaxf(m1, fmaxf(a.s[i + 2], a.s[i + 3])); }
  m0 = fmaxf(m0, __shfl_xor_sync(0xffffffffu, m0, 1)); m1 = fmaxf(m1, __shfl_xor_sync(0xffffffffu, m1, 1));
  m0 = fmaxf(m0, __shfl_xor_sync(0xffffffffu, m0, 2)); m1 = fmaxf(m1, __shfl_xor_sync(0xffffffffu, m1, 2));
  float n0 = -(m0 + MOFF), n1 = -(m1 + MOFF);
  float h0 = bf_round(n0), h1 = bf_round(n1);
  uint32_t e0 = pack(h0, n0 - h0), e1 = pack(h1, n1 - h1);
  n0 = h0 + bf_hi(e0); n1 = h1 + bf_hi(e1);
  if ((lane & 3) == ((hp + 1) & 3)) { a.q[4] = e0; a.q[5] = e1; }
#pragma unroll
  for (int i = 0; i < 32; i += 4) { a.s[i] += n0; a.s[i + 1] += n0; a.s[i + 2] += n1; a.s[i + 3] += n1; }
#pragma unroll
  for (int i = 0; i < 12; i++) a.o[i] = 0.f;
  pin<12>(a.o); pin<8>(a.q);
}
__device__ __forceinline__ void fetch_q(uint32_t* q, int cta, int hp, int tid) {
  const uint32_t* src = g_Q + (cta * 4 + hp) * 1152;
  const uint4 u = __ldcg(reinterpret_cast<const uint4*>(src) + tid);
  uint2 v = make_uint2(0u, 0u);
  if ((tid & 3) == hp) v = __ldcg(reinterpret_cast<const uint2*>(src + 1024) + (tid >> 2));
  q[0] = u.x; q[1] = u.y; q[2] = u.z; q[3] = u.w; q[4] = v.x; q[5] = v.y;
}
__device__ __forceinline__ void store_q(const uint32_t* q, int cta, int hp, int tid) {
  uint32_t* dst = g_Q + (cta * 4 + hp) * 1152;
  reinterpret_cast<uint4*>(dst)[tid] = make_uint4(q[0], q[1], q[2], q[3]);
  if ((tid & 3) == hp) reinterpret_cast<uint2*>(dst + 1024)[tid >> 2] = make_uint2(q[4], q[5]);
}
__device__ __forceinline__ void h_epilogue(const float* acc, uint32_t* dst) {
#pragma unroll
  for (int b = 0; b < 4; b++) {
    uint32_t w[2][2];
#pragma unroll
    for (int i = 0; i < 2; i++) {
      float h[4];
#pragma unroll
      for (int e = 0; e < 4; e++) {
        const float g = acc[(2 * b + i) * 4 + e], u = acc[32 + (2 * b + i) * 4 + e];
        h[e] = fmaf(tanh_fast(0.5f * g), u, u);
      }
      w[0][i] = pack(h[0], h[1]); w[1][i] = pack(h[2], h[3]);
    }
    *reinterpret_cast<uint2*>(dst + 1024 * b) = make_uint2(w[0][0], w[0][1]);
    *reinterpret_cast<uint2*>(dst + 1024 * b + 32) = make_uint2(w[1][0], w[1][1]);
  }
}
__device__ __forceinline__ void rotate9(uint32_t (&v)[9][2]) {
#pragma unroll
  for (int rh = 0; rh < 2; rh++) {
    const uint32_t r = v[8][rh];
#pragma unroll
    for (int i = 8; i > 0; i--) v[i][rh] = v[i - 1][rh];
    v[0][rh] = r;
  }
}
template <int HP> __device__ __forceinline__ void store_kv_head(uint32_t (&pk)[2][9][2], uint32_t* kvp, int lane, uint32_t sk = 0, uint32_t sv = 0) {
  const int t = lane & 3, dv = ((t - HP) & 3) - t;
  const bool up = t < HP;
#pragma unroll
  for (int rh = 0; rh < 2; rh++) {
    uint32_t* d = kvp + HP * SEQ * 20 + rh * 160;
    const uint32_t c0 = up ? pk[0][2 * HP + 1][rh] : pk[0][2 * HP][rh], c1 = up ? pk[0][2 * HP + 2][rh] : pk[0][2 * HP + 1][rh];
    const uint32_t c3 = up ? pk[1][2 * HP + 1][rh] : pk[1][2 * HP][rh], c4 = up ? pk[1][2 * HP + 2][rh] : pk[1][2 * HP + 1][rh];
    const uint32_t v9 = __shfl_sync(0xffffffffu, pk[1][2 * HP + 2][rh], (lane & ~3) | HP);
    const uint32_t c2 = t == HP ? pk[0][2 * HP + 2][rh] : t == ((HP + 1) & 3) ? 0x3f803f80u : t == ((HP + 2) & 3) ? v9 : 0u;
    d[0] = c0; d[32] = c1; d[64] = c2; d[96 + dv] = c3; d[128 + dv] = c4;
    if (sk) {
      asm volatile("st.shared.b32 [%0], %1;\nst.shared.b32 [%0 + 128], %2;\nst.shared.b32 [%0 + 256], %3;" ::"r"(sk + rh * 384), "r"(c0), "r"(c1), "r"(c2) : "memory");
      asm volatile("st.shared.b32 [%0], %1;\nst.shared.b32 [%2 + 128], %3;\nst.shared.b32 [%2 + 256], %4;" ::"r"(sv + rh * 384), "r"(c2), "r"(sv + rh * 384 + dv * 4), "r"(c3), "r"(c4) : "memory");
    }
  }
}

template <int OFF> __device__ __forceinline__ void ld4(uint32_t* v, const void* p) {
  asm volatile("ld.relaxed.gpu.global.v4.b32 {%0,%1,%2,%3}, [%4 + %5];" : "=r"(v[0]), "=r"(v[1]), "=r"(v[2]), "=r"(v[3]) : "l"(p), "n"(OFF) : "memory");
}
template <int OFF> __device__ __forceinline__ void ld2(uint32_t* v, const void* p) {
  asm volatile("ld.relaxed.gpu.global.v2.b32 {%0,%1}, [%2 + %3];" : "=r"(v[0]), "=r"(v[1]) : "l"(p), "n"(OFF) : "memory");
}
__device__ __forceinline__ void stage_partials(const float* acc, uint32_t dst, int tid) {
  const int lane = tid & 31, row = (tid >> 5) * 16 + (lane & 15);
  const uint32_t r128 = dst + row * 128;
#pragma unroll
  for (int i = 0; i < 12; i++) {
    const float* v = acc + 8 * i;
    stsm4(r128 + (i >> 2) * 16384 + (((2 * (i & 3) + (lane >> 4)) ^ (row & 7)) << 4), pack(v[0], v[1]), pack(v[2], v[3]), pack(v[4], v[5]), pack(v[6], v[7]));
  }
#pragma unroll
  for (int d = 0; d < 4; d++) {
    const float* v = acc + 128 + 8 * (d & 1) + 2 * (d >> 1);
    asm volatile("st.shared.v2.b32 [%0], {%1,%2};" ::"r"(dst + 49152 + d * 2048 + tid * 8), "r"(pack(v[0], v[1])), "r"(pack(v[4], v[5])) : "memory");
  }
}
__device__ __forceinline__ float own_share(const float* v, int o, int q) {
  const float s0 = (q & 2) ? v[o + 2] : v[o], s1 = (q & 2) ? v[o + 10] : v[o + 8];
  return (q & 1) ? s1 : s0;
}
__device__ __forceinline__ void final_epilogue(const float* acc, const float* rem, const Params& prm, int m, int hh, int q, int tid) {
  uint32_t r[18];
#pragma unroll
  for (int i = 0; i < 16; i++) r[i] = pack(acc[2 * i] * 0.5f, acc[2 * i + 1] * 0.5f);
#pragma unroll
  for (int i = 0; i < 2; i++) {
    r[16 + i] = pack(fmaf(own_share(acc + 32, 4 * i, q), 0.5f, rem[2 * i]), fmaf(own_share(acc + 32, 4 * i + 1, q), 0.5f, rem[2 * i + 1]));
  }
  const size_t off = (size_t)(128 * m + (tid >> 5) * 16 + ((tid & 31) >> 2)) * DM + 2 * (tid & 3);
  const bool odd = tid & 1;
  uint32_t* o1 = reinterpret_cast<uint32_t*>(prm.out + off + 320 * hh + 64 * q) + (odd ? 3 : 0);
  uint32_t* o2 = reinterpret_cast<uint32_t*>(prm.out + off + 256 + 32 * hh + 16 * (q & 1) + (q >> 1) * 8 * DM) + (odd ? 3 : 0);
#pragma unroll
  for (int i = 0; i < 9; i++) {
    const uint32_t A = i < 8 ? r[4 * (i >> 1) + (i & 1)] : r[16], B = i < 8 ? r[4 * (i >> 1) + 2 + (i & 1)] : r[17];
    const uint32_t y = __shfl_xor_sync(0xffffffffu, odd ? A : B, 1);
    *reinterpret_cast<uint2*>(i < 8 ? o1 + 8 * (i >> 1) + (i & 1) * 8 * (DM / 2) : o2) = odd ? make_uint2(y, B) : make_uint2(A, y);
  }
}

__global__ void __launch_bounds__(384, 1) fused_kernel(const __grid_constant__ Params prm) {
  extern __shared__ __align__(1024) uint8_t smem[];
  constexpr uint32_t sb = 1024;
  const uint32_t bar = sb + SM_BAR;
  const int m = blockIdx.x & 15, j = blockIdx.x >> 4;
  const int cta = m * 8 + j;
  const int wr = __shfl_sync(0xffffffffu, (int)(threadIdx.x >> 5), 0);
  const int wg = wr >> 2;
  const int lane = threadIdx.x & 31;
  STAMP(0);
  if (wg == 2 && lane == 0) {
    if (wr == 8) {
      asm volatile("prefetch.tensormap [%0];" ::"l"(&prm.xm) : "memory");
#pragma unroll
      for (int c = 0; c < 9; c++) mbar_init(bar + 8 * (B_X + c), 1);
#pragma unroll
      for (int c = 0; c < 9; c++) mbar_expect(bar + 8 * (B_X + c), 16384);
      asm volatile("fence.proxy.async.shared::cta;" ::: "memory");
#pragma unroll
      for (int c = 0; c < 3; c++) tma2d(sb + SM_XN + c * 16384, &prm.xm, bar + 8 * (B_X + c), 64 * c, 128 * m);
    } else {
      if (wr == 9) {
#pragma unroll
        for (int i = 0; i < 8; i++) mbar_init(bar + 8 * (B_F + i), 2);
#pragma unroll
        for (int i = 0; i < 3; i++) mbar_init(bar + 8 * (B_QF + i), 1);
      } else if (wr == 10) {
#pragma unroll
        for (int i = 0; i < 8; i++) mbar_init(bar + 8 * (B_E + i), 8);
#pragma unroll
        for (int i = 0; i < 3; i++) mbar_init(bar + 8 * (B_QE + i), 8);
      } else {
#pragma unroll
        for (int i = B_SK1; i <= B_SP; i++) mbar_init(bar + 8 * i, 8);
        mbar_init(bar + 8 * B_OL, 1); mbar_init(bar + 8 * B_RX, 1);
        mbar_init(bar + 8 * B_NR, 4); mbar_init(bar + 8 * (B_NR + 1), 4);
        asm volatile("st.shared.u32 [%0], 0;" ::"r"(sb + SM_BAD) : "memory");
        if ((uint32_t)__cvta_generic_to_shared(smem) != sb || (sb & 1023)) asm volatile("trap;");
      }
      asm volatile("fence.proxy.async.shared::cta;" ::: "memory");
    }
  }
  if (wr == 0) {
    const uint32_t one = (lane >> 3) == (lane & 3) ? ((lane & 4) ? 0x3f800000u : 0x00003f80u) : 0u;
    asm volatile("st.shared.v4.b32 [%0], {%1,%2,%2,%1};" ::"r"(sb + SM_ID + lane * 16), "r"(one), "r"(0) : "memory");
  }
  __syncthreads();

  if (wg == 2) {
    asm volatile("setmaxnreg.dec.sync.aligned.u32 24;");
    const int pw = wr & 3;
    const uint32_t epoch = *(volatile uint32_t*)FLAG_EPOCH(cta);
    const int hh = j & 1;
#define ACOL(A) (320 * hh + 64 * (((j >> 1) + 1 + (A)) & 3))
    if (pw == 0) {
      if (lane == 0) {
#pragma unroll
        for (int c = 3; c < 9; c++) tma2d(sb + SM_XN + c * 16384, &prm.xm, bar + 8 * (B_X + c), 64 * c, 128 * m);
        uint64_t pol;
        asm volatile("createpolicy.fractional.L2::evict_first.b64 %0, 1.0;" : "=l"(pol));
#pragma unroll 1
        for (int kb = 0; kb < 9; kb++) {
          const int s = kb % 3;
          if (kb >= 3) mbar_wait(bar + 8 * (B_QE + s), (kb / 3 - 1) & 1);
          const uint32_t fb = bar + 8 * (B_QF + s), dst = sb + SM_RING + s * QST;
          mbar_expect(fb, QST);
#pragma unroll
          for (int p = 0; p < 3; p++) {
            tma2d_h(dst + p * 8192, &prm.wqkv64, fb, 576 * p + 72 * j + 8 * hh, 64 * kb, pol);
            tma2d(dst + 24576 + p * 1024, &prm.wqkv8, fb, 576 * p + 72 * j + 64 - 64 * hh, 64 * kb);
          }
        }
        asm volatile("st.shared.u32 [%0], %1;" ::"r"(sb + SM_TAG), "r"((epoch + 1) & 1) : "memory");
        int col = 576 * j, kr = 0;
#pragma unroll 1
        for (int n = 0; n < N_G2; n++) {
          const uint32_t fb = bar + 8 * (B_F + (n & 7)), dst = sb + SM_RING + (n & 3) * BST;
          mbar_expect(fb, BST);
          if (n >= 4) mbar_wait(bar + 8 * (B_E + ((n - 3) & 7)), ((n - 3) >> 3) & 1);
          else if (n != 2) mbar_wait(bar + 8 * (B_QE + (n == 3 ? 2 : n)), 0);
          tma2d_h(dst, &prm.wg, fb, col, kr, pol);
          tma2d_h(dst + 8192, &prm.wu, fb, col, kr, pol);
          if ((kr += 64) == 576) { kr = 0; col += 64; }
        }
        uint32_t seen = 0;
#pragma unroll 1
        for (int b = 0; b < 26; b++) {
          const int n = N_G2 + 2 * b;
          const uint32_t fb = bar + 8 * (B_F + (n & 7)), dst = sb + (b & 3) * G2ST;
          const int own = b < 10 || b == 20 || b == 21, jj = own ? j : (j ^ 1), lb = b < 10 ? b : b < 20 ? b - 10 : 10 + (b & 1), need = (3 * lb + 6) >> 2;
          if (b < 24) {
            if (b == 10 || b == 20 || b == 22) seen = 0;
            if (seen < need) { seen = flag_wait_v(FLAG_H(m * 8 + jj), 9 * epoch + need) - 9 * epoch; fence_async(); }
          } else {
            flag_wait(FLAG_O((cta & ~1) + b - 24), epoch + 1);
            fence_async();
          }
          mbar_wait(bar + 8 * (B_E + ((n - 5) & 7)), ((n - 5) >> 3) & 1);
          if (b == 0) STAMPW(16);
          mbar_expect(fb, G2ST);
          if (b < 24) {
            bulk_g2s(dst, g_H + (m * 576 + 72 * jj + 6 * lb) * 512, 12288, fb);
#pragma unroll
            for (int a = 0; a < 4; a++) tma5d(dst + 12288 + a * 6144, &prm.wd[0], fb, ACOL(a), 36 * jj + 3 * lb);
            tma5d(dst + 36864, &prm.wd[1 + hh], fb, 0, 36 * jj + 3 * lb);
          } else {
            const int r = b - 24;
            bulk_g2s(dst, g_O + ((cta & ~1) + r) * 9 * 512 + r * 1024, 12288, fb);
#pragma unroll
            for (int a = 0; a < 4; a++) tma3d(dst + 12288 + a * 6144, &prm.wo3[0], fb, ACOL(a), 4 * (j & 6) + 5 * r);
            tma3d(dst + 36864, &prm.wo3[1 + hh], fb, 0, 4 * (j & 6) + 5 * r);
          }
          if (b == 0) STAMPW(17);
        }
        mbar_wait(bar + 8 * B_SP, 0);
        mbar_expect(bar + 8 * B_OL, 49152 + 32768);
        tma2d(sb + SM_RES, &prm.xm, bar + 8 * B_OL, ACOL(3), 128 * m);
        __nanosleep(200);
        tma2d(sb + SM_RES + 16384, &prm.xm, bar + 8 * B_OL, 256 + 32 * hh, 128 * m);
#pragma unroll 1
        for (int i = 0; i < 4; i++) {
          __nanosleep(200);
          tma3d(sb + SM_LB + i * 4096, &prm.wo2[0], bar + 8 * B_OL, ACOL(3), 8 * i + 3);
          tma3d(sb + SM_LB + 24576 + i * 4096, &prm.wo2[1 + hh], bar + 8 * B_OL, 0, 8 * i + 3);
          tma3d(sb + SM_LB + 16384 + i * 2048, &prm.wo16[0], bar + 8 * B_OL, ACOL(3), 8 * i);
          tma3d(sb + SM_LB + 40960 + i * 2048, &prm.wo16[1 + hh], bar + 8 * B_OL, 0, 8 * i);
        }
      }
    } else if (pw == 1) {
      if (lane == 0) {
        const int hx = hh * 3;
        int u = 0, kslot = 0, vrow = 0, kb = 0;
#pragma unroll 1
        for (int n = 0; n <= N_END; n++) {
          const uint32_t fb = bar + 8 * (B_F + (n & 7)), dst = n < N_AO ? sb + SM_KV + kslot * KVST : sb + SM_KV2 + (n - N_AO) * KVST;
          const bool att = n >= N_G2 || (n >= NG0 && kb != 0);
          if (++kb == 9) kb = 0;
          if (n >= N_AO) mbar_wait(bar + 8 * (B_E + ((n - 7) & 7)), ((n - 7) >> 3) & 1);
          mbar_expect(fb, !att || u < 2 ? 0 : (u == 2 || u == 128) ? KVST / 2 : KVST);
          if (n >= N_AO || (n > N_G2 && !(n & 1))) mbar_expect(fb, 0);
          if (u == 2 && att) { flag_wait(FLAG_KV(0, j), 16 * epoch + 16); fence_async(); STAMPW(18); }
          if (n >= 4 && n < N_AO) mbar_wait(bar + 8 * (B_E + ((n - 3) & 7)), ((n - 3) >> 3) & 1);
          if (att) {
            const int krow = (4 * j + ((u >> 5) ^ hx)) * 256 + ((u + 2 * m) & 31) * 8;
            if (u >= 2 && u < 128) tma2d(dst, &prm.kv, fb, 0, krow);
            if (u >= 3) tma2d(dst + 3072, &prm.kv, fb, 128, vrow);
            vrow = krow; u++;
            if (++kslot == 3) kslot = 0;
            if (u == 16) { flag_wait(FLAG_KV(1, j), 16 * epoch + 16); fence_async(); }
          }
        }
      }
    } else if (pw == 2) {
      if (lane == 0) {
#pragma unroll 1
        for (int i = 1; i < 18; i++) asm volatile("prefetch.tensormap [%0];" ::"l"(&prm.xm + i) : "memory");
        mbar_wait(bar + 8 * B_SK1, 0);
        STAMPW(22);
        fence_gpu(); flag_add(FLAG_KV(0, j));
        STAMPW(20);
        mbar_wait(bar + 8 * B_SK2, 0);
        fence_gpu(); flag_add(FLAG_KV(1, j));
#pragma unroll 1
        for (int t = 0; t < 9; t++) { mbar_wait(bar + 8 * B_SH, t & 1); __nanosleep(1000); fence_gpu(); flag_add(FLAG_H(cta)); }
        mbar_wait(bar + 8 * B_SO1, 0);
        fence_gpu(); flag_add(FLAG_O(cta));
      }
    } else {
      mbar_wait(bar + 8 * (B_X + 6), 0);
#pragma unroll 1
      for (int i = lane; i < 122; i += 32) pf_line(prm.pwqkv + (size_t)min(i * 128 + cta, 15551) * 64);
      mbar_wait(bar + 8 * (B_QE + 1), 0);
#pragma unroll 1
      for (int t = -3; t < 9; t++) {
        if (t >= 0) { mbar_wait(bar + 8 * B_SH, t & 1); __nanosleep(1500); }
        if (t < 6) {
#pragma unroll 1
          for (int i = lane; i < 72; i += 32) pf_line((i >= 36 ? prm.pwu : prm.pwg) + (size_t)(36 * m + (i >= 36 ? i - 36 : i)) * FF + 576 * j + 64 * (t + 3));
        }
        if ((t == 2 || t == 6 || t == 8)) {
          const uint32_t* kv = g_KV + (size_t)(4 * j + ((t == 2 ? 1 : t == 6 ? 2 : 3) ^ (hh * 3))) * SEQ * 20 + m * 2560;
#pragma unroll 1
          for (int i = lane; i < 80; i += 32) pf_line(kv + i * 32);
        }
        if (t >= 7) {
          const uint32_t* h = g_H + (m * 576 + 72 * j + 30 * (t - 7)) * 512;
#pragma unroll 1
          for (int i = lane; i < 480; i += 32) pf_line(h + i * 32);
        }
        if (t >= 5) {
#pragma unroll 1
          for (int i = lane; i < 81; i += 32) {
            const int l = (2 * m + hh) * 81 + i, r = l / 9;
            pf_line(prm.pwd + (size_t)(1152 * (j >> 1) + 576 * (r / 144) + 144 * (t - 5) + r % 144) * DM + 64 * (l % 9));
          }
        }
      }
      if (cta * 41 + lane < 5184) pf_line(prm.pwo + (size_t)(cta * 41 + lane) * 64);
      if (lane < 9 && cta * 41 + 32 + lane < 5184) pf_line(prm.pwo + (size_t)(cta * 41 + 32 + lane) * 64);
      if (lane == 0) {
      mbar_wait(bar + 8 * B_SP, 0);
      const int q = j >> 1;
#pragma unroll 1
      for (int i = 0; i < 14; i++) {
        bulk_s2g(g_P + cta * 3584 + i * 256, sb + SM_SEND + i * 4096, 4096);
        asm volatile("cp.async.bulk.commit_group;\ncp.async.bulk.wait_group.read 4;" ::: "memory");
      }
      asm volatile("cp.async.bulk.wait_group 0;" ::: "memory");
      fence_gpu();
      flag_add(FLAG_P(cta));
      STAMPW(15);
      mbar_expect(bar + 8 * B_RX, 55296);
#pragma unroll 1
      for (int a = 0; a < 3; a++) {
        const int src = m * 8 + 2 * ((q + 3 - a) & 3) + hh;
        flag_wait(FLAG_P(src), epoch + 1);
        fence_async();
        bulk_g2s(sb + SM_RECV + a * 16384, g_P + src * 3584 + a * 1024, 16384, bar + 8 * B_RX);
        bulk_g2s(sb + SM_RECV + 49152 + a * 2048, g_P + src * 3584 + 3072 + q * 128, 2048, bar + 8 * B_RX);
      }
      STAMPW(25);
      *FLAG_EPOCH(cta) = epoch + 1;
      }
    }
  } else {
    const int tid = threadIdx.x;
    const int t = lane & 3;
    const uint32_t l0 = lane == 0;
    const uint32_t adesc = (((sb + SM_XN + wg * 8192) & 0x3FFFF) >> 4) | LO_A;
    const uint32_t bdesc = (((sb + SM_RING) & 0x3FFFF) >> 4) | LO_B;
    const uint32_t kdesc0 = (((sb + SM_KV) & 0x3FFFF) >> 4) | LO_K;
    const int hx = (j & 1) ? 3 : 0;
    float accA[64], accB[64];
    uint32_t qn[6];
    Att a;
    uint32_t gs = 0, s8 = 0, fph = 0;
#define G1_ISSUE(ACC, AD, BD) _Pragma("unroll") for (int k = 0; k < 4; k++) wg_ss_n128<HI_SW128, HI_SW128>(ACC, (AD) + k * 2, (BD) + k * 128);
#define G1_ISSUE_Z(ACC, BD)                                                                                    \
  wg_ss_z_n128<HI_SW128, HI_SW128>(ACC, adesc, BD);                                                            \
  _Pragma("unroll") for (int k = 1; k < 4; k++) wg_ss_n128<HI_SW128, HI_SW128>(ACC, adesc + k * 2, (BD) + k * 128);
#define F_BAR (bar + 8 * B_F + 8 * s8)
#define F_PH fph
#define RELEASE() mbar_arrive_if(bar + 8 * B_E + 8 * s8, l0);
#define NEXT_SLOT() { gs++; fph ^= s8 == 7; s8 = s8 == 7 ? 0 : s8 + 1; }
#define NEXT_B() bd = bd == bdesc + 3072 ? bdesc : bd + 1024;
#define G1_ONLY() { mbar_wait(F_BAR, F_PH); wg_fence(); G1_ISSUE(accA, adesc + gs * 1024, bdesc + (gs & 3) * 1024) wg_commit(); wg_wait<1>(); RELEASE() NEXT_SLOT() }
    {
      const int lr = wr * 16 + (lane & 15);
      uint32_t ra[4];
#pragma unroll
      for (int k = 0; k < 4; k++) ra[k] = sb + SM_XN + lr * 128 + (((2 * k + (lane >> 4)) ^ (lr & 7)) << 4);
      asm volatile("setmaxnreg.inc.sync.aligned.u32 240;");
      float aq[96], ar[12];
#pragma unroll
      for (int i = 0; i < 96; i++) aq[i] = __int_as_float(lane >> 5);
#pragma unroll
      for (int i = 0; i < 12; i++) ar[i] = __int_as_float(lane >> 5);
      pin<96>(aq); pin<12>(ar);
      float cs[2][4] = {}, q0 = 0.f, q1 = 0.f, q2 = 0.f, q3 = 0.f;
#pragma unroll 1
      for (int c = 0; c < 9; c++) {
        mbar_wait(bar + 8 * (B_X + c), 0);
        uint32_t v[4][4];
#pragma unroll
        for (int k = 0; k < 4; k++) ldsm4(v[k], ra[k] + c * 16384);
#pragma unroll
        for (int k = 0; k < 4; k++) {
          mma_ones(cs[k & 1], v[k]);
#pragma unroll
          for (int e = 0; e < 4; e += 2) {
            const float x0 = bf_lo(v[k][e]), x1 = bf_hi(v[k][e]), y0 = bf_lo(v[k][e + 1]), y1 = bf_hi(v[k][e + 1]);
            q0 = fmaf(x0, x0, q0); q1 = fmaf(x1, x1, q1); q2 = fmaf(y0, y0, q2); q3 = fmaf(y1, y1, q3);
          }
        }
      }
      STAMP(11);
      const float mean0 = (cs[0][0] + cs[1][0]) * (1.f / 576.f), mean1 = (cs[0][2] + cs[1][2]) * (1.f / 576.f);
      q0 += q1; q2 += q3;
      q0 += __shfl_xor_sync(0xffffffffu, q0, 1); q2 += __shfl_xor_sync(0xffffffffu, q2, 1);
      q0 += __shfl_xor_sync(0xffffffffu, q0, 2); q2 += __shfl_xor_sync(0xffffffffu, q2, 2);
      float var0 = fmaf(q0, 1.f / 576.f, -mean0 * mean0), var1 = fmaf(q2, 1.f / 576.f, -mean1 * mean1);
      if (__any_sync(0xffffffffu, !(mean0 * mean0 <= 8.f * var0) || !(mean1 * mean1 <= 8.f * var1))) {
        q0 = q2 = 0.f;
#pragma unroll 1
        for (int i = 0; i < 36; i++) {
          uint32_t v[4];
          ldsm4(v, ((ra[0] + (i >> 2) * 16384) ^ ((i & 3) << 5)));
#pragma unroll
          for (int e = 0; e < 4; e += 2) {
            const float x0 = bf_lo(v[e]) - mean0, x1 = bf_hi(v[e]) - mean0, y0 = bf_lo(v[e + 1]) - mean1, y1 = bf_hi(v[e + 1]) - mean1;
            q0 = fmaf(x0, x0, fmaf(x1, x1, q0)); q2 = fmaf(y0, y0, fmaf(y1, y1, q2));
          }
        }
        q0 += __shfl_xor_sync(0xffffffffu, q0, 1); q2 += __shfl_xor_sync(0xffffffffu, q2, 1);
        q0 += __shfl_xor_sync(0xffffffffu, q0, 2); q2 += __shfl_xor_sync(0xffffffffu, q2, 2);
        var0 = q0 * (1.f / 576.f); var1 = q2 * (1.f / 576.f);
      }
      const float inv0 = rcp_fast(bf_round(sqrt_fast(bf_round(bf_round(var0) + 1e-5f)))), inv1 = rcp_fast(bf_round(sqrt_fast(bf_round(bf_round(var1) + 1e-5f))));
      const uint32_t mb0 = pack(mean0, mean0), mb1 = pack(mean1, mean1);
      const uint32_t h0 = pack(inv0, inv0), h1 = pack(inv1, inv1);
      const uint32_t e0 = pack(inv0 - bf_lo(h0), inv0 - bf_lo(h0)), e1 = pack(inv1 - bf_lo(h1), inv1 - bf_lo(h1));
      uint32_t v[4][4], xn[4][4];
#pragma unroll
      for (int k = 0; k < 4; k++) ldsm4(v[k], ra[k]);
      STAMP(1);
      const uint32_t rdesc = (((sb + SM_RING + 24576) & 0x3FFFF) >> 4) | LO_R;
      uint32_t s = 0, ph = 0;
#pragma unroll 1
      for (int kb = 0; kb < 9; kb++) {
#pragma unroll
        for (int k = 0; k < 4; k++) {
          xn[k][0] = bscale2(bsub2(v[k][0], mb0), h0, e0); xn[k][1] = bscale2(bsub2(v[k][1], mb1), h1, e1);
          xn[k][2] = bscale2(bsub2(v[k][2], mb0), h0, e0); xn[k][3] = bscale2(bsub2(v[k][3], mb1), h1, e1);
        }
        pin<16>(&xn[0][0]);
        mbar_wait(bar + 8 * B_QF + 8 * s, ph);
        wg_fence();
#pragma unroll
        for (int k = 0; k < 4; k++) {
          wg_rs_n192<HI_SW128>(aq, xn[k][0], xn[k][1], xn[k][2], xn[k][3], bdesc + s * (QST >> 4) + k * 128);
          wg_rs_n24<HI_R>(ar, xn[k][0], xn[k][1], xn[k][2], xn[k][3], rdesc + s * (QST >> 4) + k * 16);
        }
        wg_commit();
#pragma unroll
        for (int k = 0; k < 4; k++) stsm4(ra[k] + kb * 16384, xn[k][0], xn[k][1], xn[k][2], xn[k][3]);
#pragma unroll
        for (int k = 0; k < 4; k++) ldsm4(v[k], ra[k] + (kb < 8 ? kb + 1 : 8) * 16384);
        if (kb == 8) {
          asm volatile("fence.proxy.async.shared::cta;" ::: "memory");
          __syncwarp();
          mbar_arrive_if(bar + 8 * B_NR + 8 * wg, l0);
        }
        wg_wait<0>();
        mbar_arrive_if(bar + 8 * B_QE + 8 * s, l0);
        if (++s == 3) { s = 0; ph ^= 1; }
      }
      pin<96>(aq); pin<12>(ar);
      STAMP(2);
      uint32_t* kvp = g_KV + (size_t)(4 * j) * SEQ * 20 + (16 * m + 2 * wr) * 160 + lane;
      uint32_t pk[2][9][2];
#pragma unroll
      for (int p = 0; p < 2; p++)
#pragma unroll
        for (int i = 0; i < 9; i++) {
          const float* src = i < 8 ? &aq[(8 * (p + 1) + i) * 4] : &ar[4 * (p + 1)];
          pk[p][i][0] = pack(src[0], src[1]); pk[p][i][1] = pack(src[2], src[3]);
        }
      const uint32_t sk = sb + SM_KV + wg * KVST + (wr & 3) * 768 + lane * 4;
      mbar_wait(bar + 8 * (B_QE + 2), 0);
      if (hx) {
#pragma unroll
        for (int p = 0; p < 2; p++) { rotate9(pk[p]); }
        store_kv_head<3>(pk, kvp, lane, sk, sk + KVST + 3072);
      } else store_kv_head<0>(pk, kvp, lane, sk, sk + KVST + 3072);
      asm volatile("fence.proxy.async.shared::cta;" ::: "memory");
      __syncwarp();
      mbar_arrive_if(bar + 8 * B_SK1, l0);
      mbar_arrive_if(bar + 8 * B_LK, l0);
      STAMP(3);
      mbar_wait(bar + 8 * B_NR + 8 * wg, 0);
      mbar_wait(bar + 8 * B_F, 0);
      wg_fence();
      G1_ISSUE_Z(accA, bdesc)
      wg_commit();
      RELEASE()
      NEXT_SLOT()
      mbar_wait(F_BAR, F_PH);
      wg_fence();
      G1_ISSUE(accA, adesc + 1024, bdesc + 1024)
      wg_commit();
      uint32_t pq[9][2];
#pragma unroll
      for (int i = 0; i < 9; i++) {
        const float* src = i < 8 ? &aq[i * 4] : &ar[0];
        pq[i][0] = bscale2(pack(src[0], src[1]), QS_HI, QS_LO); pq[i][1] = bscale2(pack(src[2], src[3]), QS_HI, QS_LO);
      }
      if (hx) rotate9(pq);
      pin<18>(&pq[0][0]);
      wg_wait<1>();
      RELEASE()
      NEXT_SLOT()
      G1_ONLY()
      mbar_wait(F_BAR, F_PH);
      wg_fence();
      G1_ISSUE(accA, adesc + 3 * 1024, bdesc + 3 * 1024)
      wg_commit();
      if (hx) store_kv_head<0>(pk, kvp, lane); else store_kv_head<3>(pk, kvp, lane);
      store_kv_head<1>(pk, kvp, lane);
      store_kv_head<2>(pk, kvp, lane);
      __syncwarp();
      mbar_arrive_if(bar + 8 * B_SK2, l0);
      wg_wait<1>();
      RELEASE()
      NEXT_SLOT()
      mbar_wait(F_BAR, F_PH);
      wg_fence();
      G1_ISSUE(accA, adesc + 4 * 1024, bdesc)
      wg_commit();
      uint32_t qf[4][6];
#pragma unroll
      for (int hp = 0; hp < 4; hp++) {
        const bool up = t < hp;
        qf[hp][0] = up ? pq[2 * hp + 1][0] : pq[2 * hp][0]; qf[hp][1] = up ? pq[2 * hp + 1][1] : pq[2 * hp][1];
        qf[hp][2] = up ? pq[2 * hp + 2][0] : pq[2 * hp + 1][0]; qf[hp][3] = up ? pq[2 * hp + 2][1] : pq[2 * hp + 1][1];
        qf[hp][4] = t == hp ? pq[2 * hp + 2][0] : 0u; qf[hp][5] = t == hp ? pq[2 * hp + 2][1] : 0u;
      }
      if (hx) {
        store_q(qf[0], cta, 0, tid); store_q(qf[1], cta, 1, tid);
#pragma unroll
        for (int i = 0; i < 6; i++) { a.q[i] = qf[3][i]; qn[i] = qf[2][i]; }
      } else {
        store_q(qf[2], cta, 2, tid); store_q(qf[3], cta, 3, tid);
#pragma unroll
        for (int i = 0; i < 6; i++) { a.q[i] = qf[0][i]; qn[i] = qf[1][i]; }
      }
      a.q[6] = __shfl_sync(0xffffffffu, lane, 0); a.q[7] = __shfl_sync(0xffffffffu, lane >> 1, 1);
#pragma unroll
      for (int i = 0; i < 16; i++) a.p[i] = 0;
#pragma unroll
      for (int i = 0; i < 12; i++) a.o[i] = 0.f;
      pin<16>(a.p); pin<12>(a.o); pin<8>(a.q);
      wg_wait<1>();
      RELEASE()
      NEXT_SLOT()
    }
    static_assert(NG0 == 5, "item boundaries must fall into even F tiles / even GEMM2 slots");
    STAMP(4);
    mbar_wait(bar + 8 * B_LK, 0);
    mbar_wait(F_BAR, F_PH);
    STAMP(23);
    uint32_t kd = kdesc0;
    uint32_t it = 0;
    uint32_t ox0 = 0, ox1 = 0;
    uint32_t* hdst = g_H + ((m * 576 + 72 * j + (t >> 1)) * 128 + 16 * wr + (lane >> 2)) * 4 + 2 * (t & 1);
    uint32_t ad = adesc + NG0 * 1024, bd = bdesc + (gs & 3) * 1024;

#define ITEM_FIRST()                                                                                           \
  {                                                                                                            \
    pin<12>(a.o);                                                                                              \
    if (it != 0) {                                                                                             \
      uint32_t w[4];                                                                                           \
      o_normalise(a.o, w, ox0, ox1, ((it >> 5) - 1) ^ hx, lane, sb + SM_BAD, wr);                              \
      uint32_t* d = g_O + cta * 9 * 512 + (((it >> 5) - 1) ^ hx) * 1024 + wr * 64 + lane;                      \
      d[0] = w[0]; d[32] = w[1]; d[512] = w[2]; d[544] = w[3];                                                 \
    }                                                                                                          \
    if (it == 96) mbar_arrive_if(bar + 8 * B_SO1, l0 & (bad_heads(sb + SM_BAD, wr) == 0));                     \
    first_tile(a, (it >> 5) ^ hx, lane);                                                                       \
  }
#define KV_ADVANCE() { kd = kd == kdesc0 + 768 ? kdesc0 : kd + 384; }
#define SOFTMAX_NEXT() { softmax_a(a); mbar_wait(F_BAR, F_PH); softmax_b(a); }
#define EPI_STEP(ACCN, ACCO)                                                                                   \
  {                                                                                                            \
    wg_fence();                                                                                                \
    G1_ISSUE_Z(ACCN, bd)                                                                                       \
    wg_commit();                                                                                               \
    wg_wait<1>();                                                                                              \
    pin<64>(ACCO);                                                                                             \
    RELEASE()                                                                                                  \
    NEXT_SLOT()                                                                                                \
    ad = adesc + 1024; NEXT_B()                                                                                \
    const uint32_t ok = mbar_test(F_BAR, F_PH);                                                                \
    h_epilogue(ACCO, hdst);                                                                                    \
    hdst += 4096;                                                                                              \
    __syncwarp();                                                                                              \
    mbar_arrive_if(bar + 8 * B_SH, l0);                                                                        \
    if (__builtin_expect(!ok, 0)) mbar_wait(F_BAR, F_PH);                                                                                            \
  }
#define ATT_LOOP1(ACC, ITEMS)                                                                                  \
  do {                                                                                                         \
    wg_fence();                                                                                                \
    issue_att(a, kd);                                                                                          \
    wg_commit();                                                                                               \
    G1_ISSUE(ACC, ad, bd)                                                                                      \
    wg_commit();                                                                                               \
    wg_wait<1>();                                                                                              \
    pin<32>(a.s);                                                                                              \
    RELEASE()                                                                                                  \
    TRACE()                                                                                                    \
    if (ITEMS) { if (__builtin_expect(((it + 1) & 31) < 2, 0)) { if (it & 1) { store_q(a.q, cta, (it >> 5) ^ hx, tid); _Pragma("unroll") for (int i = 0; i < 6; i++) asm volatile("mov.b32 %0, %1;" : "=r"(a.q[i]) : "r"(qn[i])); } else { if (it == 64) fetch_q(qn, cta, 3 ^ hx, tid); ITEM_FIRST() } } } \
    NEXT_SLOT() it++;                                                                                                \
    KV_ADVANCE()                                                                                               \
    ad += 1024; NEXT_B()                                                                                       \
    SOFTMAX_NEXT()                                                                                             \
    pin<8>(a.q);                                                                                               \
  } while ((int)(ad - adesc) < 9 * 1024);
#pragma unroll 1
    for (int pr = 0;; pr++) {
      ATT_LOOP1(accA, true)
      if (pr == 4) break;
      if (pr == 2) STAMP(29);
      EPI_STEP(accB, accA)
      if (pr == 2) STAMP(30);
      ATT_LOOP1(accB, false)
      if (pr == 2) STAMP(31);
      if (pr == 3) fetch_q(qn, cta, 2 ^ hx, tid);
      EPI_STEP(accA, accB)
      if (pr == 2) STAMP(21);
      if (pr == 3) STAMP(14);
    }
    STAMP(5);
    wg_wait<0>();
    pin<64>(accA);
    h_epilogue(accA, hdst);
    __syncwarp();
    mbar_arrive_if(bar + 8 * B_SH, l0);
    mbar_wait(bar + 8 * B_E, 0);
    asm volatile("st.shared.v4.b32 [%0], {%1,%2,%3,%4};\nst.shared.v2.b32 [%5], {%6,%7};" ::"r"(sb + SM_QS + tid * 16), "r"(qn[0]), "r"(qn[1]), "r"(qn[2]), "r"(qn[3]),
                 "r"(sb + SM_QS + 4096 + tid * 8), "r"(qn[4]), "r"(qn[5]) : "memory");
    STAMP(6);
    STAMP(12);

    float acc2[144];
    const uint32_t a2desc = (((sb + wg * 1024) & 0x3FFFF) >> 4) | LO_O;
    const uint32_t b2desc = (((sb + 12288) & 0x3FFFF) >> 4) | LO_B48;
    ad = a2desc; bd = b2desc;
#define G2_LO(K) wg_ss_n128<HI_O, HI_SW128>(acc2, ad + (K) * 256, bd + (K) * 128);
#define G2_HI(K) wg_ss_n160<HI_O, HI_SW128>(acc2 + 64, ad + (K) * 256, bd + (K) * 128 + 768);
#define ATT_PAIR(ZERO)                                                                                         \
  {                                                                                                            \
    wg_fence();                                                                                                \
    issue_att(a, kd);                                                                                          \
    wg_commit();                                                                                               \
    if (ZERO) { wg_ss_z_n128<HI_O, HI_SW128>(acc2, ad, bd); wg_ss_z_n160<HI_O, HI_SW128>(acc2 + 64, ad, bd + 768); } \
    else { G2_LO(0) G2_HI(0) }                                                                                 \
    G2_LO(1)                                                                                                   \
    wg_commit();                                                                                               \
    wg_wait<1>();                                                                                              \
    pin<32>(a.s);                                                                                              \
    RELEASE()                                                                                                  \
    TRACE()                                                                                                    \
    if (!(ZERO)) { if (__builtin_expect(gs == N_G2 + 96 - IT_G2, 0)) ITEM_FIRST() }                                    \
    NEXT_SLOT() it++;                                                                                                \
    KV_ADVANCE()                                                                                               \
    SOFTMAX_NEXT()                                                                                             \
    pin<8>(a.q);                                                                                               \
    wg_fence();                                                                                                \
    issue_att(a, kd);                                                                                          \
    wg_commit();                                                                                               \
    G2_HI(1) G2_LO(2) G2_HI(2)                                                                                 \
    wg_commit();                                                                                               \
    wg_wait<1>();                                                                                              \
    pin<32>(a.s);                                                                                              \
    RELEASE()                                                                                                  \
    TRACE()                                                                                                    \
    if (!(ZERO) && __builtin_expect(gs == N_G2 + 95 - IT_G2, 0)) {                                                     \
      const int ft = fresh_tid();                                                                              \
      asm volatile("ld.shared.v4.b32 {%0,%1,%2,%3}, [%6];\nld.shared.v2.b32 {%4,%5}, [%7];" : "=r"(a.q[0]), "=r"(a.q[1]), "=r"(a.q[2]), "=r"(a.q[3]), \
                   "=r"(a.q[4]), "=r"(a.q[5]) : "r"(sb + SM_QS + ft * 16), "r"(sb + SM_QS + 4096 + ft * 8) : "memory"); \
    }                                                                                                          \
    NEXT_SLOT() it++;                                                                                                \
    KV_ADVANCE()                                                                                               \
    ad = ad == a2desc + 3 * 2688 ? a2desc : ad + 2688; bd = ad + (b2desc - a2desc);                                \
    SOFTMAX_NEXT()                                                                                             \
    pin<8>(a.q);                                                                                               \
  }
    ATT_PAIR(true)
#pragma unroll 1
    for (int half = 0; half < 2; half++) {
      const uint32_t stop = half ? N_AO : N_G2 + 46;
      do ATT_PAIR(false) while (gs != stop);
      if (!half) {
        const uint32_t bad = bad_heads(sb + SM_BAD, wr);
        if (bad) { repair_rows(cta, wr, bad, 3 ^ hx, false); mbar_arrive_if(bar + 8 * B_SO1, l0); }
      }
    }
    STAMP(13);
    wg_wait<0>();
    pin<144>(acc2);
    mbar_wait(bar + 8 * (B_E + 1), 0);
    stage_partials(acc2, sb + SM_SEND, fresh_tid());
    asm volatile("fence.proxy.async.shared::cta;" ::: "memory");
    __syncwarp();
    mbar_arrive_if(bar + 8 * B_SP, l0);
    static_assert(N_END - N_AO == 8, "SM_KV2 layout");
    kd = (((sb + SM_KV2) & 0x3FFFF) >> 4) | LO_K;
    do {
      wg_fence();
      issue_att(a, kd);
      wg_commit();
      wg_wait<0>();
      pin<32>(a.s);
      RELEASE()
      TRACE()
      NEXT_SLOT() it++;
      kd += 384;
      SOFTMAX_NEXT()
    } while (gs != N_END);
    STAMP(7);
    wg_fence();
    issue_pv(a, kd);
    wg_commit();
    int tid2, bid2;
    asm volatile("mov.u32 %0, %%tid.x;" : "=r"(tid2));
    asm volatile("mov.u32 %0, %%ctaid.x;" : "=r"(bid2));
    const int m2 = bid2 & 15, j2 = bid2 >> 4;
    uint32_t tag;
    asm volatile("ld.shared.u32 %0, [%1];" : "=r"(tag) : "r"(sb + SM_TAG) : "memory");
    wg_wait<0>();
    pin<12>(a.o);
    {
      uint32_t w[4];
      o_normalise(a.o, w, ox0, ox1, 3 ^ hx, lane, sb + SM_BAD, wr);
      ox0 = __shfl_xor_sync(0xffffffffu, ox0, 2); ox1 = __shfl_xor_sync(0xffffffffu, ox1, 2);
      const uint32_t bad = bad_heads(sb + SM_BAD, wr);
      if (bad) {
        uint32_t* d = g_O + cta * 9 * 512 + wr * 64 + lane;
        uint32_t* h = d + (3 ^ hx) * 1024;
        h[0] = w[0]; h[32] = w[1]; h[512] = w[2]; h[544] = w[3]; d[4096] = ox0; d[4128] = ox1;
        __syncwarp();
        repair_rows(cta, wr, bad, 3 ^ hx, true);
        w[0] = __ldcg(h); w[1] = __ldcg(h + 32); w[2] = __ldcg(h + 512); w[3] = __ldcg(h + 544); ox0 = __ldcg(d + 4096); ox1 = __ldcg(d + 4128);
      }
      asm volatile("st.relaxed.gpu.global.v4.b32 [%0], {%1,%2,%3,%4};" ::"l"(g_L + (m2 * 8 + j2) * 384 + tid2), "r"((w[0] & ~1u) | tag), "r"((w[1] & ~1u) | tag),
                   "r"((w[2] & ~1u) | tag), "r"((w[3] & ~1u) | tag) : "memory");
      asm volatile("st.relaxed.gpu.global.v2.b32 [%0], {%1,%2};" ::"l"(reinterpret_cast<uint2*>(g_L + (m2 * 8 + j2) * 384 + 256) + tid2), "r"((ox0 & ~1u) | tag),
                   "r"((ox1 & ~1u) | tag) : "memory");
    }
    STAMP(8);
    uint32_t la[48];
    const uint4* p4 = g_L + m2 * 8 * 384 + tid2;
    const uint2* p2 = reinterpret_cast<const uint2*>(g_L + m2 * 8 * 384 + 256) + tid2;
#define LOAD_LA2() { ld2<0>(la + 32, p2); ld2<6144>(la + 34, p2); ld2<12288>(la + 36, p2); ld2<18432>(la + 38, p2); \
                     ld2<24576>(la + 40, p2); ld2<30720>(la + 42, p2); ld2<36864>(la + 44, p2); ld2<43008>(la + 46, p2); }
#define LOAD_LA4() { ld4<0>(la, p4); ld4<6144>(la + 4, p4); ld4<12288>(la + 8, p4); ld4<18432>(la + 12, p4); \
                     ld4<24576>(la + 16, p4); ld4<30720>(la + 20, p4); ld4<36864>(la + 24, p4); ld4<43008>(la + 28, p4); }
    float fin[48];
    uint32_t id[4][4];
    {
      uint32_t id2[4][4];
#pragma unroll
      for (int k = 0; k < 4; k++) {
        asm volatile("ld.volatile.shared.v4.b32 {%0,%1,%2,%3}, [%4];" : "=r"(id[k][0]), "=r"(id[k][1]), "=r"(id[k][2]), "=r"(id[k][3])
                     : "r"(sb + SM_ID + ((wr & 3) == k ? lane : 1) * 16) : "memory");
#pragma unroll
        for (int e = 0; e < 4; e++) id2[k][e] = id[k][e] + (id[k][e] & 0x00800080u);
      }
      pin<16>(&id[0][0]); pin<16>(&id2[0][0]);
      const uint32_t xdesc = (((sb + SM_RES + wg * 8192) & 0x3FFFF) >> 4) | LO_B;
      STAMP(26);
      mbar_wait(bar + 8 * B_OL, 0);
      STAMP(27);
      wg_fence();
      wg_rsb_z_n64<HI_SW128>(fin, id2[0][0], id2[0][1], id2[0][2], id2[0][3], xdesc);
#pragma unroll
      for (int k = 1; k < 4; k++) {
        wg_rsb_n64<HI_SW128>(fin, id2[k][0], id2[k][1], id2[k][2], id2[k][3], xdesc + k * 128);
      }
      wg_commit();
    }
    STAMP(28);
    const uint32_t pdesc = (((sb + SM_RECV + wg * 8192) & 0x3FFFF) >> 4) | LO_B;
    mbar_wait(bar + 8 * B_RX, 0);
    STAMP(24);
    wg_fence();
#pragma unroll
    for (int i = 0; i < 12; i++) wg_rsb_n64<HI_SW128>(fin, id[i & 3][0], id[i & 3][1], id[i & 3][2], id[i & 3][3], pdesc + (i >> 2) * 1024 + (i & 3) * 128);
    wg_commit();
    float rem[4];
    {
      const int q = j2 >> 1, g = (tid2 & 31) >> 2;
      uint32_t u[4][2];
#pragma unroll
      for (int i = 0; i < 2; i++)
        asm volatile("ld.shared.b32 %0, [%1];" : "=r"(u[3][i]) : "r"(sb + SM_RES + 16384 + ((tid2 >> 5) * 16 + (q >> 1) * 8 + g) * 128 + (((2 * (q & 1) + i) ^ g) << 4) + (tid2 & 3) * 4) : "memory");
#pragma unroll
      for (int d = 0; d < 3; d++) asm volatile("ld.shared.v2.b32 {%0,%1}, [%2];" : "=r"(u[d][0]), "=r"(u[d][1]) : "r"(sb + SM_RECV + 49152 + d * 2048 + tid2 * 8) : "memory");
#pragma unroll
      for (int i = 0; i < 2; i++) {
        rem[2 * i] = fmaf((bf_lo(u[0][i]) + bf_lo(u[1][i])) + (bf_lo(u[2][i]) + own_share(acc2 + 128, 4 * i, q)), 0.5f, bf_lo(u[3][i]));
        rem[2 * i + 1] = fmaf((bf_hi(u[0][i]) + bf_hi(u[1][i])) + (bf_hi(u[2][i]) + own_share(acc2 + 128, 4 * i + 1, q)), 0.5f, bf_hi(u[3][i]));
      }
    }
    wg_wait<0>();
    pin<32>(fin);
#pragma unroll
    for (int i = 0; i < 32; i++) fin[i] += acc2[96 + i];
    pin<32>(fin);
    for (uint32_t tries = 0; tries < 0x400000u; tries++) {
      const uint32_t* pw = reinterpret_cast<const uint32_t*>(g_L + (m2 * 8 + (lane & 7)) * 384 + 256) + (tid2 | 31) * 2 + 1;
      uint32_t bad;
      do {
        asm volatile("ld.relaxed.gpu.global.b32 %0, [%1];" : "=r"(bad) : "l"(pw) : "memory");
      } while (!__all_sync(0xffffffffu, !((bad ^ tag) & 1)) && ++tries < 0x400000u);
      LOAD_LA4()
      LOAD_LA2()
      bad = 0;
#pragma unroll
      for (int i = 0; i < 48; i++) bad |= la[i] ^ tag;
      if (__all_sync(0xffffffffu, !(bad & 1))) break;
    }
#pragma unroll
    for (int i = 0; i < 48; i++) la[i] ^= tag;
    pin<48>(la);
    STAMP(19);
    const uint32_t ldesc = (((sb + SM_LB) & 0x3FFFF) >> 4) | LO_B;
    wg_fence();
#pragma unroll
    for (int k = 0; k < 12; k++) {
      wg_rsb_n64<HI_SW128>(fin, la[4 * k], la[4 * k + 1], la[4 * k + 2], la[4 * k + 3], ldesc + k * 128);
      if (k == 0) wg_rs_z_n32<HI_SW128>(fin + 32, la[0], la[1], la[2], la[3], ldesc + 1536);
      else wg_rs_n32<HI_SW128>(fin + 32, la[4 * k], la[4 * k + 1], la[4 * k + 2], la[4 * k + 3], ldesc + 1536 + k * 128);
    }
    wg_commit();
    wg_wait<0>();
    pin<48>(fin);
    STAMP(9);
    final_epilogue(fin, rem, prm, m2, j2 & 1, j2 >> 1, tid2);
    STAMP(10);
  }
}

typedef CUresult (*EncodeFn)(CUtensorMap*, CUtensorMapDataType, cuuint32_t, void*, const cuuint64_t*, const cuuint64_t*, const cuuint32_t*, const cuuint32_t*,
                             CUtensorMapInterleave, CUtensorMapSwizzle, CUtensorMapL2promotion, CUtensorMapFloatOOBfill);

void enc2d(EncodeFn enc, CUtensorMap* tm, const void* base, uint64_t w, uint64_t h, uint64_t pitch_elems, uint32_t bw, uint32_t bh, CUtensorMapSwizzle sw) {
  cuuint64_t dims[2] = {w, h}, str[1] = {pitch_elems * 2};
  cuuint32_t box[2] = {bw, bh}, es[2] = {1, 1};
  enc(tm, CU_TENSOR_MAP_DATA_TYPE_BFLOAT16, 2, const_cast<void*>(base), dims, str, box, es, CU_TENSOR_MAP_INTERLEAVE_NONE, sw,
      CU_TENSOR_MAP_L2_PROMOTION_L2_128B, CU_TENSOR_MAP_FLOAT_OOB_FILL_NONE);
}

}

extern "C" void kernel_launch(void* const* d_in, const int* in_sizes, int n_in, void* d_out, int out_size) {
  (void)in_sizes; (void)n_in; (void)out_size;
  const __nv_bfloat16* x = (const __nv_bfloat16*)d_in[0];
  const __nv_bfloat16* wqkv = (const __nv_bfloat16*)d_in[1];
  const __nv_bfloat16* wo = (const __nv_bfloat16*)d_in[2];
  const __nv_bfloat16* wg = (const __nv_bfloat16*)d_in[4];
  const __nv_bfloat16* wu = (const __nv_bfloat16*)d_in[5];
  const __nv_bfloat16* wd = (const __nv_bfloat16*)d_in[6];
  void* fn = nullptr;
  cudaDriverEntryPointQueryResult qr;
  cudaGetDriverEntryPoint("cuTensorMapEncodeTiled", &fn, cudaEnableDefault, &qr);
  EncodeFn enc = (EncodeFn)fn;
  void* kvp = nullptr;
  cudaGetSymbolAddress(&kvp, g_KV);
  Params p;
  enc2d(enc, &p.xm, x, DM, SEQ, DM, 64, 128, CU_TENSOR_MAP_SWIZZLE_128B);
  enc2d(enc, &p.kv, kvp, 320, 32 * 256, 320, 192, 8, CU_TENSOR_MAP_SWIZZLE_NONE);
  enc2d(enc, &p.wqkv64, wqkv, 3 * DM, DM, 3 * DM, 64, 64, CU_TENSOR_MAP_SWIZZLE_128B);
  enc2d(enc, &p.wqkv8, wqkv, 3 * DM, DM, 3 * DM, 8, 64, CU_TENSOR_MAP_SWIZZLE_NONE);
  enc2d(enc, &p.wg, wg, FF, DM, FF, 64, 64, CU_TENSOR_MAP_SWIZZLE_128B);
  enc2d(enc, &p.wu, wu, FF, DM, FF, 64, 64, CU_TENSOR_MAP_SWIZZLE_128B);
  for (int v = 0; v < 3; v++) {
    const cuuint64_t wdt = v ? 32 : DM;
    const int c0 = v ? 256 + 32 * (v - 1) : 0;
    for (int e = 0; e < 3; e++) {
      cuuint64_t d3[3] = {wdt, e == 2 ? 2u : 16u, 32}, s3[2] = {DM * 2, 18 * DM * 2};
      cuuint32_t b3[3] = {64, e == 2 ? 2u : 16u, e == 0 ? 3u : e == 1 ? 2u : 8u}, e3[3] = {1, 1, 1};
      enc(e == 0 ? &p.wo3[v] : e == 1 ? &p.wo2[v] : &p.wo16[v], CU_TENSOR_MAP_DATA_TYPE_BFLOAT16, 3, (void*)(wo + c0 + (e == 2 ? 16 * DM : 0)), d3, s3, b3, e3,
          CU_TENSOR_MAP_INTERLEAVE_NONE, CU_TENSOR_MAP_SWIZZLE_128B, CU_TENSOR_MAP_L2_PROMOTION_L2_128B, CU_TENSOR_MAP_FLOAT_OOB_FILL_NONE);
    }
    cuuint64_t dims[5] = {wdt, 2, 2, 4, FF / 16}, str[4] = {DM * 2, 8 * DM * 2, 2 * DM * 2, 16 * DM * 2};
    cuuint32_t box[5] = {64, 2, 2, 4, 3}, es[5] = {1, 1, 1, 1, 1};
    enc(&p.wd[v], CU_TENSOR_MAP_DATA_TYPE_BFLOAT16, 5, (void*)(wd + c0), dims, str, box, es, CU_TENSOR_MAP_INTERLEAVE_NONE,
        CU_TENSOR_MAP_SWIZZLE_128B, CU_TENSOR_MAP_L2_PROMOTION_L2_128B, CU_TENSOR_MAP_FLOAT_OOB_FILL_NONE);
  }
  p.x = x; p.pwqkv = wqkv; p.pwo = wo; p.pwg = wg; p.pwu = wu; p.pwd = wd;
  p.out = (__nv_bfloat16*)d_out;
  cudaFuncSetAttribute(fused_kernel, cudaFuncAttributeMaxDynamicSharedMemorySize, SM_TOTAL);
  fused_kernel<<<NCTA, 384, SM_TOTAL, cudaStreamPerThread>>>(p);
}
```

```cpp
#include <cuda_runtime.h>
#include <cuda.h>
#include <cuda_bf16.h>
#include <stdint.h>

namespace {

constexpr int SEQ = 2048, DM = 576, FF = 4608;
constexpr int NCTA = 128;

constexpr uint32_t SM_XN = 0;
constexpr uint32_t SM_RING = 147456;
constexpr uint32_t SM_KV = 212992;
constexpr uint32_t QST = 27648, BST = 16384, KVST = 6144;
constexpr uint32_t G2ST = 43008;
constexpr uint32_t SM_LB = 0, SM_RES = 49152, SM_SEND = 86016, SM_RECV = SM_SEND;
constexpr uint32_t SM_QS = 204800;
constexpr uint32_t SM_KV2 = SM_KV - 6 * KVST;
constexpr uint32_t SM_ID = 231424;
constexpr uint32_t SM_BAR = 231936;
constexpr uint32_t SM_TAG = 232436;
constexpr uint32_t SM_BAD = 232432;
constexpr uint32_t SM_TOTAL = 232448;
enum { B_F = 0, B_E = 8, B_QF = 16, B_QE = 19, B_SK1 = 22, B_SK2 = 23, B_SH = 24, B_SO1 = 25, B_LK = 26, B_SP = 27, B_OL = 28, B_RX = 29, B_NR = 30, B_X = 32, B_N = 41 };
constexpr int N_G2 = 81, N_AO = 133;
#define N_END (136 + NG0)
#define IT_G2 (73 - NG0)
#define QDB 1
constexpr int NG0 = 5;
constexpr int SM_B = 12;

constexpr uint32_t HI_SW128 = 0x40000040u;
constexpr uint32_t LO_A = 1u << 16;
constexpr uint32_t LO_B = 512u << 16;
constexpr uint32_t HI_R = 64u, LO_R = 8u << 16;
constexpr uint32_t HI_K = 24u, LO_K = 8u << 16;
constexpr uint32_t HI_V = 8u, LO_V = 24u << 16;
constexpr uint32_t LO_B48 = 384u << 16;
constexpr uint32_t HI_O = 8u, LO_O = 128u << 16;

constexpr uint32_t QS_HI = 0x3eae3eaeu, QS_LO = 0x39553955u;
constexpr float MOFF = 90.f;

struct __align__(64) Params {
  CUtensorMap xm, wqkv64, wqkv8, wg, wu, kv, wd[3], wo3[3], wo2[3], wo16[3];
  const __nv_bfloat16 *x, *pwqkv, *pwo, *pwg, *pwu, *pwd;
  __nv_bfloat16* out;
};

__device__ __align__(1024) uint32_t g_H[16 * 576 * 512];
__device__ __align__(1024) uint32_t g_O[NCTA * 9 * 512];
__device__ __align__(1024) uint32_t g_KV[32 * SEQ * 20];
__device__ __align__(1024) uint32_t g_Q[NCTA * 4 * 1152];
__device__ __align__(1024) uint4 g_P[NCTA * 3584];
__device__ __align__(1024) uint4 g_L[NCTA * 384];
__device__ float g_S[NCTA * 8 * SEQ];
__device__ uint32_t g_flags[16 * 32 + NCTA * 32 * 4];
#define FLAG_KV(l, j) (&g_flags[((l) * 8 + (j)) * 32])
#define FLAG_H(c) (&g_flags[16 * 32 + (c) * 32])
#define FLAG_O(c) (&g_flags[16 * 32 + NCTA * 32 + (c) * 32])
#define FLAG_P(c) (&g_flags[16 * 32 + NCTA * 64 + (c) * 32])
#define FLAG_EPOCH(c) (&g_flags[16 * 32 + NCTA * 96 + (c) * 32])
#define STAMP(i)
#define STAMPW(i)
#define TRACE()

template<uint32_t BHI> __device__ __forceinline__ void wg_rs_n192(float* d, uint32_t a0, uint32_t a1, uint32_t a2, uint32_t a3, uint32_t b) {
  asm volatile("{\n.reg .pred p;\n.reg .b64 db;\nsetp.ne.b32 p, 1, 0;\nmov.b64 db, {%100, %101};\n"
    "wgmma.mma_async.sync.aligned.m64n192k16.f32.bf16.bf16 {%0, %1, %2, %3, %4, %5, %6, %7, %8, %9, %10, %11, %12, %13, %14, %15, %16, %17, %18, %19, %20, %21, %22, %23, %24, %25, %26, %27, %28, %29, %30, %31, %32, %33, %34, %35, %36, %37, %38, %39, %40, %41, %42, %43, %44, %45, %46, %47, %48, %49, %50, %51, %52, %53, %54, %55, %56, %57, %58, %59, %60, %61, %62, %63, %64, %65, %66, %67, %68, %69, %70, %71, %72, %73, %74, %75, %76, %77, %78, %79, %80, %81, %82, %83, %84, %85, %86, %87, %88, %89, %90, %91, %92, %93, %94, %95}, {%96, %97, %98, %99}, db, p, 1, 1, 1;\n}\n"
    : "+f"(d[0]), "+f"(d[1]), "+f"(d[2]), "+f"(d[3]), "+f"(d[4]), "+f"(d[5]), "+f"(d[6]), "+f"(d[7]), "+f"(d[8]), "+f"(d[9]), "+f"(d[10]), "+f"(d[11]), "+f"(d[12]), "+f"(d[13]), "+f"(d[14]), "+f"(d[15]), "+f"(d[16]), "+f"(d[17]), "+f"(d[18]), "+f"(d[19]), "+f"(d[20]), "+f"(d[21]), "+f"(d[22]), "+f"(d[23]), "+f"(d[24]), "+f"(d[25]), "+f"(d[26]), "+f"(d[27]), "+f"(d[28]), "+f"(d[29]), "+f"(d[30]), "+f"(d[31]), "+f"(d[32]), "+f"(d[33]), "+f"(d[34]), "+f"(d[35]), "+f"(d[36]), "+f"(d[37]), "+f"(d[38]), "+f"(d[39]), "+f"(d[40]), "+f"(d[41]), "+f"(d[42]), "+f"(d[43]), "+f"(d[44]), "+f"(d[45]), "+f"(d[46]), "+f"(d[47]), "+f"(d[48]), "+f"(d[49]), "+f"(d[50]), "+f"(d[51]), "+f"(d[52]), "+f"(d[53]), "+f"(d[54]), "+f"(d[55]), "+f"(d[56]), "+f"(d[57]), "+f"(d[58]), "+f"(d[59]), "+f"(d[60]), "+f"(d[61]), "+f"(d[62]), "+f"(d[63]), "+f"(d[64]), "+f"(d[65]), "+f"(d[66]), "+f"(d[67]), "+f"(d[68]), "+f"(d[69]), "+f"(d[70]), "+f"(d[71]), "+f"(d[72]), "+f"(d[73]), "+f"(d[74]), "+f"(d[75]), "+f"(d[76]), "+f"(d[77]), "+f"(d[78]), "+f"(d[79]), "+f"(d[80]), "+f"(d[81]), "+f"(d[82]), "+f"(d[83]), "+f"(d[84]), "+f"(d[85]), "+f"(d[86]), "+f"(d[87]), "+f"(d[88]), "+f"(d[89]), "+f"(d[90]), "+f"(d[91]), "+f"(d[92]), "+f"(d[93]), "+f"(d[94]), "+f"(d[95])
    : "r"(a0), "r"(a1), "r"(a2), "r"(a3), "r"(b), "n"(BHI));
}
template<uint32_t BHI> __device__ __forceinline__ void wg_rs_z_n192(float* d, uint32_t a0, uint32_t a1, uint32_t a2, uint32_t a3, uint32_t b) {
  asm volatile("{\n.reg .pred p;\n.reg .b64 db;\nsetp.ne.b32 p, 0, 0;\nmov.b64 db, {%100, %101};\n"
    "wgmma.mma_async.sync.aligned.m64n192k16.f32.bf16.bf16 {%0, %1, %2, %3, %4, %5, %6, %7, %8, %9, %10, %11, %12, %13, %14, %15, %16, %17, %18, %19, %20, %21, %22, %23, %24, %25, %26, %27, %28, %29, %30, %31, %32, %33, %34, %35, %36, %37, %38, %39, %40, %41, %42, %43, %44, %45, %46, %47, %48, %49, %50, %51, %52, %53, %54, %55, %56, %57, %58, %59, %60, %61, %62, %63, %64, %65, %66, %67, %68, %69, %70, %71, %72, %73, %74, %75, %76, %77, %78, %79, %80, %81, %82, %83, %84, %85, %86, %87, %88, %89, %90, %91, %92, %93, %94, %95}, {%96, %97, %98, %99}, db, p, 1, 1, 1;\n}\n"
    : "=f"(d[0]), "=f"(d[1]), "=f"(d[2]), "=f"(d[3]), "=f"(d[4]), "=f"(d[5]), "=f"(d[6]), "=f"(d[7]), "=f"(d[8]), "=f"(d[9]), "=f"(d[10]), "=f"(d[11]), "=f"(d[12]), "=f"(d[13]), "=f"(d[14]), "=f"(d[15]), "=f"(d[16]), "=f"(d[17]), "=f"(d[18]), "=f"(d[19]), "=f"(d[20]), "=f"(d[21]), "=f"(d[22]), "=f"(d[23]), "=f"(d[24]), "=f"(d[25]), "=f"(d[26]), "=f"(d[27]), "=f"(d[28]), "=f"(d[29]), "=f"(d[30]), "=f"(d[31]), "=f"(d[32]), "=f"(d[33]), "=f"(d[34]), "=f"(d[35]), "=f"(d[36]), "=f"(d[37]), "=f"(d[38]), "=f"(d[39]), "=f"(d[40]), "=f"(d[41]), "=f"(d[42]), "=f"(d[43]), "=f"(d[44]), "=f"(d[45]), "=f"(d[46]), "=f"(d[47]), "=f"(d[48]), "=f"(d[49]), "=f"(d[50]), "=f"(d[51]), "=f"(d[52]), "=f"(d[53]), "=f"(d[54]), "=f"(d[55]), "=f"(d[56]), "=f"(d[57]), "=f"(d[58]), "=f"(d[59]), "=f"(d[60]), "=f"(d[61]), "=f"(d[62]), "=f"(d[63]), "=f"(d[64]), "=f"(d[65]), "=f"(d[66]), "=f"(d[67]), "=f"(d[68]), "=f"(d[69]), "=f"(d[70]), "=f"(d[71]), "=f"(d[72]), "=f"(d[73]), "=f"(d[74]), "=f"(d[75]), "=f"(d[76]), "=f"(d[77]), "=f"(d[78]), "=f"(d[79]), "=f"(d[80]), "=f"(d[81]), "=f"(d[82]), "=f"(d[83]), "=f"(d[84]), "=f"(d[85]), "=f"(d[86]), "=f"(d[87]), "=f"(d[88]), "=f"(d[89]), "=f"(d[90]), "=f"(d[91]), "=f"(d[92]), "=f"(d[93]), "=f"(d[94]), "=f"(d[95])
    : "r"(a0), "r"(a1), "r"(a2), "r"(a3), "r"(b), "n"(BHI));
}
template<uint32_t AHI, uint32_t BHI> __device__ __forceinline__ void wg_ss_n128(float* d, uint32_t a, uint32_t b) {
  asm volatile("{\n.reg .pred p;\n.reg .b64 da, db;\nsetp.ne.b32 p, 1, 0;\nmov.b64 da, {%64, %66};\nmov.b64 db, {%65, %67};\n"
    "wgmma.mma_async.sync.aligned.m64n128k16.f32.bf16.bf16 {%0, %1, %2, %3, %4, %5, %6, %7, %8, %9, %10, %11, %12, %13, %14, %15, %16, %17, %18, %19, %20, %21, %22, %23, %24, %25, %26, %27, %28, %29, %30, %31, %32, %33, %34, %35, %36, %37, %38, %39, %40, %41, %42, %43, %44, %45, %46, %47, %48, %49, %50, %51, %52, %53, %54, %55, %56, %57, %58, %59, %60, %61, %62, %63}, da, db, p, 1, 1, 0, 1;\n}\n"
    : "+f"(d[0]), "+f"(d[1]), "+f"(d[2]), "+f"(d[3]), "+f"(d[4]), "+f"(d[5]), "+f"(d[6]), "+f"(d[7]), "+f"(d[8]), "+f"(d[9]), "+f"(d[10]), "+f"(d[11]), "+f"(d[12]), "+f"(d[13]), "+f"(d[14]), "+f"(d[15]), "+f"(d[16]), "+f"(d[17]), "+f"(d[18]), "+f"(d[19]), "+f"(d[20]), "+f"(d[21]), "+f"(d[22]), "+f"(d[23]), "+f"(d[24]), "+f"(d[25]), "+f"(d[26]), "+f"(d[27]), "+f"(d[28]), "+f"(d[29]), "+f"(d[30]), "+f"(d[31]), "+f"(d[32]), "+f"(d[33]), "+f"(d[34]), "+f"(d[35]), "+f"(d[36]), "+f"(d[37]), "+f"(d[38]), "+f"(d[39]), "+f"(d[40]), "+f"(d[41]), "+f"(d[42]), "+f"(d[43]), "+f"(d[44]), "+f"(d[45]), "+f"(d[46]), "+f"(d[47]), "+f"(d[48]), "+f"(d[49]), "+f"(d[50]), "+f"(d[51]), "+f"(d[52]), "+f"(d[53]), "+f"(d[54]), "+f"(d[55]), "+f"(d[56]), "+f"(d[57]), "+f"(d[58]), "+f"(d[59]), "+f"(d[60]), "+f"(d[61]), "+f"(d[62]), "+f"(d[63])
    : "r"(a), "r"(b), "n"(AHI), "n"(BHI));
}
template<uint32_t AHI, uint32_t BHI> __device__ __forceinline__ void wg_ss_z_n128(float* d, uint32_t a, uint32_t b) {
  asm volatile("{\n.reg .pred p;\n.reg .b64 da, db;\nsetp.ne.b32 p, 0, 0;\nmov.b64 da, {%64, %66};\nmov.b64 db, {%65, %67};\n"
    "wgmma.mma_async.sync.aligned.m64n128k16.f32.bf16.bf16 {%0, %1, %2, %3, %4, %5, %6, %7, %8, %9, %10, %11, %12, %13, %14, %15, %16, %17, %18, %19, %20, %21, %22, %23, %24, %25, %26, %27, %28, %29, %30, %31, %32, %33, %34, %35, %36, %37, %38, %39, %40, %41, %42, %43, %44, %45, %46, %47, %48, %49, %50, %51, %52, %53, %54, %55, %56, %57, %58, %59, %60, %61, %62, %63}, da, db, p, 1, 1, 0, 1;\n}\n"
    : "=f"(d[0]), "=f"(d[1]), "=f"(d[2]), "=f"(d[3]), "=f"(d[4]), "=f"(d[5]), "=f"(d[6]), "=f"(d[7]), "=f"(d[8]), "=f"(d[9]), "=f"(d[10]), "=f"(d[11]), "=f"(d[12]), "=f"(d[13]), "=f"(d[14]), "=f"(d[15]), "=f"(d[16]), "=f"(d[17]), "=f"(d[18]), "=f"(d[19]), "=f"(d[20]), "=f"(d[21]), "=f"(d[22]), "=f"(d[23]), "=f"(d[24]), "=f"(d[25]), "=f"(d[26]), "=f"(d[27]), "=f"(d[28]), "=f"(d[29]), "=f"(d[30]), "=f"(d[31]), "=f"(d[32]), "=f"(d[33]), "=f"(d[34]), "=f"(d[35]), "=f"(d[36]), "=f"(d[37]), "=f"(d[38]), "=f"(d[39]), "=f"(d[40]), "=f"(d[41]), "=f"(d[42]), "=f"(d[43]), "=f"(d[44]), "=f"(d[45]), "=f"(d[46]), "=f"(d[47]), "=f"(d[48]), "=f"(d[49]), "=f"(d[50]), "=f"(d[51]), "=f"(d[52]), "=f"(d[53]), "=f"(d[54]), "=f"(d[55]), "=f"(d[56]), "=f"(d[57]), "=f"(d[58]), "=f"(d[59]), "=f"(d[60]), "=f"(d[61]), "=f"(d[62]), "=f"(d[63])
    : "r"(a), "r"(b), "n"(AHI), "n"(BHI));
}
template<uint32_t AHI, uint32_t BHI> __device__ __forceinline__ void wg_ss_n160(float* d, uint32_t a, uint32_t b) {
  asm volatile("{\n.reg .pred p;\n.reg .b64 da, db;\nsetp.ne.b32 p, 1, 0;\nmov.b64 da, {%80, %82};\nmov.b64 db, {%81, %83};\n"
    "wgmma.mma_async.sync.aligned.m64n160k16.f32.bf16.bf16 {%0, %1, %2, %3, %4, %5, %6, %7, %8, %9, %10, %11, %12, %13, %14, %15, %16, %17, %18, %19, %20, %21, %22, %23, %24, %25, %26, %27, %28, %29, %30, %31, %32, %33, %34, %35, %36, %37, %38, %39, %40, %41, %42, %43, %44, %45, %46, %47, %48, %49, %50, %51, %52, %53, %54, %55, %56, %57, %58, %59, %60, %61, %62, %63, %64, %65, %66, %67, %68, %69, %70, %71, %72, %73, %74, %75, %76, %77, %78, %79}, da, db, p, 1, 1, 0, 1;\n}\n"
    : "+f"(d[0]), "+f"(d[1]), "+f"(d[2]), "+f"(d[3]), "+f"(d[4]), "+f"(d[5]), "+f"(d[6]), "+f"(d[7]), "+f"(d[8]), "+f"(d[9]), "+f"(d[10]), "+f"(d[11]), "+f"(d[12]), "+f"(d[13]), "+f"(d[14]), "+f"(d[15]), "+f"(d[16]), "+f"(d[17]), "+f"(d[18]), "+f"(d[19]), "+f"(d[20]), "+f"(d[21]), "+f"(d[22]), "+f"(d[23]), "+f"(d[24]), "+f"(d[25]), "+f"(d[26]), "+f"(d[27]), "+f"(d[28]), "+f"(d[29]), "+f"(d[30]), "+f"(d[31]), "+f"(d[32]), "+f"(d[33]), "+f"(d[34]), "+f"(d[35]), "+f"(d[36]), "+f"(d[37]), "+f"(d[38]), "+f"(d[39]), "+f"(d[40]), "+f"(d[41]), "+f"(d[42]), "+f"(d[43]), "+f"(d[44]), "+f"(d[45]), "+f"(d[46]), "+f"(d[47]), "+f"(d[48]), "+f"(d[49]), "+f"(d[50]), "+f"(d[51]), "+f"(d[52]), "+f"(d[53]), "+f"(d[54]), "+f"(d[55]), "+f"(d[56]), "+f"(d[57]), "+f"(d[58]), "+f"(d[59]), "+f"(d[60]), "+f"(d[61]), "+f"(d[62]), "+f"(d[63]), "+f"(d[64]), "+f"(d[65]), "+f"(d[66]), "+f"(d[67]), "+f"(d[68]), "+f"(d[69]), "+f"(d[70]), "+f"(d[71]), "+f"(d[72]), "+f"(d[73]), "+f"(d[74]), "+f"(d[75]), "+f"(d[76]), "+f"(d[77]), "+f"(d[78]), "+f"(d[79])
    : "r"(a), "r"(b), "n"(AHI), "n"(BHI));
}
template<uint32_t AHI, uint32_t BHI> __device__ __forceinline__ void wg_ss_z_n160(float* d, uint32_t a, uint32_t b) {
  asm volatile("{\n.reg .pred p;\n.reg .b64 da, db;\nsetp.ne.b32 p, 0, 0;\nmov.b64 da, {%80, %82};\nmov.b64 db, {%81, %83};\n"
    "wgmma.mma_async.sync.aligned.m64n160k16.f32.bf16.bf16 {%0, %1, %2, %3, %4, %5, %6, %7, %8, %9, %10, %11, %12, %13, %14, %15, %16, %17, %18, %19, %20, %21, %22, %23, %24, %25, %26, %27, %28, %29, %30, %31, %32, %33, %34, %35, %36, %37, %38, %39, %40, %41, %42, %43, %44, %45, %46, %47, %48, %49, %50, %51, %52, %53, %54, %55, %56, %57, %58, %59, %60, %61, %62, %63, %64, %65, %66, %67, %68, %69, %70, %71, %72, %73, %74, %75, %76, %77, %78, %79}, da, db, p, 1, 1, 0, 1;\n}\n"
    : "=f"(d[0]), "=f"(d[1]), "=f"(d[2]), "=f"(d[3]), "=f"(d[4]), "=f"(d[5]), "=f"(d[6]), "=f"(d[7]), "=f"(d[8]), "=f"(d[9]), "=f"(d[10]), "=f"(d[11]), "=f"(d[12]), "=f"(d[13]), "=f"(d[14]), "=f"(d[15]), "=f"(d[16]), "=f"(d[17]), "=f"(d[18]), "=f"(d[19]), "=f"(d[20]), "=f"(d[21]), "=f"(d[22]), "=f"(d[23]), "=f"(d[24]), "=f"(d[25]), "=f"(d[26]), "=f"(d[27]), "=f"(d[28]), "=f"(d[29]), "=f"(d[30]), "=f"(d[31]), "=f"(d[32]), "=f"(d[33]), "=f"(d[34]), "=f"(d[35]), "=f"(d[36]), "=f"(d[37]), "=f"(d[38]), "=f"(d[39]), "=f"(d[40]), "=f"(d[41]), "=f"(d[42]), "=f"(d[43]), "=f"(d[44]), "=f"(d[45]), "=f"(d[46]), "=f"(d[47]), "=f"(d[48]), "=f"(d[49]), "=f"(d[50]), "=f"(d[51]), "=f"(d[52]), "=f"(d[53]), "=f"(d[54]), "=f"(d[55]), "=f"(d[56]), "=f"(d[57]), "=f"(d[58]), "=f"(d[59]), "=f"(d[60]), "=f"(d[61]), "=f"(d[62]), "=f"(d[63]), "=f"(d[64]), "=f"(d[65]), "=f"(d[66]), "=f"(d[67]), "=f"(d[68]), "=f"(d[69]), "=f"(d[70]), "=f"(d[71]), "=f"(d[72]), "=f"(d[73]), "=f"(d[74]), "=f"(d[75]), "=f"(d[76]), "=f"(d[77]), "=f"(d[78]), "=f"(d[79])
    : "r"(a), "r"(b), "n"(AHI), "n"(BHI));
}
template<uint32_t BHI> __device__ __forceinline__ void wg_rs_n32(float* d, uint32_t a0, uint32_t a1, uint32_t a2, uint32_t a3, uint32_t b) {
  asm volatile("{\n.reg .pred p;\n.reg .b64 db;\nsetp.ne.b32 p, 1, 0;\nmov.b64 db, {%20, %21};\n"
    "wgmma.mma_async.sync.aligned.m64n32k16.f32.bf16.bf16 {%0, %1, %2, %3, %4, %5, %6, %7, %8, %9, %10, %11, %12, %13, %14, %15}, {%16, %17, %18, %19}, db, p, 1, 1, 1;\n}\n"
    : "+f"(d[0]), "+f"(d[1]), "+f"(d[2]), "+f"(d[3]), "+f"(d[4]), "+f"(d[5]), "+f"(d[6]), "+f"(d[7]), "+f"(d[8]), "+f"(d[9]), "+f"(d[10]), "+f"(d[11]), "+f"(d[12]), "+f"(d[13]), "+f"(d[14]), "+f"(d[15])
    : "r"(a0), "r"(a1), "r"(a2), "r"(a3), "r"(b), "n"(BHI));
}
template<uint32_t BHI> __device__ __forceinline__ void wg_rs_z_n32(float* d, uint32_t a0, uint32_t a1, uint32_t a2, uint32_t a3, uint32_t b) {
  asm volatile("{\n.reg .pred p;\n.reg .b64 db;\nsetp.ne.b32 p, 0, 0;\nmov.b64 db, {%20, %21};\n"
    "wgmma.mma_async.sync.aligned.m64n32k16.f32.bf16.bf16 {%0, %1, %2, %3, %4, %5, %6, %7, %8, %9, %10, %11, %12, %13, %14, %15}, {%16, %17, %18, %19}, db, p, 1, 1, 1;\n}\n"
    : "=f"(d[0]), "=f"(d[1]), "=f"(d[2]), "=f"(d[3]), "=f"(d[4]), "=f"(d[5]), "=f"(d[6]), "=f"(d[7]), "=f"(d[8]), "=f"(d[9]), "=f"(d[10]), "=f"(d[11]), "=f"(d[12]), "=f"(d[13]), "=f"(d[14]), "=f"(d[15])
    : "r"(a0), "r"(a1), "r"(a2), "r"(a3), "r"(b), "n"(BHI));
}
template<uint32_t BHI> __device__ __forceinline__ void wg_rs_n64(float* d, uint32_t a0, uint32_t a1, uint32_t a2, uint32_t a3, uint32_t b) {
  asm volatile("{\n.reg .pred p;\n.reg .b64 db;\nsetp.ne.b32 p, 1, 0;\nmov.b64 db, {%36, %37};\n"
    "wgmma.mma_async.sync.aligned.m64n64k16.f32.bf16.bf16 {%0, %1, %2, %3, %4, %5, %6, %7, %8, %9, %10, %11, %12, %13, %14, %15, %16, %17, %18, %19, %20, %21, %22, %23, %24, %25, %26, %27, %28, %29, %30, %31}, {%32, %33, %34, %35}, db, p, 1, 1, 0;\n}\n"
    : "+f"(d[0]), "+f"(d[1]), "+f"(d[2]), "+f"(d[3]), "+f"(d[4]), "+f"(d[5]), "+f"(d[6]), "+f"(d[7]), "+f"(d[8]), "+f"(d[9]), "+f"(d[10]), "+f"(d[11]), "+f"(d[12]), "+f"(d[13]), "+f"(d[14]), "+f"(d[15]), "+f"(d[16]), "+f"(d[17]), "+f"(d[18]), "+f"(d[19]), "+f"(d[20]), "+f"(d[21]), "+f"(d[22]), "+f"(d[23]), "+f"(d[24]), "+f"(d[25]), "+f"(d[26]), "+f"(d[27]), "+f"(d[28]), "+f"(d[29]), "+f"(d[30]), "+f"(d[31])
    : "r"(a0), "r"(a1), "r"(a2), "r"(a3), "r"(b), "n"(BHI));
}
template<uint32_t BHI> __device__ __forceinline__ void wg_rs_z_n64(float* d, uint32_t a0, uint32_t a1, uint32_t a2, uint32_t a3, uint32_t b) {
  asm volatile("{\n.reg .pred p;\n.reg .b64 db;\nsetp.ne.b32 p, 0, 0;\nmov.b64 db, {%36, %37};\n"
    "wgmma.mma_async.sync.aligned.m64n64k16.f32.bf16.bf16 {%0, %1, %2, %3, %4, %5, %6, %7, %8, %9, %10, %11, %12, %13, %14, %15, %16, %17, %18, %19, %20, %21, %22, %23, %24, %25, %26, %27, %28, %29, %30, %31}, {%32, %33, %34, %35}, db, p, 1, 1, 0;\n}\n"
    : "=f"(d[0]), "=f"(d[1]), "=f"(d[2]), "=f"(d[3]), "=f"(d[4]), "=f"(d[5]), "=f"(d[6]), "=f"(d[7]), "=f"(d[8]), "=f"(d[9]), "=f"(d[10]), "=f"(d[11]), "=f"(d[12]), "=f"(d[13]), "=f"(d[14]), "=f"(d[15]), "=f"(d[16]), "=f"(d[17]), "=f"(d[18]), "=f"(d[19]), "=f"(d[20]), "=f"(d[21]), "=f"(d[22]), "=f"(d[23]), "=f"(d[24]), "=f"(d[25]), "=f"(d[26]), "=f"(d[27]), "=f"(d[28]), "=f"(d[29]), "=f"(d[30]), "=f"(d[31])
    : "r"(a0), "r"(a1), "r"(a2), "r"(a3), "r"(b), "n"(BHI));
}
template<uint32_t BHI> __device__ __forceinline__ void wg_rs_n24(float* d, uint32_t a0, uint32_t a1, uint32_t a2, uint32_t a3, uint32_t b) {
  asm volatile("{\n.reg .pred p;\n.reg .b64 db;\nsetp.ne.b32 p, 1, 0;\nmov.b64 db, {%16, %17};\n"
    "wgmma.mma_async.sync.aligned.m64n24k16.f32.bf16.bf16 {%0, %1, %2, %3, %4, %5, %6, %7, %8, %9, %10, %11}, {%12, %13, %14, %15}, db, p, 1, 1, 1;\n}\n"
    : "+f"(d[0]), "+f"(d[1]), "+f"(d[2]), "+f"(d[3]), "+f"(d[4]), "+f"(d[5]), "+f"(d[6]), "+f"(d[7]), "+f"(d[8]), "+f"(d[9]), "+f"(d[10]), "+f"(d[11])
    : "r"(a0), "r"(a1), "r"(a2), "r"(a3), "r"(b), "n"(BHI));
}
template<uint32_t BHI> __device__ __forceinline__ void wg_rs_z_n24(float* d, uint32_t a0, uint32_t a1, uint32_t a2, uint32_t a3, uint32_t b) {
  asm volatile("{\n.reg .pred p;\n.reg .b64 db;\nsetp.ne.b32 p, 0, 0;\nmov.b64 db, {%16, %17};\n"
    "wgmma.mma_async.sync.aligned.m64n24k16.f32.bf16.bf16 {%0, %1, %2, %3, %4, %5, %6, %7, %8, %9, %10, %11}, {%12, %13, %14, %15}, db, p, 1, 1, 1;\n}\n"
    : "=f"(d[0]), "=f"(d[1]), "=f"(d[2]), "=f"(d[3]), "=f"(d[4]), "=f"(d[5]), "=f"(d[6]), "=f"(d[7]), "=f"(d[8]), "=f"(d[9]), "=f"(d[10]), "=f"(d[11])
    : "r"(a0), "r"(a1), "r"(a2), "r"(a3), "r"(b), "n"(BHI));
}
template<uint32_t BHI> __device__ __forceinline__ void wg_rsb_n64(float* d, uint32_t a0, uint32_t a1, uint32_t a2, uint32_t a3, uint32_t b) {
  asm volatile("{\n.reg .pred p;\n.reg .b64 db;\nsetp.ne.b32 p, 1, 0;\nmov.b64 db, {%36, %37};\n"
    "wgmma.mma_async.sync.aligned.m64n64k16.f32.bf16.bf16 {%0, %1, %2, %3, %4, %5, %6, %7, %8, %9, %10, %11, %12, %13, %14, %15, %16, %17, %18, %19, %20, %21, %22, %23, %24, %25, %26, %27, %28, %29, %30, %31}, {%32, %33, %34, %35}, db, p, 1, 1, 1;\n}\n"
    : "+f"(d[0]), "+f"(d[1]), "+f"(d[2]), "+f"(d[3]), "+f"(d[4]), "+f"(d[5]), "+f"(d[6]), "+f"(d[7]), "+f"(d[8]), "+f"(d[9]), "+f"(d[10]), "+f"(d[11]), "+f"(d[12]), "+f"(d[13]), "+f"(d[14]), "+f"(d[15]), "+f"(d[16]), "+f"(d[17]), "+f"(d[18]), "+f"(d[19]), "+f"(d[20]), "+f"(d[21]), "+f"(d[22]), "+f"(d[23]), "+f"(d[24]), "+f"(d[25]), "+f"(d[26]), "+f"(d[27]), "+f"(d[28]), "+f"(d[29]), "+f"(d[30]), "+f"(d[31])
    : "r"(a0), "r"(a1), "r"(a2), "r"(a3), "r"(b), "n"(BHI));
}
template<uint32_t BHI> __device__ __forceinline__ void wg_rsb_z_n64(float* d, uint32_t a0, uint32_t a1, uint32_t a2, uint32_t a3, uint32_t b) {
  asm volatile("{\n.reg .pred p;\n.reg .b64 db;\nsetp.ne.b32 p, 0, 0;\nmov.b64 db, {%36, %37};\n"
    "wgmma.mma_async.sync.aligned.m64n64k16.f32.bf16.bf16 {%0, %1, %2, %3, %4, %5, %6, %7, %8, %9, %10, %11, %12, %13, %14, %15, %16, %17, %18, %19, %20, %21, %22, %23, %24, %25, %26, %27, %28, %29, %30, %31}, {%32, %33, %34, %35}, db, p, 1, 1, 1;\n}\n"
    : "=f"(d[0]), "=f"(d[1]), "=f"(d[2]), "=f"(d[3]), "=f"(d[4]), "=f"(d[5]), "=f"(d[6]), "=f"(d[7]), "=f"(d[8]), "=f"(d[9]), "=f"(d[10]), "=f"(d[11]), "=f"(d[12]), "=f"(d[13]), "=f"(d[14]), "=f"(d[15]), "=f"(d[16]), "=f"(d[17]), "=f"(d[18]), "=f"(d[19]), "=f"(d[20]), "=f"(d[21]), "=f"(d[22]), "=f"(d[23]), "=f"(d[24]), "=f"(d[25]), "=f"(d[26]), "=f"(d[27]), "=f"(d[28]), "=f"(d[29]), "=f"(d[30]), "=f"(d[31])
    : "r"(a0), "r"(a1), "r"(a2), "r"(a3), "r"(b), "n"(BHI));
}

__device__ __forceinline__ void wg_fence() { asm volatile("wgmma.fence.sync.aligned;" ::: "memory"); }
__device__ __forceinline__ void wg_commit() { asm volatile("wgmma.commit_group.sync.aligned;" ::: "memory"); }
template <int N> __device__ __forceinline__ void wg_wait() { asm volatile("wgmma.wait_group.sync.aligned %0;" ::"n"(N) : "memory"); }
template <int R> __device__ __forceinline__ void pin(float* d) {
#pragma unroll
  for (int i = 0; i < R; i++) asm volatile("" : "+f"(d[i])::"memory");
}
template <int R> __device__ __forceinline__ void pin(uint32_t* d) {
#pragma unroll
  for (int i = 0; i < R; i++) asm volatile("" : "+r"(d[i])::"memory");
}
__device__ __forceinline__ float ex2(float x) { float y; asm("ex2.approx.ftz.f32 %0, %1;" : "=f"(y) : "f"(x)); return y; }
__device__ __forceinline__ float tanh_fast(float x) { float y; asm("tanh.approx.f32 %0, %1;" : "=f"(y) : "f"(x)); return y; }
__device__ __forceinline__ uint32_t pack(float lo, float hi) { uint32_t r; asm("cvt.rn.bf16x2.f32 %0, %1, %2;" : "=r"(r) : "f"(hi), "f"(lo)); return r; }
__device__ __forceinline__ float bf_lo(uint32_t v) { return __uint_as_float(v << 16); }
__device__ __forceinline__ float bf_hi(uint32_t v) { return __uint_as_float(v & 0xffff0000u); }
__device__ __forceinline__ float bf_round(float x) { return bf_lo(pack(x, 0.f)); }

__device__ __forceinline__ void mbar_init(uint32_t bar, uint32_t cnt) { asm volatile("mbarrier.init.shared::cta.b64 [%0], %1;" ::"r"(bar), "r"(cnt) : "memory"); }
__device__ __forceinline__ void mbar_expect(uint32_t bar, uint32_t bytes) { asm volatile("mbarrier.arrive.expect_tx.shared::cta.b64 _, [%0], %1;" ::"r"(bar), "r"(bytes) : "memory"); }
__device__ __forceinline__ void mbar_wait(uint32_t bar, uint32_t parity) {
  asm volatile(
      "{\n.reg .pred p;\n.reg .u32 c;\n"
      "mbarrier.try_wait.parity.shared::cta.b64 p, [%0], %1;\n"
      "@p bra.uni DONE;\n"
      "mov.u32 c, 0;\n"
      "LOOP:\n"
      "mbarrier.try_wait.parity.shared::cta.b64 p, [%0], %1;\n"
      "@p bra.uni DONE;\n"
      "add.u32 c, c, 1;\n"
      "setp.lt.u32 p, c, 0x400000;\n"
      "@p bra.uni LOOP;\n"
      "trap;\n"
      "DONE:\n}\n" ::"r"(bar), "r"(parity) : "memory");
}
__device__ __forceinline__ uint32_t mbar_test(uint32_t bar, uint32_t parity) {
  uint32_t ok;
  asm volatile("{\n.reg .pred p;\nmbarrier.test_wait.parity.shared::cta.b64 p, [%1], %2;\nselp.u32 %0, 1, 0, p;\n}\n" : "=r"(ok) : "r"(bar), "r"(parity) : "memory");
  return ok;
}
__device__ __forceinline__ void mbar_arrive_if(uint32_t bar, uint32_t cond) {
  asm volatile("{\n.reg .pred p;\nsetp.ne.u32 p, %1, 0;\n@p mbarrier.arrive.shared::cta.b64 _, [%0];\n}\n" ::"r"(bar), "r"(cond) : "memory");
}
__device__ __forceinline__ uint32_t bsub2(uint32_t a, uint32_t b) { uint32_t d; asm("sub.rn.bf16x2 %0, %1, %2;" : "=r"(d) : "r"(a), "r"(b)); return d; }
__device__ __forceinline__ uint32_t bscale2(uint32_t d, uint32_t hi, uint32_t lo) {
  uint32_t t, r;
  asm("mul.rn.bf16x2 %0, %1, %2;" : "=r"(t) : "r"(d), "r"(lo));
  asm("fma.rn.bf16x2 %0, %1, %2, %3;" : "=r"(r) : "r"(d), "r"(hi), "r"(t));
  return r;
}
__device__ __forceinline__ void flag_wait(const uint32_t* f, uint32_t target) {
  asm volatile(
      "{\n.reg .pred p;\n.reg .u32 c, v;\n"
      "mov.u32 c, 0;\n"
      "LOOP:\n"
      "ld.acquire.gpu.global.u32 v, [%0];\n"
      "sub.u32 v, v, %1;\n"
      "setp.ge.s32 p, v, 0;\n"
      "@p bra DONE;\n"
      "add.u32 c, c, 1;\n"
      "setp.lt.u32 p, c, 0x400000;\n"
      "@p bra LOOP;\n"
      "trap;\n"
      "DONE:\n}\n" ::"l"(f), "r"(target) : "memory");
}
__device__ __forceinline__ uint32_t flag_wait_v(const uint32_t* f, uint32_t target) {
  uint32_t v;
  asm volatile(
      "{\n.reg .pred p;\n.reg .u32 c, d;\n"
      "mov.u32 c, 0;\n"
      "LOOP:\n"
      "ld.acquire.gpu.global.u32 %0, [%1];\n"
      "sub.u32 d, %0, %2;\n"
      "setp.ge.s32 p, d, 0;\n"
      "@p bra DONE;\n"
      "add.u32 c, c, 1;\n"
      "setp.lt.u32 p, c, 0x400000;\n"
      "@p bra LOOP;\n"
      "trap;\n"
      "DONE:\n}\n" : "=&r"(v) : "l"(f), "r"(target) : "memory");
  return v;
}
__device__ __forceinline__ float sqrt_fast(float x) { float y; asm("sqrt.approx.f32 %0, %1;" : "=f"(y) : "f"(x)); return y; }
__device__ __forceinline__ float rcp_fast(float x) { float y; asm("rcp.approx.ftz.f32 %0, %1;" : "=f"(y) : "f"(x)); return y; }
__device__ __forceinline__ void ldsm4(uint32_t* v, uint32_t addr) {
  asm volatile("ldmatrix.sync.aligned.m8n8.x4.shared.b16 {%0,%1,%2,%3}, [%4];" : "=r"(v[0]), "=r"(v[1]), "=r"(v[2]), "=r"(v[3]) : "r"(addr) : "memory");
}
__device__ __forceinline__ void stsm4(uint32_t addr, uint32_t a, uint32_t b, uint32_t c, uint32_t d) {
  asm volatile("stmatrix.sync.aligned.m8n8.x4.shared.b16 [%0], {%1,%2,%3,%4};" ::"r"(addr), "r"(a), "r"(b), "r"(c), "r"(d) : "memory");
}
__device__ __forceinline__ void flag_add(uint32_t* f) { asm volatile("red.relaxed.gpu.global.add.u32 [%0], 1;" ::"l"(f) : "memory"); }
__device__ __forceinline__ void fence_gpu() { asm volatile("fence.acq_rel.gpu;" ::: "memory"); }
__device__ __forceinline__ void fence_async() { asm volatile("fence.proxy.async.global;" ::: "memory"); }
__device__ __forceinline__ void tma2d(uint32_t dst, const CUtensorMap* tm, uint32_t bar, int c0, int c1) {
  asm volatile("cp.async.bulk.tensor.2d.shared::cluster.global.mbarrier::complete_tx::bytes [%0], [%1, {%3, %4}], [%2];" ::"r"(dst), "l"(tm), "r"(bar), "r"(c0), "r"(c1) : "memory");
}
__device__ __forceinline__ void tma2d_h(uint32_t dst, const CUtensorMap* tm, uint32_t bar, int c0, int c1, uint64_t pol) {
  asm volatile("cp.async.bulk.tensor.2d.shared::cluster.global.mbarrier::complete_tx::bytes.L2::cache_hint [%0], [%1, {%3, %4}], [%2], %5;" ::"r"(dst), "l"(tm), "r"(bar), "r"(c0), "r"(c1), "l"(pol) : "memory");
}
__device__ __forceinline__ void bulk_s2g(void* dst, uint32_t src, uint32_t bytes) {
  asm volatile("cp.async.bulk.global.shared::cta.bulk_group [%0], [%1], %2;" ::"l"(dst), "r"(src), "r"(bytes) : "memory");
}
__device__ __forceinline__ void mma_ones(float* c, const uint32_t* a) {
  asm("mma.sync.aligned.m16n8k16.row.col.f32.bf16.bf16.f32 {%0,%1,%2,%3}, {%4,%5,%6,%7}, {%8,%8}, {%0,%1,%2,%3};"
      : "+f"(c[0]), "+f"(c[1]), "+f"(c[2]), "+f"(c[3]) : "r"(a[0]), "r"(a[1]), "r"(a[2]), "r"(a[3]), "r"(0x3f803f80u));
}
__device__ __forceinline__ void tma5d(uint32_t dst, const CUtensorMap* tm, uint32_t bar, int c0, int c4) {
  asm volatile("cp.async.bulk.tensor.5d.shared::cluster.global.mbarrier::complete_tx::bytes [%0], [%1, {%3, %5, %5, %5, %4}], [%2];" ::"r"(dst), "l"(tm), "r"(bar), "r"(c0), "r"(c4), "r"(0) : "memory");
}
__device__ __forceinline__ void tma3d(uint32_t dst, const CUtensorMap* tm, uint32_t bar, int c0, int c2) {
  asm volatile("cp.async.bulk.tensor.3d.shared::cluster.global.mbarrier::complete_tx::bytes [%0], [%1, {%3, %5, %4}], [%2];" ::"r"(dst), "l"(tm), "r"(bar), "r"(c0), "r"(c2), "r"(0) : "memory");
}
__device__ __forceinline__ void bulk_g2s(uint32_t dst, const void* src, uint32_t bytes, uint32_t bar) {
  asm volatile("cp.async.bulk.shared::cluster.global.mbarrier::complete_tx::bytes [%0], [%1], %2, [%3];" ::"r"(dst), "l"(src), "r"(bytes), "r"(bar) : "memory");
}
__device__ __forceinline__ void pf_line(const void* p) { asm volatile("prefetch.global.L2 [%0];" ::"l"(p) : "memory"); }
__device__ __forceinline__ int fresh_tid() { int v; asm volatile("mov.u32 %0, %%tid.x;" : "=r"(v)); return v; }
struct Att {
  float s[32];
  float o[12];
  uint32_t p[16];
  uint32_t q[8];
};

__device__ __forceinline__ float warp_sum(float v) {
#pragma unroll 1
  for (int d = 16; d; d >>= 1) v += __shfl_xor_sync(0xffffffffu, v, d);
  return v;
}
#define OPAQUE(x) asm volatile("" : "+r"(x))
__device__ __forceinline__ void attn_slow_row(int cta, uint32_t& w) {
  float mx = -INFINITY;
#pragma unroll 1
  for (uint32_t key = threadIdx.x & 31; key < SEQ; key += 32) {
    float s = 0.f;
#pragma unroll 1
    for (uint32_t v = 0; v < 9; v++) {
      OPAQUE(w); OPAQUE(key);
      const uint32_t hp = (w >> 4) & 3, pos = (v + hp) & 3;
      const uint32_t q = g_Q[(cta * 4 + hp) * 1152 + ((w >> 3) & 1) + (v < 8 ? (((w >> 6) & 7) * 32 + (w & 7) * 4 + pos) * 4 + 2 * (v >> 2) : 1024 + (((w >> 6) & 7) * 8 + (w & 7)) * 2)];
      const uint32_t u = g_KV[(4 * (cta & 7) + hp) * SEQ * 20 + (key >> 3) * 160 + (key & 7) * 4 + (v >> 2) * 32 + pos];
      s = fmaf(bf_lo(q), bf_lo(u), fmaf(bf_hi(q), bf_hi(u), s));
    }
    g_S[(cta * 8 + ((w >> 6) & 7)) * SEQ + key] = s;
    mx = fmaxf(mx, s);
  }
#pragma unroll 1
  for (int d = 16; d; d >>= 1) mx = fmaxf(mx, __shfl_xor_sync(0xffffffffu, mx, d));
  float l = 0.f;
#pragma unroll 1
  for (uint32_t key = threadIdx.x & 31; key < SEQ; key += 32) l += ex2(g_S[(cta * 8 + ((w >> 6) & 7)) * SEQ + key] - mx);
  l = 2.f * rcp_fast(warp_sum(l));
#pragma unroll 1
  for (uint32_t v = w >> 9; v < 9; v++) {
    float a = 0.f, b = 0.f;
#pragma unroll 1
    for (uint32_t key = threadIdx.x & 31; key < SEQ; key += 32) {
      OPAQUE(w); OPAQUE(v);
      const uint32_t hp = (w >> 4) & 3;
      const uint32_t u = g_KV[(4 * (cta & 7) + hp) * SEQ * 20 + (key >> 3) * 160 + (key & 7) * 4 + (v < 8 ? (3 + (v >> 2)) * 32 + (v & 3) : 64 + ((hp + 2) & 3))];
      const float p = ex2(g_S[(cta * 8 + ((w >> 6) & 7)) * SEQ + key] - mx);
      a = fmaf(p, bf_lo(u), a); b = fmaf(p, bf_hi(u), b);
    }
    a = warp_sum(a); b = warp_sum(b);
    OPAQUE(w);
    const uint32_t hp = (w >> 4) & 3;
    if ((threadIdx.x & 31) == 0) g_O[cta * 9 * 512 + (((w >> 6) & 7) * 16 + (w & 15)) * 4 + (v < 8 ? (2 * hp + (v >> 2)) * 512 + (v & 3) : 8 * 512 + hp)] = pack(a * l, b * l);
  }
}

__device__ __forceinline__ uint32_t bad_heads(uint32_t bad_addr, int wr) {
  uint32_t bad;
  __syncwarp();
  asm volatile("ld.volatile.shared.u32 %0, [%1];" : "=r"(bad) : "r"(bad_addr) : "memory");
  return __shfl_sync(0xffffffffu, (bad >> (4 * wr)) & 15, 0);
}
__device__ __forceinline__ void repair_rows(int cta, int wr, uint32_t bad, int last_head, bool final) {
#pragma unroll 1
  for (uint32_t w = wr * 64; w < wr * 64 + 64; w++) {
    if (!((bad >> ((w >> 4) & 3)) & 1)) continue;
    if (final && ((w >> 4) & 3) != last_head) w |= 8u << 9;
    attn_slow_row(cta, w);
    w &= 511;
  }
  __syncwarp();
}
__device__ __forceinline__ void o_normalise(const float* o, uint32_t* w, uint32_t& x0, uint32_t& x1, int hp, int lane, uint32_t bad_addr, int wr) {
  const int src = (lane & ~3) | ((hp + 1) & 3);
  float l0 = __shfl_sync(0xffffffffu, o[0], src), l1 = __shfl_sync(0xffffffffu, o[2], src);
  float sa = 0.f;
#pragma unroll
  for (int i = 0; i < 12; i++) sa += fabsf(o[i]);
  bool ok = (l0 <= 1.329228e36f) && (l1 <= 1.329228e36f) && (l0 > 0.f) && (l1 > 0.f) && (sa <= 3.0e38f);
  float i0 = 2.f * rcp_fast(l0), i1 = 2.f * rcp_fast(l1);
  w[0] = pack(o[4] * i0, o[5] * i0);
  w[1] = pack(o[6] * i1, o[7] * i1);
  w[2] = pack(o[8] * i0, o[9] * i0);
  w[3] = pack(o[10] * i1, o[11] * i1);
  if ((lane & 3) == ((hp + 2) & 3)) { x0 = pack(o[0] * i0, o[1] * i0); x1 = pack(o[2] * i1, o[3] * i1); }
  if (!ok) asm volatile("red.shared.or.b32 [%0], %1;" ::"r"(bad_addr), "r"(1u << (4 * wr + hp)) : "memory");
}

__device__ __forceinline__ void issue_pv(Att& a, uint32_t kdesc) {
  const uint32_t vdesc = kdesc + 192 + (LO_V - LO_K);
#pragma unroll
  for (int k = 0; k < 4; k++) wg_rs_n24<HI_V>(a.o, a.p[4 * k], a.p[4 * k + 1], a.p[4 * k + 2], a.p[4 * k + 3], vdesc + k * 48);
}
__device__ __forceinline__ void issue_att(Att& a, uint32_t kdesc) {
  issue_pv(a, kdesc);
  wg_rs_z_n64<HI_K>(a.s, a.q[0], a.q[1], a.q[2], a.q[3], kdesc);
  wg_rs_n64<HI_K>(a.s, a.q[4], a.q[5], a.q[6], a.q[7], kdesc + 16);
}
__device__ __forceinline__ void softmax_a(Att& a) {
#pragma unroll
  for (int i = 0; i < SM_B; i++) a.p[i] = pack(ex2(a.s[2 * i]), ex2(a.s[2 * i + 1]));
  a.s[2 * SM_B] = ex2(a.s[2 * SM_B]); a.s[2 * SM_B + 1] = ex2(a.s[2 * SM_B + 1]);
  pin<SM_B>(a.p); pin<2>(a.s + 2 * SM_B);
}
__device__ __forceinline__ void softmax_b(Att& a) {
  a.p[SM_B] = pack(a.s[2 * SM_B], a.s[2 * SM_B + 1]);
#pragma unroll
  for (int i = SM_B + 1; i < 16; i++) a.p[i] = pack(ex2(a.s[2 * i]), ex2(a.s[2 * i + 1]));
  pin<16 - SM_B>(a.p + SM_B);
}
__device__ __forceinline__ void first_tile(Att& a, int hp, int lane) {
  float m0 = fmaxf(a.s[0], a.s[1]), m1 = fmaxf(a.s[2], a.s[3]);
#pragma unroll
  for (int i = 4; i < 32; i += 4) { m0 = fmaxf(m0, fmaxf(a.s[i], a.s[i + 1])); m1 = fmaxf(m1, fmaxf(a.s[i + 2], a.s[i + 3])); }
  m0 = fmaxf(m0, __shfl_xor_sync(0xffffffffu, m0, 1)); m1 = fmaxf(m1, __shfl_xor_sync(0xffffffffu, m1, 1));
  m0 = fmaxf(m0, __shfl_xor_sync(0xffffffffu, m0, 2)); m1 = fmaxf(m1, __shfl_xor_sync(0xffffffffu, m1, 2));
  float n0 = -(m0 + MOFF), n1 = -(m1 + MOFF);
  float h0 = bf_round(n0), h1 = bf_round(n1);
  uint32_t e0 = pack(h0, n0 - h0), e1 = pack(h1, n1 - h1);
  n0 = h0 + bf_hi(e0); n1 = h1 + bf_hi(e1);
  if ((lane & 3) == ((hp + 1) & 3)) { a.q[4] = e0; a.q[5] = e1; }
#pragma unroll
  for (int i = 0; i < 32; i += 4) { a.s[i] += n0; a.s[i + 1] += n0; a.s[i + 2] += n1; a.s[i + 3] += n1; }
#pragma unroll
  for (int i = 0; i < 12; i++) a.o[i] = 0.f;
  pin<12>(a.o); pin<8>(a.q);
}
__device__ __forceinline__ void fetch_q(uint32_t* q, int cta, int hp, int tid) {
  const uint32_t* src = g_Q + (cta * 4 + hp) * 1152;
  const uint4 u = __ldcg(reinterpret_cast<const uint4*>(src) + tid);
  uint2 v = make_uint2(0u, 0u);
  if ((tid & 3) == hp) v = __ldcg(reinterpret_cast<const uint2*>(src + 1024) + (tid >> 2));
  q[0] = u.x; q[1] = u.y; q[2] = u.z; q[3] = u.w; q[4] = v.x; q[5] = v.y;
}
__device__ __forceinline__ void store_q(const uint32_t* q, int cta, int hp, int tid) {
  uint32_t* dst = g_Q + (cta * 4 + hp) * 1152;
  reinterpret_cast<uint4*>(dst)[tid] = make_uint4(q[0], q[1], q[2], q[3]);
  if ((tid & 3) == hp) reinterpret_cast<uint2*>(dst + 1024)[tid >> 2] = make_uint2(q[4], q[5]);
}
__device__ __forceinline__ void h_epilogue(const float* acc, uint32_t* dst) {
#pragma unroll
  for (int b = 0; b < 4; b++) {
    uint32_t w[2][2];
#pragma unroll
    for (int i = 0; i < 2; i++) {
      float h[4];
#pragma unroll
      for (int e = 0; e < 4; e++) {
        const float g = acc[(2 * b + i) * 4 + e], u = acc[32 + (2 * b + i) * 4 + e];
        h[e] = fmaf(tanh_fast(0.5f * g), u, u);
      }
      w[0][i] = pack(h[0], h[1]); w[1][i] = pack(h[2], h[3]);
    }
    *reinterpret_cast<uint2*>(dst + 1024 * b) = make_uint2(w[0][0], w[0][1]);
    *reinterpret_cast<uint2*>(dst + 1024 * b + 32) = make_uint2(w[1][0], w[1][1]);
  }
}
__device__ __forceinline__ void rotate9(uint32_t (&v)[9][2]) {
#pragma unroll
  for (int rh = 0; rh < 2; rh++) {
    const uint32_t r = v[8][rh];
#pragma unroll
    for (int i = 8; i > 0; i--) v[i][rh] = v[i - 1][rh];
    v[0][rh] = r;
  }
}
template <int HP> __device__ __forceinline__ void store_kv_head(uint32_t (&pk)[2][9][2], uint32_t* kvp, int lane, uint32_t sk = 0, uint32_t sv = 0) {
  const int t = lane & 3, dv = ((t - HP) & 3) - t;
  const bool up = t < HP;
#pragma unroll
  for (int rh = 0; rh < 2; rh++) {
    uint32_t* d = kvp + HP * SEQ * 20 + rh * 160;
    const uint32_t c0 = up ? pk[0][2 * HP + 1][rh] : pk[0][2 * HP][rh], c1 = up ? pk[0][2 * HP + 2][rh] : pk[0][2 * HP + 1][rh];
    const uint32_t c3 = up ? pk[1][2 * HP + 1][rh] : pk[1][2 * HP][rh], c4 = up ? pk[1][2 * HP + 2][rh] : pk[1][2 * HP + 1][rh];
    const uint32_t v9 = __shfl_sync(0xffffffffu, pk[1][2 * HP + 2][rh], (lane & ~3) | HP);
    const uint32_t c2 = t == HP ? pk[0][2 * HP + 2][rh] : t == ((HP + 1) & 3) ? 0x3f803f80u : t == ((HP + 2) & 3) ? v9 : 0u;
    d[0] = c0; d[32] = c1; d[64] = c2; d[96 + dv] = c3; d[128 + dv] = c4;
    if (sk) {
      asm volatile("st.shared.b32 [%0], %1;\nst.shared.b32 [%0 + 128], %2;\nst.shared.b32 [%0 + 256], %3;" ::"r"(sk + rh * 384), "r"(c0), "r"(c1), "r"(c2) : "memory");
      asm volatile("st.shared.b32 [%0], %1;\nst.shared.b32 [%2 + 128], %3;\nst.shared.b32 [%2 + 256], %4;" ::"r"(sv + rh * 384), "r"(c2), "r"(sv + rh * 384 + dv * 4), "r"(c3), "r"(c4) : "memory");
    }
  }
}

template <int OFF> __device__ __forceinline__ void ld4(uint32_t* v, const void* p) {
  asm volatile("ld.relaxed.gpu.global.v4.b32 {%0,%1,%2,%3}, [%4 + %5];" : "=r"(v[0]), "=r"(v[1]), "=r"(v[2]), "=r"(v[3]) : "l"(p), "n"(OFF) : "memory");
}
template <int OFF> __device__ __forceinline__ void ld2(uint32_t* v, const void* p) {
  asm volatile("ld.relaxed.gpu.global.v2.b32 {%0,%1}, [%2 + %3];" : "=r"(v[0]), "=r"(v[1]) : "l"(p), "n"(OFF) : "memory");
}
__device__ __forceinline__ void stage_partials(const float* acc, uint32_t dst, int tid) {
  const int lane = tid & 31, row = (tid >> 5) * 16 + (lane & 15);
  const uint32_t r128 = dst + row * 128;
#pragma unroll
  for (int i = 0; i < 12; i++) {
    const float* v = acc + 8 * i;
    stsm4(r128 + (i >> 2) * 16384 + (((2 * (i & 3) + (lane >> 4)) ^ (row & 7)) << 4), pack(v[0], v[1]), pack(v[2], v[3]), pack(v[4], v[5]), pack(v[6], v[7]));
  }
#pragma unroll
  for (int d = 0; d < 4; d++) {
    const float* v = acc + 128 + 8 * (d & 1) + 2 * (d >> 1);
    asm volatile("st.shared.v2.b32 [%0], {%1,%2};" ::"r"(dst + 49152 + d * 2048 + tid * 8), "r"(pack(v[0], v[1])), "r"(pack(v[4], v[5])) : "memory");
  }
}
__device__ __forceinline__ float own_share(const float* v, int o, int q) {
  const float s0 = (q & 2) ? v[o + 2] : v[o], s1 = (q & 2) ? v[o + 10] : v[o + 8];
  return (q & 1) ? s1 : s0;
}
__device__ __forceinline__ void final_epilogue(const float* acc, const float* rem, const Params& prm, int m, int hh, int q, int tid) {
  uint32_t r[18];
#pragma unroll
  for (int i = 0; i < 16; i++) r[i] = pack(acc[2 * i] * 0.5f, acc[2 * i + 1] * 0.5f);
#pragma unroll
  for (int i = 0; i < 2; i++) {
    r[16 + i] = pack(fmaf(own_share(acc + 32, 4 * i, q), 0.5f, rem[2 * i]), fmaf(own_share(acc + 32, 4 * i + 1, q), 0.5f, rem[2 * i + 1]));
  }
  const size_t off = (size_t)(128 * m + (tid >> 5) * 16 + ((tid & 31) >> 2)) * DM + 2 * (tid & 3);
  const bool odd = tid & 1;
  uint32_t* o1 = reinterpret_cast<uint32_t*>(prm.out + off + 320 * hh + 64 * q) + (odd ? 3 : 0);
  uint32_t* o2 = reinterpret_cast<uint32_t*>(prm.out + off + 256 + 32 * hh + 16 * (q & 1) + (q >> 1) * 8 * DM) + (odd ? 3 : 0);
#pragma unroll
  for (int i = 0; i < 9; i++) {
    const uint32_t A = i < 8 ? r[4 * (i >> 1) + (i & 1)] : r[16], B = i < 8 ? r[4 * (i >> 1) + 2 + (i & 1)] : r[17];
    const uint32_t y = __shfl_xor_sync(0xffffffffu, odd ? A : B, 1);
    *reinterpret_cast<uint2*>(i < 8 ? o1 + 8 * (i >> 1) + (i & 1) * 8 * (DM / 2) : o2) = odd ? make_uint2(y, B) : make_uint2(A, y);
  }
}

__global__ void __launch_bounds__(384, 1) fused_kernel(const __grid_constant__ Params prm) {
  extern __shared__ __align__(1024) uint8_t smem[];
  constexpr uint32_t sb = 1024;
  const uint32_t bar = sb + SM_BAR;
  const int m = blockIdx.x & 15, j = blockIdx.x >> 4;
  const int cta = m * 8 + j;
  const int wr = __shfl_sync(0xffffffffu, (int)(threadIdx.x >> 5), 0);
  const int wg = wr >> 2;
  const int lane = threadIdx.x & 31;
  STAMP(0);
  if (wg == 2 && lane == 0) {
    if (wr == 8) {
      asm volatile("prefetch.tensormap [%0];" ::"l"(&prm.xm) : "memory");
#pragma unroll
      for (int c = 0; c < 9; c++) mbar_init(bar + 8 * (B_X + c), 1);
#pragma unroll
      for (int c = 0; c < 9; c++) mbar_expect(bar + 8 * (B_X + c), 16384);
      asm volatile("fence.proxy.async.shared::cta;" ::: "memory");
#pragma unroll
      for (int c = 0; c < 3; c++) tma2d(sb + SM_XN + c * 16384, &prm.xm, bar + 8 * (B_X + c), 64 * c, 128 * m);
    } else {
      if (wr == 9) {
#pragma unroll
        for (int i = 0; i < 8; i++) mbar_init(bar + 8 * (B_F + i), 2);
#pragma unroll
        for (int i = 0; i < 3; i++) mbar_init(bar + 8 * (B_QF + i), 1);
      } else if (wr == 10) {
#pragma unroll
        for (int i = 0; i < 8; i++) mbar_init(bar + 8 * (B_E + i), 8);
#pragma unroll
        for (int i = 0; i < 3; i++) mbar_init(bar + 8 * (B_QE + i), 8);
      } else {
#pragma unroll
        for (int i = B_SK1; i <= B_SP; i++) mbar_init(bar + 8 * i, 8);
        mbar_init(bar + 8 * B_OL, 1); mbar_init(bar + 8 * B_RX, 1);
        mbar_init(bar + 8 * B_NR, 4); mbar_init(bar + 8 * (B_NR + 1), 4);
        asm volatile("st.shared.u32 [%0], 0;" ::"r"(sb + SM_BAD) : "memory");
        if ((uint32_t)__cvta_generic_to_shared(smem) != sb || (sb & 1023)) asm volatile("trap;");
      }
      asm volatile("fence.proxy.async.shared::cta;" ::: "memory");
    }
  }
  if (wr == 0) {
    const uint32_t one = (lane >> 3) == (lane & 3) ? ((lane & 4) ? 0x3f800000u : 0x00003f80u) : 0u;
    asm volatile("st.shared.v4.b32 [%0], {%1,%2,%2,%1};" ::"r"(sb + SM_ID + lane * 16), "r"(one), "r"(0) : "memory");
  }
  __syncthreads();

  if (wg == 2) {
    asm volatile("setmaxnreg.dec.sync.aligned.u32 24;");
    const int pw = wr & 3;
    const uint32_t epoch = *(volatile uint32_t*)FLAG_EPOCH(cta);
    const int hh = j & 1;
#define ACOL(A) (320 * hh + 64 * (((j >> 1) + 1 + (A)) & 3))
    if (pw == 0) {
      if (lane == 0) {
#pragma unroll
        for (int c = 3; c < 9; c++) tma2d(sb + SM_XN + c * 16384, &prm.xm, bar + 8 * (B_X + c), 64 * c, 128 * m);
        uint64_t pol;
        asm volatile("createpolicy.fractional.L2::evict_first.b64 %0, 1.0;" : "=l"(pol));
#pragma unroll 1
        for (int kb = 0; kb < 9; kb++) {
          const int s = kb % 3;
          if (kb >= 3) mbar_wait(bar + 8 * (B_QE + s), (kb / 3 - 1) & 1);
          const uint32_t fb = bar + 8 * (B_QF + s), dst = sb + SM_RING + s * QST;
          mbar_expect(fb, QST);
#pragma unroll
          for (int p = 0; p < 3; p++) {
            tma2d_h(dst + p * 8192, &prm.wqkv64, fb, 576 * p + 72 * j + 8 * hh, 64 * kb, pol);
            tma2d(dst + 24576 + p * 1024, &prm.wqkv8, fb, 576 * p + 72 * j + 64 - 64 * hh, 64 * kb);
          }
        }
        asm volatile("st.shared.u32 [%0], %1;" ::"r"(sb + SM_TAG), "r"((epoch + 1) & 1) : "memory");
        int col = 576 * j, kr = 0;
#pragma unroll 1
        for (int n = 0; n < N_G2; n++) {
          const uint32_t fb = bar + 8 * (B_F + (n & 7)), dst = sb + SM_RING + (n & 3) * BST;
          mbar_expect(fb, BST);
          if (n >= 4) mbar_wait(bar + 8 * (B_E + ((n - 3) & 7)), ((n - 3) >> 3) & 1);
          else if (n != 2) mbar_wait(bar + 8 * (B_QE + (n == 3 ? 2 : n)), 0);
          tma2d_h(dst, &prm.wg, fb, col, kr, pol);
          tma2d_h(dst + 8192, &prm.wu, fb, col, kr, pol);
          if ((kr += 64) == 576) { kr = 0; col += 64; }
        }
        uint32_t seen = 0;
#pragma unroll 1
        for (int b = 0; b < 26; b++) {
          const int n = N_G2 + 2 * b;
          const uint32_t fb = bar + 8 * (B_F + (n & 7)), dst = sb + (b & 3) * G2ST;
          const int own = b < 10 || b == 20 || b == 21, jj = own ? j : (j ^ 1), lb = b < 10 ? b : b < 20 ? b - 10 : 10 + (b & 1), need = (3 * lb + 6) >> 2;
          if (b < 24) {
            if (b == 10 || b == 20 || b == 22) seen = 0;
            if (seen < need) { seen = flag_wait_v(FLAG_H(m * 8 + jj), 9 * epoch + need) - 9 * epoch; fence_async(); }
          } else {
            flag_wait(FLAG_O((cta & ~1) + b - 24), epoch + 1);
            fence_async();
          }
          mbar_wait(bar + 8 * (B_E + ((n - 5) & 7)), ((n - 5) >> 3) & 1);
          if (b == 0) STAMPW(16);
          mbar_expect(fb, G2ST);
          if (b < 24) {
            bulk_g2s(dst, g_H + (m * 576 + 72 * jj + 6 * lb) * 512, 12288, fb);
#pragma unroll
            for (int a = 0; a < 4; a++) tma5d(dst + 12288 + a * 6144, &prm.wd[0], fb, ACOL(a), 36 * jj + 3 * lb);
            tma5d(dst + 36864, &prm.wd[1 + hh], fb, 0, 36 * jj + 3 * lb);
          } else {
            const int r = b - 24;
            bulk_g2s(dst, g_O + ((cta & ~1) + r) * 9 * 512 + r * 1024, 12288, fb);
#pragma unroll
            for (int a = 0; a < 4; a++) tma3d(dst + 12288 + a * 6144, &prm.wo3[0], fb, ACOL(a), 4 * (j & 6) + 5 * r);
            tma3d(dst + 36864, &prm.wo3[1 + hh], fb, 0, 4 * (j & 6) + 5 * r);
          }
          if (b == 0) STAMPW(17);
        }
        mbar_wait(bar + 8 * B_SP, 0);
        mbar_expect(bar + 8 * B_OL, 49152 + 32768);
        tma2d(sb + SM_RES, &prm.xm, bar + 8 * B_OL, ACOL(3), 128 * m);
        __nanosleep(200);
        tma2d(sb + SM_RES + 16384, &prm.xm, bar + 8 * B_OL, 256 + 32 * hh, 128 * m);
#pragma unroll 1
        for (int i = 0; i < 4; i++) {
          __nanosleep(200);
          tma3d(sb + SM_LB + i * 4096, &prm.wo2[0], bar + 8 * B_OL, ACOL(3), 8 * i + 3);
          tma3d(sb + SM_LB + 24576 + i * 4096, &prm.wo2[1 + hh], bar + 8 * B_OL, 0, 8 * i + 3);
          tma3d(sb + SM_LB + 16384 + i * 2048, &prm.wo16[0], bar + 8 * B_OL, ACOL(3), 8 * i);
          tma3d(sb + SM_LB + 40960 + i * 2048, &prm.wo16[1 + hh], bar + 8 * B_OL, 0, 8 * i);
        }
      }
    } else if (pw == 1) {
      if (lane == 0) {
        const int hx = hh * 3;
        int u = 0, kslot = 0, vrow = 0, kb = 0;
#pragma unroll 1
        for (int n = 0; n <= N_END; n++) {
          const uint32_t fb = bar + 8 * (B_F + (n & 7)), dst = n < N_AO ? sb + SM_KV + kslot * KVST : sb + SM_KV2 + (n - N_AO) * KVST;
          const bool att = n >= N_G2 || (n >= NG0 && kb != 0);
          if (++kb == 9) kb = 0;
          if (n >= N_AO) mbar_wait(bar + 8 * (B_E + ((n - 7) & 7)), ((n - 7) >> 3) & 1);
          mbar_expect(fb, !att || u < 2 ? 0 : (u == 2 || u == 128) ? KVST / 2 : KVST);
          if (n >= N_AO || (n > N_G2 && !(n & 1))) mbar_expect(fb, 0);
          if (u == 2 && att) { flag_wait(FLAG_KV(0, j), 16 * epoch + 16); fence_async(); STAMPW(18); }
          if (n >= 4 && n < N_AO) mbar_wait(bar + 8 * (B_E + ((n - 3) & 7)), ((n - 3) >> 3) & 1);
          if (att) {
            const int krow = (4 * j + ((u >> 5) ^ hx)) * 256 + ((u + 2 * m) & 31) * 8;
            if (u >= 2 && u < 128) tma2d(dst, &prm.kv, fb, 0, krow);
            if (u >= 3) tma2d(dst + 3072, &prm.kv, fb, 128, vrow);
            vrow = krow; u++;
            if (++kslot == 3) kslot = 0;
            if (u == 16) { flag_wait(FLAG_KV(1, j), 16 * epoch + 16); fence_async(); }
          }
        }
      }
    } else if (pw == 2) {
      if (lane == 0) {
#pragma unroll 1
        for (int i = 1; i < 18; i++) asm volatile("prefetch.tensormap [%0];" ::"l"(&prm.xm + i) : "memory");
        mbar_wait(bar + 8 * B_SK1, 0);
        STAMPW(22);
        fence_gpu(); flag_add(FLAG_KV(0, j));
        STAMPW(20);
        mbar_wait(bar + 8 * B_SK2, 0);
        fence_gpu(); flag_add(FLAG_KV(1, j));
#pragma unroll 1
        for (int t = 0; t < 9; t++) { mbar_wait(bar + 8 * B_SH, t & 1); __nanosleep(1000); fence_gpu(); flag_add(FLAG_H(cta)); }
        mbar_wait(bar + 8 * B_SO1, 0);
        fence_gpu(); flag_add(FLAG_O(cta));
      }
    } else {
      mbar_wait(bar + 8 * (B_X + 6), 0);
#pragma unroll 1
      for (int i = lane; i < 122; i += 32) pf_line(prm.pwqkv + (size_t)min(i * 128 + cta, 15551) * 64);
      mbar_wait(bar + 8 * (B_QE + 1), 0);
#pragma unroll 1
      for (int t = -3; t < 9; t++) {
        if (t >= 0) { mbar_wait(bar + 8 * B_SH, t & 1); __nanosleep(1500); }
        if (t < 6) {
#pragma unroll 1
          for (int i = lane; i < 72; i += 32) pf_line((i >= 36 ? prm.pwu : prm.pwg) + (size_t)(36 * m + (i >= 36 ? i - 36 : i)) * FF + 576 * j + 64 * (t + 3));
        }
        if ((t == 2 || t == 6 || t == 8)) {
          const uint32_t* kv = g_KV + (size_t)(4 * j + ((t == 2 ? 1 : t == 6 ? 2 : 3) ^ (hh * 3))) * SEQ * 20 + m * 2560;
#pragma unroll 1
          for (int i = lane; i < 80; i += 32) pf_line(kv + i * 32);
        }
        if (t >= 7) {
          const uint32_t* h = g_H + (m * 576 + 72 * j + 30 * (t - 7)) * 512;
#pragma unroll 1
          for (int i = lane; i < 480; i += 32) pf_line(h + i * 32);
        }
        if (t >= 5) {
#pragma unroll 1
          for (int i = lane; i < 81; i += 32) {
            const int l = (2 * m + hh) * 81 + i, r = l / 9;
            pf_line(prm.pwd + (size_t)(1152 * (j >> 1) + 576 * (r / 144) + 144 * (t - 5) + r % 144) * DM + 64 * (l % 9));
          }
        }
      }
      if (cta * 41 + lane < 5184) pf_line(prm.pwo + (size_t)(cta * 41 + lane) * 64);
      if (lane < 9 && cta * 41 + 32 + lane < 5184) pf_line(prm.pwo + (size_t)(cta * 41 + 32 + lane) * 64);
      if (lane == 0) {
      mbar_wait(bar + 8 * B_SP, 0);
      const int q = j >> 1;
#pragma unroll 1
      for (int i = 0; i < 14; i++) {
        bulk_s2g(g_P + cta * 3584 + i * 256, sb + SM_SEND + i * 4096, 4096);
        asm volatile("cp.async.bulk.commit_group;\ncp.async.bulk.wait_group.read 4;" ::: "memory");
      }
      asm volatile("cp.async.bulk.wait_group 0;" ::: "memory");
      fence_gpu();
      flag_add(FLAG_P(cta));
      STAMPW(15);
      mbar_expect(bar + 8 * B_RX, 55296);
#pragma unroll 1
      for (int a = 0; a < 3; a++) {
        const int src = m * 8 + 2 * ((q + 3 - a) & 3) + hh;
        flag_wait(FLAG_P(src), epoch + 1);
        fence_async();
        bulk_g2s(sb + SM_RECV + a * 16384, g_P + src * 3584 + a * 1024, 16384, bar + 8 * B_RX);
        bulk_g2s(sb + SM_RECV + 49152 + a * 2048, g_P + src * 3584 + 3072 + q * 128, 2048, bar + 8 * B_RX);
      }
      STAMPW(25);
      *FLAG_EPOCH(cta) = epoch + 1;
      }
    }
  } else {
    const int tid = threadIdx.x;
    const int t = lane & 3;
    const uint32_t l0 = lane == 0;
    const uint32_t adesc = (((sb + SM_XN + wg * 8192) & 0x3FFFF) >> 4) | LO_A;
    const uint32_t bdesc = (((sb + SM_RING) & 0x3FFFF) >> 4) | LO_B;
    const uint32_t kdesc0 = (((sb + SM_KV) & 0x3FFFF) >> 4) | LO_K;
    const int hx = (j & 1) ? 3 : 0;
    float accA[64], accB[64];
    uint32_t qn[6];
    Att a;
    uint32_t gs = 0, s8 = 0, fph = 0;
#define G1_ISSUE(ACC, AD, BD) _Pragma("unroll") for (int k = 0; k < 4; k++) wg_ss_n128<HI_SW128, HI_SW128>(ACC, (AD) + k * 2, (BD) + k * 128);
#define G1_ISSUE_Z(ACC, BD)                                                                                    \
  wg_ss_z_n128<HI_SW128, HI_SW128>(ACC, adesc, BD);                                                            \
  _Pragma("unroll") for (int k = 1; k < 4; k++) wg_ss_n128<HI_SW128, HI_SW128>(ACC, adesc + k * 2, (BD) + k * 128);
#define F_BAR (bar + 8 * B_F + 8 * s8)
#define F_PH fph
#define RELEASE() mbar_arrive_if(bar + 8 * B_E + 8 * s8, l0);
#define NEXT_SLOT() { gs++; fph ^= s8 == 7; s8 = s8 == 7 ? 0 : s8 + 1; }
#define NEXT_B() bd = bd == bdesc + 3072 ? bdesc : bd + 1024;
#define G1_ONLY() { mbar_wait(F_BAR, F_PH); wg_fence(); G1_ISSUE(accA, adesc + gs * 1024, bdesc + (gs & 3) * 1024) wg_commit(); wg_wait<1>(); RELEASE() NEXT_SLOT() }
    {
      const int lr = wr * 16 + (lane & 15);
      uint32_t ra[4];
#pragma unroll
      for (int k = 0; k < 4; k++) ra[k] = sb + SM_XN + lr * 128 + (((2 * k + (lane >> 4)) ^ (lr & 7)) << 4);
      asm volatile("setmaxnreg.inc.sync.aligned.u32 240;");
      float aq[96], ar[12];
#pragma unroll
      for (int i = 0; i < 96; i++) aq[i] = __int_as_float(lane >> 5);
#pragma unroll
      for (int i = 0; i < 12; i++) ar[i] = __int_as_float(lane >> 5);
      pin<96>(aq); pin<12>(ar);
      float cs[2][4] = {}, q0 = 0.f, q1 = 0.f, q2 = 0.f, q3 = 0.f;
#pragma unroll 1
      for (int c = 0; c < 9; c++) {
        mbar_wait(bar + 8 * (B_X + c), 0);
        uint32_t v[4][4];
#pragma unroll
        for (int k = 0; k < 4; k++) ldsm4(v[k], ra[k] + c * 16384);
#pragma unroll
        for (int k = 0; k < 4; k++) {
          mma_ones(cs[k & 1], v[k]);
#pragma unroll
          for (int e = 0; e < 4; e += 2) {
            const float x0 = bf_lo(v[k][e]), x1 = bf_hi(v[k][e]), y0 = bf_lo(v[k][e + 1]), y1 = bf_hi(v[k][e + 1]);
            q0 = fmaf(x0, x0, q0); q1 = fmaf(x1, x1, q1); q2 = fmaf(y0, y0, q2); q3 = fmaf(y1, y1, q3);
          }
        }
      }
      STAMP(11);
      const float mean0 = (cs[0][0] + cs[1][0]) * (1.f / 576.f), mean1 = (cs[0][2] + cs[1][2]) * (1.f / 576.f);
      q0 += q1; q2 += q3;
      q0 += __shfl_xor_sync(0xffffffffu, q0, 1); q2 += __shfl_xor_sync(0xffffffffu, q2, 1);
      q0 += __shfl_xor_sync(0xffffffffu, q0, 2); q2 += __shfl_xor_sync(0xffffffffu, q2, 2);
      float var0 = fmaf(q0, 1.f / 576.f, -mean0 * mean0), var1 = fmaf(q2, 1.f / 576.f, -mean1 * mean1);
      if (__any_sync(0xffffffffu, !(mean0 * mean0 <= 8.f * var0) || !(mean1 * mean1 <= 8.f * var1))) {
        q0 = q2 = 0.f;
#pragma unroll 1
        for (int i = 0; i < 36; i++) {
          uint32_t v[4];
          ldsm4(v, ((ra[0] + (i >> 2) * 16384) ^ ((i & 3) << 5)));
#pragma unroll
          for (int e = 0; e < 4; e += 2) {
            const float x0 = bf_lo(v[e]) - mean0, x1 = bf_hi(v[e]) - mean0, y0 = bf_lo(v[e + 1]) - mean1, y1 = bf_hi(v[e + 1]) - mean1;
            q0 = fmaf(x0, x0, fmaf(x1, x1, q0)); q2 = fmaf(y0, y0, fmaf(y1, y1, q2));
          }
        }
        q0 += __shfl_xor_sync(0xffffffffu, q0, 1); q2 += __shfl_xor_sync(0xffffffffu, q2, 1);
        q0 += __shfl_xor_sync(0xffffffffu, q0, 2); q2 += __shfl_xor_sync(0xffffffffu, q2, 2);
        var0 = q0 * (1.f / 576.f); var1 = q2 * (1.f / 576.f);
      }
      const float inv0 = rcp_fast(bf_round(sqrt_fast(bf_round(bf_round(var0) + 1e-5f)))), inv1 = rcp_fast(bf_round(sqrt_fast(bf_round(bf_round(var1) + 1e-5f))));
      const uint32_t mb0 = pack(mean0, mean0), mb1 = pack(mean1, mean1);
      const uint32_t h0 = pack(inv0, inv0), h1 = pack(inv1, inv1);
      const uint32_t e0 = pack(inv0 - bf_lo(h0), inv0 - bf_lo(h0)), e1 = pack(inv1 - bf_lo(h1), inv1 - bf_lo(h1));
      uint32_t v[4][4], xn[4][4];
#pragma unroll
      for (int k = 0; k < 4; k++) ldsm4(v[k], ra[k]);
      STAMP(1);
      const uint32_t rdesc = (((sb + SM_RING + 24576) & 0x3FFFF) >> 4) | LO_R;
      uint32_t s = 0, ph = 0;
#define QKV_STEP(XN, KB, LAST)                                                                                 \
  {                                                                                                            \
    _Pragma("unroll") for (int k = 0; k < 4; k++) {                                                            \
      XN[k][0] = bscale2(bsub2(v[k][0], mb0), h0, e0); XN[k][1] = bscale2(bsub2(v[k][1], mb1), h1, e1);        \
      XN[k][2] = bscale2(bsub2(v[k][2], mb0), h0, e0); XN[k][3] = bscale2(bsub2(v[k][3], mb1), h1, e1);        \
    }                                                                                                          \
    pin<16>(&XN[0][0]);                                                                                        \
    mbar_wait(bar + 8 * B_QF + 8 * s, ph);                                                                     \
    wg_fence();                                                                                                \
    _Pragma("unroll") for (int k = 0; k < 4; k++) {                                                            \
      wg_rs_n192<HI_SW128>(aq, XN[k][0], XN[k][1], XN[k][2], XN[k][3], bdesc + s * (QST >> 4) + k * 128);      \
      wg_rs_n24<HI_R>(ar, XN[k][0], XN[k][1], XN[k][2], XN[k][3], rdesc + s * (QST >> 4) + k * 16);            \
    }                                                                                                          \
    wg_commit();                                                                                               \
    _Pragma("unroll") for (int k = 0; k < 4; k++) stsm4(ra[k] + (KB) * 16384, XN[k][0], XN[k][1], XN[k][2], XN[k][3]); \
    if (!(LAST)) { _Pragma("unroll") for (int k = 0; k < 4; k++) ldsm4(v[k], ra[k] + ((KB) + 1) * 16384); }    \
    else { asm volatile("fence.proxy.async.shared::cta;" ::: "memory"); __syncwarp(); mbar_arrive_if(bar + 8 * B_NR + 8 * wg, l0); } \
    wg_wait<1>();                                                                                              \
    mbar_arrive_if(bar + 8 * B_QE + (s == 0 ? 16 : 8 * s - 8), l0 & ((KB) > 0));                               \
    if (++s == 3) { s = 0; ph ^= 1; }                                                                          \
  }
      uint32_t xm[4][4];
#pragma unroll 1
      for (int kb = 0; kb < 8; kb += 2) {
        QKV_STEP(xn, kb, false)
        QKV_STEP(xm, kb + 1, false)
      }
      QKV_STEP(xn, 8, true)
      wg_wait<0>();
      mbar_arrive_if(bar + 8 * (B_QE + 2), l0);
      pin<96>(aq); pin<12>(ar);
      STAMP(2);
      uint32_t* kvp = g_KV + (size_t)(4 * j) * SEQ * 20 + (16 * m + 2 * wr) * 160 + lane;
      uint32_t pk[2][9][2];
#pragma unroll
      for (int p = 0; p < 2; p++)
#pragma unroll
        for (int i = 0; i < 9; i++) {
          const float* src = i < 8 ? &aq[(8 * (p + 1) + i) * 4] : &ar[4 * (p + 1)];
          pk[p][i][0] = pack(src[0], src[1]); pk[p][i][1] = pack(src[2], src[3]);
        }
      const uint32_t sk = sb + SM_KV + wg * KVST + (wr & 3) * 768 + lane * 4;
      mbar_wait(bar + 8 * (B_QE + 2), 0);
      if (hx) {
#pragma unroll
        for (int p = 0; p < 2; p++) { rotate9(pk[p]); }
        store_kv_head<3>(pk, kvp, lane, sk, sk + KVST + 3072);
      } else store_kv_head<0>(pk, kvp, lane, sk, sk + KVST + 3072);
      asm volatile("fence.proxy.async.shared::cta;" ::: "memory");
      __syncwarp();
      mbar_arrive_if(bar + 8 * B_SK1, l0);
      mbar_arrive_if(bar + 8 * B_LK, l0);
      STAMP(3);
      mbar_wait(bar + 8 * B_NR + 8 * wg, 0);
      mbar_wait(bar + 8 * B_F, 0);
      wg_fence();
      G1_ISSUE_Z(accA, bdesc)
      wg_commit();
      RELEASE()
      NEXT_SLOT()
      mbar_wait(F_BAR, F_PH);
      wg_fence();
      G1_ISSUE(accA, adesc + 1024, bdesc + 1024)
      wg_commit();
      uint32_t pq[9][2];
#pragma unroll
      for (int i = 0; i < 9; i++) {
        const float* src = i < 8 ? &aq[i * 4] : &ar[0];
        pq[i][0] = bscale2(pack(src[0], src[1]), QS_HI, QS_LO); pq[i][1] = bscale2(pack(src[2], src[3]), QS_HI, QS_LO);
      }
      if (hx) rotate9(pq);
      pin<18>(&pq[0][0]);
      wg_wait<1>();
      RELEASE()
      NEXT_SLOT()
      G1_ONLY()
      mbar_wait(F_BAR, F_PH);
      wg_fence();
      G1_ISSUE(accA, adesc + 3 * 1024, bdesc + 3 * 1024)
      wg_commit();
      if (hx) store_kv_head<0>(pk, kvp, lane); else store_kv_head<3>(pk, kvp, lane);
      store_kv_head<1>(pk, kvp, lane);
      store_kv_head<2>(pk, kvp, lane);
      __syncwarp();
      mbar_arrive_if(bar + 8 * B_SK2, l0);
      wg_wait<1>();
      RELEASE()
      NEXT_SLOT()
      mbar_wait(F_BAR, F_PH);
      wg_fence();
      G1_ISSUE(accA, adesc + 4 * 1024, bdesc)
      wg_commit();
      uint32_t qf[4][6];
#pragma unroll
      for (int hp = 0; hp < 4; hp++) {
        const bool up = t < hp;
        qf[hp][0] = up ? pq[2 * hp + 1][0] : pq[2 * hp][0]; qf[hp][1] = up ? pq[2 * hp + 1][1] : pq[2 * hp][1];
        qf[hp][2] = up ? pq[2 * hp + 2][0] : pq[2 * hp + 1][0]; qf[hp][3] = up ? pq[2 * hp + 2][1] : pq[2 * hp + 1][1];
        qf[hp][4] = t == hp ? pq[2 * hp + 2][0] : 0u; qf[hp][5] = t == hp ? pq[2 * hp + 2][1] : 0u;
      }
      if (hx) {
        store_q(qf[0], cta, 0, tid); store_q(qf[1], cta, 1, tid);
#pragma unroll
        for (int i = 0; i < 6; i++) { a.q[i] = qf[3][i]; qn[i] = qf[2][i]; }
      } else {
        store_q(qf[2], cta, 2, tid); store_q(qf[3], cta, 3, tid);
#pragma unroll
        for (int i = 0; i < 6; i++) { a.q[i] = qf[0][i]; qn[i] = qf[1][i]; }
      }
      a.q[6] = __shfl_sync(0xffffffffu, lane, 0); a.q[7] = __shfl_sync(0xffffffffu, lane >> 1, 1);
#pragma unroll
      for (int i = 0; i < 16; i++) a.p[i] = 0;
#pragma unroll
      for (int i = 0; i < 12; i++) a.o[i] = 0.f;
      pin<16>(a.p); pin<12>(a.o); pin<8>(a.q);
      wg_wait<1>();
      RELEASE()
      NEXT_SLOT()
    }
    static_assert(NG0 == 5, "item boundaries must fall into even F tiles / even GEMM2 slots");
    STAMP(4);
    mbar_wait(bar + 8 * B_LK, 0);
    mbar_wait(F_BAR, F_PH);
    STAMP(23);
    uint32_t kd = kdesc0;
    uint32_t it = 0;
    uint32_t ox0 = 0, ox1 = 0;
    uint32_t* hdst = g_H + ((m * 576 + 72 * j + (t >> 1)) * 128 + 16 * wr + (lane >> 2)) * 4 + 2 * (t & 1);
    uint32_t ad = adesc + NG0 * 1024, bd = bdesc + (gs & 3) * 1024;

#define ITEM_FIRST()                                                                                           \
  {                                                                                                            \
    pin<12>(a.o);                                                                                              \
    if (it != 0) {                                                                                             \
      uint32_t w[4];                                                                                           \
      o_normalise(a.o, w, ox0, ox1, ((it >> 5) - 1) ^ hx, lane, sb + SM_BAD, wr);                              \
      uint32_t* d = g_O + cta * 9 * 512 + (((it >> 5) - 1) ^ hx) * 1024 + wr * 64 + lane;                      \
      d[0] = w[0]; d[32] = w[1]; d[512] = w[2]; d[544] = w[3];                                                 \
    }                                                                                                          \
    if (it == 96) mbar_arrive_if(bar + 8 * B_SO1, l0 & (bad_heads(sb + SM_BAD, wr) == 0));                     \
    first_tile(a, (it >> 5) ^ hx, lane);                                                                       \
  }
#define KV_ADVANCE() { kd = kd == kdesc0 + 768 ? kdesc0 : kd + 384; }
#define SOFTMAX_NEXT() { softmax_a(a); mbar_wait(F_BAR, F_PH); softmax_b(a); }
#define EPI_STEP(ACCN, ACCO)                                                                                   \
  {                                                                                                            \
    wg_fence();                                                                                                \
    G1_ISSUE_Z(ACCN, bd)                                                                                       \
    wg_commit();                                                                                               \
    wg_wait<1>();                                                                                              \
    pin<64>(ACCO);                                                                                             \
    RELEASE()                                                                                                  \
    NEXT_SLOT()                                                                                                \
    ad = adesc + 1024; NEXT_B()                                                                                \
    const uint32_t ok = mbar_test(F_BAR, F_PH);                                                                \
    h_epilogue(ACCO, hdst);                                                                                    \
    hdst += 4096;                                                                                              \
    __syncwarp();                                                                                              \
    mbar_arrive_if(bar + 8 * B_SH, l0);                                                                        \
    if (__builtin_expect(!ok, 0)) mbar_wait(F_BAR, F_PH);                                                                                            \
  }
#define ATT_LOOP1(ACC, ITEMS)                                                                                  \
  do {                                                                                                         \
    wg_fence();                                                                                                \
    issue_att(a, kd);                                                                                          \
    wg_commit();                                                                                               \
    G1_ISSUE(ACC, ad, bd)                                                                                      \
    wg_commit();                                                                                               \
    wg_wait<1>();                                                                                              \
    pin<32>(a.s);                                                                                              \
    RELEASE()                                                                                                  \
    TRACE()                                                                                                    \
    if (ITEMS) { if (__builtin_expect(((it + 1) & 31) < 2, 0)) { if (it & 1) { store_q(a.q, cta, (it >> 5) ^ hx, tid); _Pragma("unroll") for (int i = 0; i < 6; i++) asm volatile("mov.b32 %0, %1;" : "=r"(a.q[i]) : "r"(qn[i])); } else { if (it == 64) fetch_q(qn, cta, 3 ^ hx, tid); ITEM_FIRST() } } } \
    NEXT_SLOT() it++;                                                                                                \
    KV_ADVANCE()                                                                                               \
    ad += 1024; NEXT_B()                                                                                       \
    SOFTMAX_NEXT()                                                                                             \
    pin<8>(a.q);                                                                                               \
  } while ((int)(ad - adesc) < 9 * 1024);
#pragma unroll 1
    for (int pr = 0;; pr++) {
      ATT_LOOP1(accA, true)
      if (pr == 4) break;
      if (pr == 2) STAMP(29);
      EPI_STEP(accB, accA)
      if (pr == 2) STAMP(30);
      ATT_LOOP1(accB, false)
      if (pr == 2) STAMP(31);
      if (pr == 3) fetch_q(qn, cta, 2 ^ hx, tid);
      EPI_STEP(accA, accB)
      if (pr == 2) STAMP(21);
      if (pr == 3) STAMP(14);
    }
    STAMP(5);
    wg_wait<0>();
    pin<64>(accA);
    h_epilogue(accA, hdst);
    __syncwarp();
    mbar_arrive_if(bar + 8 * B_SH, l0);
    mbar_wait(bar + 8 * B_E, 0);
    asm volatile("st.shared.v4.b32 [%0], {%1,%2,%3,%4};\nst.shared.v2.b32 [%5], {%6,%7};" ::"r"(sb + SM_QS + tid * 16), "r"(qn[0]), "r"(qn[1]), "r"(qn[2]), "r"(qn[3]),
                 "r"(sb + SM_QS + 4096 + tid * 8), "r"(qn[4]), "r"(qn[5]) : "memory");
    STAMP(6);
    STAMP(12);

    float acc2[144];
    const uint32_t a2desc = (((sb + wg * 1024) & 0x3FFFF) >> 4) | LO_O;
    const uint32_t b2desc = (((sb + 12288) & 0x3FFFF) >> 4) | LO_B48;
    ad = a2desc; bd = b2desc;
#define G2_LO(K) wg_ss_n128<HI_O, HI_SW128>(acc2, ad + (K) * 256, bd + (K) * 128);
#define G2_HI(K) wg_ss_n160<HI_O, HI_SW128>(acc2 + 64, ad + (K) * 256, bd + (K) * 128 + 768);
#define ATT_PAIR(ZERO)                                                                                         \
  {                                                                                                            \
    wg_fence();                                                                                                \
    issue_att(a, kd);                                                                                          \
    wg_commit();                                                                                               \
    if (ZERO) { wg_ss_z_n128<HI_O, HI_SW128>(acc2, ad, bd); wg_ss_z_n160<HI_O, HI_SW128>(acc2 + 64, ad, bd + 768); } \
    else { G2_LO(0) G2_HI(0) }                                                                                 \
    G2_LO(1)                                                                                                   \
    wg_commit();                                                                                               \
    wg_wait<1>();                                                                                              \
    pin<32>(a.s);                                                                                              \
    RELEASE()                                                                                                  \
    TRACE()                                                                                                    \
    if (!(ZERO)) { if (__builtin_expect(gs == N_G2 + 96 - IT_G2, 0)) ITEM_FIRST() }                                    \
    NEXT_SLOT() it++;                                                                                                \
    KV_ADVANCE()                                                                                               \
    SOFTMAX_NEXT()                                                                                             \
    pin<8>(a.q);                                                                                               \
    wg_fence();                                                                                                \
    issue_att(a, kd);                                                                                          \
    wg_commit();                                                                                               \
    G2_HI(1) G2_LO(2) G2_HI(2)                                                                                 \
    wg_commit();                                                                                               \
    wg_wait<1>();                                                                                              \
    pin<32>(a.s);                                                                                              \
    RELEASE()                                                                                                  \
    TRACE()                                                                                                    \
    if (!(ZERO) && __builtin_expect(gs == N_G2 + 95 - IT_G2, 0)) {                                                     \
      const int ft = fresh_tid();                                                                              \
      asm volatile("ld.shared.v4.b32 {%0,%1,%2,%3}, [%6];\nld.shared.v2.b32 {%4,%5}, [%7];" : "=r"(a.q[0]), "=r"(a.q[1]), "=r"(a.q[2]), "=r"(a.q[3]), \
                   "=r"(a.q[4]), "=r"(a.q[5]) : "r"(sb + SM_QS + ft * 16), "r"(sb + SM_QS + 4096 + ft * 8) : "memory"); \
    }                                                                                                          \
    NEXT_SLOT() it++;                                                                                                \
    KV_ADVANCE()                                                                                               \
    ad = ad == a2desc + 3 * 2688 ? a2desc : ad + 2688; bd = ad + (b2desc - a2desc);                                \
    SOFTMAX_NEXT()                                                                                             \
    pin<8>(a.q);                                                                                               \
  }
    ATT_PAIR(true)
#pragma unroll 1
    for (int half = 0; half < 2; half++) {
      const uint32_t stop = half ? N_AO : N_G2 + 46;
      do ATT_PAIR(false) while (gs != stop);
      if (!half) {
        const uint32_t bad = bad_heads(sb + SM_BAD, wr);
        if (bad) { repair_rows(cta, wr, bad, 3 ^ hx, false); mbar_arrive_if(bar + 8 * B_SO1, l0); }
      }
    }
    STAMP(13);
    wg_wait<0>();
    pin<144>(acc2);
    mbar_wait(bar + 8 * (B_E + 1), 0);
    stage_partials(acc2, sb + SM_SEND, fresh_tid());
    asm volatile("fence.proxy.async.shared::cta;" ::: "memory");
    __syncwarp();
    mbar_arrive_if(bar + 8 * B_SP, l0);
    static_assert(N_END - N_AO == 8, "SM_KV2 layout");
    kd = (((sb + SM_KV2) & 0x3FFFF) >> 4) | LO_K;
    do {
      wg_fence();
      issue_att(a, kd);
      wg_commit();
      wg_wait<0>();
      pin<32>(a.s);
      RELEASE()
      TRACE()
      NEXT_SLOT() it++;
      kd += 384;
      SOFTMAX_NEXT()
    } while (gs != N_END);
    STAMP(7);
    wg_fence();
    issue_pv(a, kd);
    wg_commit();
    int tid2, bid2;
    asm volatile("mov.u32 %0, %%tid.x;" : "=r"(tid2));
    asm volatile("mov.u32 %0, %%ctaid.x;" : "=r"(bid2));
    const int m2 = bid2 & 15, j2 = bid2 >> 4;
    uint32_t tag;
    asm volatile("ld.shared.u32 %0, [%1];" : "=r"(tag) : "r"(sb + SM_TAG) : "memory");
    wg_wait<0>();
    pin<12>(a.o);
    {
      uint32_t w[4];
      o_normalise(a.o, w, ox0, ox1, 3 ^ hx, lane, sb + SM_BAD, wr);
      ox0 = __shfl_xor_sync(0xffffffffu, ox0, 2); ox1 = __shfl_xor_sync(0xffffffffu, ox1, 2);
      const uint32_t bad = bad_heads(sb + SM_BAD, wr);
      if (bad) {
        uint32_t* d = g_O + cta * 9 * 512 + wr * 64 + lane;
        uint32_t* h = d + (3 ^ hx) * 1024;
        h[0] = w[0]; h[32] = w[1]; h[512] = w[2]; h[544] = w[3]; d[4096] = ox0; d[4128] = ox1;
        __syncwarp();
        repair_rows(cta, wr, bad, 3 ^ hx, true);
        w[0] = __ldcg(h); w[1] = __ldcg(h + 32); w[2] = __ldcg(h + 512); w[3] = __ldcg(h + 544); ox0 = __ldcg(d + 4096); ox1 = __ldcg(d + 4128);
      }
      asm volatile("st.relaxed.gpu.global.v4.b32 [%0], {%1,%2,%3,%4};" ::"l"(g_L + (m2 * 8 + j2) * 384 + tid2), "r"((w[0] & ~1u) | tag), "r"((w[1] & ~1u) | tag),
                   "r"((w[2] & ~1u) | tag), "r"((w[3] & ~1u) | tag) : "memory");
      asm volatile("st.relaxed.gpu.global.v2.b32 [%0], {%1,%2};" ::"l"(reinterpret_cast<uint2*>(g_L + (m2 * 8 + j2) * 384 + 256) + tid2), "r"((ox0 & ~1u) | tag),
                   "r"((ox1 & ~1u) | tag) : "memory");
    }
    STAMP(8);
    uint32_t la[48];
    const uint4* p4 = g_L + m2 * 8 * 384 + tid2;
    const uint2* p2 = reinterpret_cast<const uint2*>(g_L + m2 * 8 * 384 + 256) + tid2;
#define LOAD_LA2() { ld2<0>(la + 32, p2); ld2<6144>(la + 34, p2); ld2<12288>(la + 36, p2); ld2<18432>(la + 38, p2); \
                     ld2<24576>(la + 40, p2); ld2<30720>(la + 42, p2); ld2<36864>(la + 44, p2); ld2<43008>(la + 46, p2); }
#define LOAD_LA4() { ld4<0>(la, p4); ld4<6144>(la + 4, p4); ld4<12288>(la + 8, p4); ld4<18432>(la + 12, p4); \
                     ld4<24576>(la + 16, p4); ld4<30720>(la + 20, p4); ld4<36864>(la + 24, p4); ld4<43008>(la + 28, p4); }
    float fin[48];
    uint32_t id[4][4];
    {
      uint32_t id2[4][4];
#pragma unroll
      for (int k = 0; k < 4; k++) {
        asm volatile("ld.volatile.shared.v4.b32 {%0,%1,%2,%3}, [%4];" : "=r"(id[k][0]), "=r"(id[k][1]), "=r"(id[k][2]), "=r"(id[k][3])
                     : "r"(sb + SM_ID + ((wr & 3) == k ? lane : 1) * 16) : "memory");
#pragma unroll
        for (int e = 0; e < 4; e++) id2[k][e] = id[k][e] + (id[k][e] & 0x00800080u);
      }
      pin<16>(&id[0][0]); pin<16>(&id2[0][0]);
      const uint32_t xdesc = (((sb + SM_RES + wg * 8192) & 0x3FFFF) >> 4) | LO_B;
      STAMP(26);
      mbar_wait(bar + 8 * B_OL, 0);
      STAMP(27);
      wg_fence();
      wg_rsb_z_n64<HI_SW128>(fin, id2[0][0], id2[0][1], id2[0][2], id2[0][3], xdesc);
#pragma unroll
      for (int k = 1; k < 4; k++) {
        wg_rsb_n64<HI_SW128>(fin, id2[k][0], id2[k][1], id2[k][2], id2[k][3], xdesc + k * 128);
      }
      wg_commit();
    }
    STAMP(28);
    const uint32_t pdesc = (((sb + SM_RECV + wg * 8192) & 0x3FFFF) >> 4) | LO_B;
    mbar_wait(bar + 8 * B_RX, 0);
    STAMP(24);
    wg_fence();
#pragma unroll
    for (int i = 0; i < 12; i++) wg_rsb_n64<HI_SW128>(fin, id[i & 3][0], id[i & 3][1], id[i & 3][2], id[i & 3][3], pdesc + (i >> 2) * 1024 + (i & 3) * 128);
    wg_commit();
    float rem[4];
    {
      const int q = j2 >> 1, g = (tid2 & 31) >> 2;
      uint32_t u[4][2];
#pragma unroll
      for (int i = 0; i < 2; i++)
        asm volatile("ld.shared.b32 %0, [%1];" : "=r"(u[3][i]) : "r"(sb + SM_RES + 16384 + ((tid2 >> 5) * 16 + (q >> 1) * 8 + g) * 128 + (((2 * (q & 1) + i) ^ g) << 4) + (tid2 & 3) * 4) : "memory");
#pragma unroll
      for (int d = 0; d < 3; d++) asm volatile("ld.shared.v2.b32 {%0,%1}, [%2];" : "=r"(u[d][0]), "=r"(u[d][1]) : "r"(sb + SM_RECV + 49152 + d * 2048 + tid2 * 8) : "memory");
#pragma unroll
      for (int i = 0; i < 2; i++) {
        rem[2 * i] = fmaf((bf_lo(u[0][i]) + bf_lo(u[1][i])) + (bf_lo(u[2][i]) + own_share(acc2 + 128, 4 * i, q)), 0.5f, bf_lo(u[3][i]));
        rem[2 * i + 1] = fmaf((bf_hi(u[0][i]) + bf_hi(u[1][i])) + (bf_hi(u[2][i]) + own_share(acc2 + 128, 4 * i + 1, q)), 0.5f, bf_hi(u[3][i]));
      }
    }
    wg_wait<0>();
    pin<32>(fin);
#pragma unroll
    for (int i = 0; i < 32; i++) fin[i] += acc2[96 + i];
    pin<32>(fin);
    for (uint32_t tries = 0; tries < 0x400000u; tries++) {
      const uint32_t* pw = reinterpret_cast<const uint32_t*>(g_L + (m2 * 8 + (lane & 7)) * 384 + 256) + (tid2 | 31) * 2 + 1;
      uint32_t bad;
      do {
        asm volatile("ld.relaxed.gpu.global.b32 %0, [%1];" : "=r"(bad) : "l"(pw) : "memory");
      } while (!__all_sync(0xffffffffu, !((bad ^ tag) & 1)) && ++tries < 0x400000u);
      LOAD_LA4()
      LOAD_LA2()
      bad = 0;
#pragma unroll
      for (int i = 0; i < 48; i++) bad |= la[i] ^ tag;
      if (__all_sync(0xffffffffu, !(bad & 1))) break;
    }
#pragma unroll
    for (int i = 0; i < 48; i++) la[i] ^= tag;
    pin<48>(la);
    STAMP(19);
    const uint32_t ldesc = (((sb + SM_LB) & 0x3FFFF) >> 4) | LO_B;
    wg_fence();
#pragma unroll
    for (int k = 0; k < 12; k++) {
      wg_rsb_n64<HI_SW128>(fin, la[4 * k], la[4 * k + 1], la[4 * k + 2], la[4 * k + 3], ldesc + k * 128);
      if (k == 0) wg_rs_z_n32<HI_SW128>(fin + 32, la[0], la[1], la[2], la[3], ldesc + 1536);
      else wg_rs_n32<HI_SW128>(fin + 32, la[4 * k], la[4 * k + 1], la[4 * k + 2], la[4 * k + 3], ldesc + 1536 + k * 128);
    }
    wg_commit();
    wg_wait<0>();
    pin<48>(fin);
    STAMP(9);
    final_epilogue(fin, rem, prm, m2, j2 & 1, j2 >> 1, tid2);
    STAMP(10);
  }
}

typedef CUresult (*EncodeFn)(CUtensorMap*, CUtensorMapDataType, cuuint32_t, void*, const cuuint64_t*, const cuuint64_t*, const cuuint32_t*, const cuuint32_t*,
                             CUtensorMapInterleave, CUtensorMapSwizzle, CUtensorMapL2promotion, CUtensorMapFloatOOBfill);

void enc2d(EncodeFn enc, CUtensorMap* tm, const void* base, uint64_t w, uint64_t h, uint64_t pitch_elems, uint32_t bw, uint32_t bh, CUtensorMapSwizzle sw) {
  cuuint64_t dims[2] = {w, h}, str[1] = {pitch_elems * 2};
  cuuint32_t box[2] = {bw, bh}, es[2] = {1, 1};
  enc(tm, CU_TENSOR_MAP_DATA_TYPE_BFLOAT16, 2, const_cast<void*>(base), dims, str, box, es, CU_TENSOR_MAP_INTERLEAVE_NONE, sw,
      CU_TENSOR_MAP_L2_PROMOTION_L2_128B, CU_TENSOR_MAP_FLOAT_OOB_FILL_NONE);
}

}

extern "C" void kernel_launch(void* const* d_in, const int* in_sizes, int n_in, void* d_out, int out_size) {
  (void)in_sizes; (void)n_in; (void)out_size;
  const __nv_bfloat16* x = (const __nv_bfloat16*)d_in[0];
  const __nv_bfloat16* wqkv = (const __nv_bfloat16*)d_in[1];
  const __nv_bfloat16* wo = (const __nv_bfloat16*)d_in[2];
  const __nv_bfloat16* wg = (const __nv_bfloat16*)d_in[4];
  const __nv_bfloat16* wu = (const __nv_bfloat16*)d_in[5];
  const __nv_bfloat16* wd = (const __nv_bfloat16*)d_in[6];
  void* fn = nullptr;
  cudaDriverEntryPointQueryResult qr;
  cudaGetDriverEntryPoint("cuTensorMapEncodeTiled", &fn, cudaEnableDefault, &qr);
  EncodeFn enc = (EncodeFn)fn;
  void* kvp = nullptr;
  cudaGetSymbolAddress(&kvp, g_KV);
  Params p;
  enc2d(enc, &p.xm, x, DM, SEQ, DM, 64, 128, CU_TENSOR_MAP_SWIZZLE_128B);
  enc2d(enc, &p.kv, kvp, 320, 32 * 256, 320, 192, 8, CU_TENSOR_MAP_SWIZZLE_NONE);
  enc2d(enc, &p.wqkv64, wqkv, 3 * DM, DM, 3 * DM, 64, 64, CU_TENSOR_MAP_SWIZZLE_128B);
  enc2d(enc, &p.wqkv8, wqkv, 3 * DM, DM, 3 * DM, 8, 64, CU_TENSOR_MAP_SWIZZLE_NONE);
  enc2d(enc, &p.wg, wg, FF, DM, FF, 64, 64, CU_TENSOR_MAP_SWIZZLE_128B);
  enc2d(enc, &p.wu, wu, FF, DM, FF, 64, 64, CU_TENSOR_MAP_SWIZZLE_128B);
  for (int v = 0; v < 3; v++) {
    const cuuint64_t wdt = v ? 32 : DM;
    const int c0 = v ? 256 + 32 * (v - 1) : 0;
    for (int e = 0; e < 3; e++) {
      cuuint64_t d3[3] = {wdt, e == 2 ? 2u : 16u, 32}, s3[2] = {DM * 2, 18 * DM * 2};
      cuuint32_t b3[3] = {64, e == 2 ? 2u : 16u, e == 0 ? 3u : e == 1 ? 2u : 8u}, e3[3] = {1, 1, 1};
      enc(e == 0 ? &p.wo3[v] : e == 1 ? &p.wo2[v] : &p.wo16[v], CU_TENSOR_MAP_DATA_TYPE_BFLOAT16, 3, (void*)(wo + c0 + (e == 2 ? 16 * DM : 0)), d3, s3, b3, e3,
          CU_TENSOR_MAP_INTERLEAVE_NONE, CU_TENSOR_MAP_SWIZZLE_128B, CU_TENSOR_MAP_L2_PROMOTION_L2_128B, CU_TENSOR_MAP_FLOAT_OOB_FILL_NONE);
    }
    cuuint64_t dims[5] = {wdt, 2, 2, 4, FF / 16}, str[4] = {DM * 2, 8 * DM * 2, 2 * DM * 2, 16 * DM * 2};
    cuuint32_t box[5] = {64, 2, 2, 4, 3}, es[5] = {1, 1, 1, 1, 1};
    enc(&p.wd[v], CU_TENSOR_MAP_DATA_TYPE_BFLOAT16, 5, (void*)(wd + c0), dims, str, box, es, CU_TENSOR_MAP_INTERLEAVE_NONE,
        CU_TENSOR_MAP_SWIZZLE_128B, CU_TENSOR_MAP_L2_PROMOTION_L2_128B, CU_TENSOR_MAP_FLOAT_OOB_FILL_NONE);
  }
  p.x = x; p.pwqkv = wqkv; p.pwo = wo; p.pwg = wg; p.pwu = wu; p.pwd = wd;
  p.out = (__nv_bfloat16*)d_out;
  cudaFuncSetAttribute(fused_kernel, cudaFuncAttributeMaxDynamicSharedMemorySize, SM_TOTAL);
  fused_kernel<<<NCTA, 384, SM_TOTAL, cudaStreamPerThread>>>(p);
}
```
